```python
import torch

def _softmax(x, axis=-1):
    return torch.softmax(x, dim=axis)
def _gelu(x):
    return torch.nn.functional.gelu(x, approximate="tanh")
def _silu(x):
    return torch.nn.functional.silu(x)
def _sigmoid(x):
    return torch.sigmoid(x)
def _layernorm(x, axis=-1, eps=1e-5):
    m = x.mean(dim=axis, keepdim=True)
    v = x.var(dim=axis, keepdim=True, unbiased=False)
    return (x - m) / torch.sqrt(v + eps)
def _scatter_add(tgt, idx, src, axis=0):
    return tgt.clone().index_add_(axis, idx, src)
def _segment_sum(src, seg, n):
    out = torch.zeros((n,) + src.shape[1:], dtype=src.dtype)
    return out.index_add_(0, seg, src)
def _pad(x, pw):
    flat = tuple(v for pair in reversed(pw) for v in pair)
    return torch.nn.functional.pad(x, flat)

kernel_name = 'standalone__self_sup_conv_stem_wavlm__speech'

def setup_inputs():

    _w = (lambda a: (lambda t: t.to(torch.bfloat16) if t.is_floating_point() else t)(torch.as_tensor(a)))
    B, T, D, K = 2, 16000, 512, 31
    scale = (K * D) ** -0.5
    return {
        "x": _w((lambda *s: torch.randn(*s, dtype=torch.bfloat16) * 0.05)(B, T, D)),
        "w": _w((lambda *s: torch.randn(*s, dtype=torch.bfloat16) * 0.05)(K, D, D) * scale),
        "gn_gamma": _w((lambda *s: torch.randn(*s, dtype=torch.bfloat16) * 0.05)(D) * 0.1 + 1.0),
        "gn_beta": _w((lambda *s: torch.randn(*s, dtype=torch.bfloat16) * 0.05)(D) * 0.1),
    }

def reference(x, w, gn_gamma, gn_beta):
    B, T, D = x.shape
    K = w.shape[0]
    s = 2
    L = (T - K) // s + 1
    h = torch.einsum('blc,cd->bld', x[:, 0:s * L:s, :], w[0])
    for i in range(1, K):
        h = h + torch.einsum('blc,cd->bld', x[:, i:i + s * L:s, :], w[i])
    mu = torch.einsum('bld->bd', h)[:, None, :] / L
    var = torch.einsum('bld->bd', (h - mu) ** 2)[:, None, :] / L
    h = (h - mu) / torch.sqrt(var + 1e-5)
    h = h * gn_gamma[None, None, :] + gn_beta[None, None, :]
    return _gelu(h)
```

```cpp
#include <cuda_runtime.h>
#include <cuda_bf16.h>
#include <cuda.h>
#include <stdint.h>

namespace {

constexpr int kL    = 7985;
constexpr int kRows = 8000;
constexpr int kMO   = 50;
constexpr int kNT   = 160;

constexpr int V0 = 7;
constexpr int NPRE = 6;
constexpr int RX = 4;
constexpr int YSLEEP = 100;
constexpr int GP1 = 0;
constexpr int NU0 = 7;
constexpr int NU1 = 5;
constexpr int FA0 = 128;
constexpr int FA1 = 128;
constexpr int FC0 = 256;
constexpr int RW = 10;

static_assert(V0 >= 7 && RX >= 2 && RX <= 4 && RW >= V0 - 1 && RW <= 12, "rings must fit and be as deep as the look-ahead");
constexpr uint32_t HOME_MASK = 0xB;
constexpr uint32_t R_W = 64 * RX, R_Y = R_W + 22 * RW, NPAGES = 32;
static_assert(R_Y + 427 <= 32 * NPAGES, "scratch size");

__device__ __align__(1024) uint8_t g_sp[(size_t)(NPAGES + 1) * (2u << 20)];
__device__ unsigned g_tsel[32];
__device__ __forceinline__ uint32_t run_sel(uint32_t r, uint32_t group, uint32_t pmask) {
    return ((pmask >> (r >> 5)) ^ __popc(r & HOME_MASK) ^ group) & 1;
}
__device__ __forceinline__ uint32_t run_off(uint32_t r, uint32_t run, uint32_t group, uint32_t pmask) {
    return (r << 16) + 4096 + (run_sel(r, group, pmask) << 13) + (run << 14);
}
__device__ __forceinline__ unsigned* chunk_flag(uint8_t* sp, int done, int part, int chunk) {
    return reinterpret_cast<unsigned*>(sp + (4 + 3 * (chunk >> 5)) * 65536 + (done ? (part ? 15 : 13) : (part ? 0 : 14)) * 4096 + (chunk & 31) * 128);
}
__device__ __forceinline__ unsigned long long* part_sums(uint8_t* sp, int b, int db) {
    return reinterpret_cast<unsigned long long*>(sp + (8 + 2 * db + ((__popc((8 + 2 * db) & HOME_MASK) ^ b) & 1)) * 65536 + 13 * 4096);
}
__device__ unsigned g_yready[16 * 32];
__device__ __align__(256) float g_corr[16 * kNT * 64];
__device__ unsigned g_cready[4 * 32];
__device__ float g_direct[256 * 500 * 64];
__device__ unsigned long long g_dpart[2 * 256 * 64];
__device__ unsigned g_exit, g_epoch;

__device__ __forceinline__ uint32_t smem_u32(const void* p) { return (uint32_t)__cvta_generic_to_shared(p); }

__device__ __forceinline__ void mbar_init(uint32_t bar, uint32_t count) {
    asm volatile("mbarrier.init.shared::cta.b64 [%0], %1;" ::"r"(bar), "r"(count) : "memory");
}
__device__ __forceinline__ void mbar_expect_tx(uint32_t bar, uint32_t bytes) {
    asm volatile("mbarrier.arrive.expect_tx.shared::cta.b64 _, [%0], %1;" ::"r"(bar), "r"(bytes) : "memory");
}
__device__ __forceinline__ void mbar_arrive(uint32_t bar) {
    asm volatile("mbarrier.arrive.shared::cta.b64 _, [%0];" ::"r"(bar) : "memory");
}
__device__ __forceinline__ bool mbar_try(uint32_t bar, uint32_t parity) {
    uint32_t ok;
    asm volatile(
        "{\n.reg .pred p;\n"
        "mbarrier.try_wait.parity.shared::cta.b64 p, [%1], %2;\n"
        "selp.u32 %0, 1, 0, p;\n}\n"
        : "=r"(ok) : "r"(bar), "r"(parity) : "memory");
    return ok;
}
__device__ __forceinline__ bool mbar_test(uint32_t bar, uint32_t parity) {
    uint32_t ok;
    asm volatile(
        "{\n.reg .pred p;\n"
        "mbarrier.test_wait.parity.shared::cta.b64 p, [%1], %2;\n"
        "selp.u32 %0, 1, 0, p;\n}\n"
        : "=r"(ok) : "r"(bar), "r"(parity) : "memory");
    return ok;
}
__device__ __forceinline__ void mbar_wait(uint32_t bar, uint32_t parity) {
#pragma unroll 1
    for (uint32_t n = 0; n < (1u << 14); n++)
        if (mbar_try(bar, parity)) break;
}
__device__ __forceinline__ void fence_proxy_async_smem() { asm volatile("fence.proxy.async.shared::cta;" ::: "memory"); }
__device__ __forceinline__ void fence_mbar_init() { asm volatile("fence.mbarrier_init.release.cluster;" ::: "memory"); }

__device__ __forceinline__ void bulk_g2s(uint32_t dst, const void* src, uint32_t bytes, uint32_t bar) {
    asm volatile("cp.async.bulk.shared::cluster.global.mbarrier::complete_tx::bytes [%0], [%1], %2, [%3];"
                 ::"r"(dst), "l"(src), "r"(bytes), "r"(bar) : "memory");
}
__device__ __forceinline__ void bulk_g2s_ef(uint32_t dst, const void* src, uint32_t bytes, uint32_t bar) {
    asm volatile("{\n.reg .b64 pol;\ncreatepolicy.fractional.L2::evict_first.b64 pol, 1.0;\n"
                 "cp.async.bulk.shared::cluster.global.mbarrier::complete_tx::bytes.L2::cache_hint [%0], [%1], %2, [%3], pol;\n}"
                 ::"r"(dst), "l"(src), "r"(bytes), "r"(bar) : "memory");
}
__device__ __forceinline__ void tma3d_ef(uint32_t dst, const CUtensorMap* tm, int c0, int c1, int c2, uint32_t bar) {
    asm volatile("{\n.reg .b64 pol;\ncreatepolicy.fractional.L2::evict_first.b64 pol, 1.0;\n"
                 "cp.async.bulk.tensor.3d.shared::cluster.global.mbarrier::complete_tx::bytes.L2::cache_hint [%0], [%1, {%3, %4, %5}], [%2], pol;\n}"
                 ::"r"(dst), "l"(tm), "r"(bar), "r"(c0), "r"(c1), "r"(c2) : "memory");
}
__device__ __forceinline__ void tma3d(uint32_t dst, const CUtensorMap* tm, int c0, int c1, int c2, uint32_t bar) {
    asm volatile("cp.async.bulk.tensor.3d.shared::cluster.global.mbarrier::complete_tx::bytes [%0], [%1, {%3, %4, %5}], [%2];"
                 ::"r"(dst), "l"(tm), "r"(bar), "r"(c0), "r"(c1), "r"(c2) : "memory");
}
__device__ __forceinline__ void poll_ge(const unsigned* p, unsigned target) {
#pragma unroll 1
    for (uint32_t n = 0; n < (1u << 15); n++) {
        unsigned v;
        asm volatile("ld.acquire.gpu.global.u32 %0, [%1];" : "=r"(v) : "l"(p) : "memory");
        if (v >= target) break;
        __nanosleep(32);
    }
}
__device__ __forceinline__ void red_relaxed(unsigned* p) { asm volatile("red.relaxed.gpu.global.add.u32 [%0], 1;" ::"l"(p) : "memory"); }
__device__ __forceinline__ void named_arrive(int id, int n) { asm volatile("bar.arrive %0, %1;" ::"r"(id), "r"(n) : "memory"); }
__device__ __forceinline__ void named_bar(int id, int n) { asm volatile("bar.sync %0, %1;" ::"r"(id), "r"(n) : "memory"); }

__device__ __forceinline__ void wg_fence() { asm volatile("wgmma.fence.sync.aligned;" ::: "memory"); }
__device__ __forceinline__ void wg_commit() { asm volatile("wgmma.commit_group.sync.aligned;" ::: "memory"); }
template <int N> __device__ __forceinline__ void wg_wait() { asm volatile("wgmma.wait_group.sync.aligned %0;" ::"n"(N) : "memory"); }
template <int N> __device__ __forceinline__ void reg_fence(float (&d)[N]) {
#pragma unroll
    for (int i = 0; i < N; i++) asm volatile("" : "+f"(d[i])::"memory");
}

#define F4(a, i) "+f"(a[i]), "+f"(a[i + 1]), "+f"(a[i + 2]), "+f"(a[i + 3])
#define F8(a, i) F4(a, i), F4(a, i + 4)
#define F16(a, i) F8(a, i), F8(a, i + 8)

constexpr uint32_t HI128 = 0x40000040u, HI64 = 0x80000020u;
__device__ __forceinline__ uint32_t desc_lo(uint32_t addr) { return (addr >> 4) | 0x10000u; }


#define R4(a, i) "+r"(a[i]), "+r"(a[i + 1]), "+r"(a[i + 2]), "+r"(a[i + 3])
#define R8(a, i) R4(a, i), R4(a, i + 4)
template <int N> __device__ __forceinline__ void reg_fence(uint32_t (&d)[N]) {
#pragma unroll
    for (int i = 0; i < N; i++) asm volatile("" : "+r"(d[i])::"memory");
}
__device__ __forceinline__ void tma2d(uint32_t dst, const CUtensorMap* tm, int c0, int c1, uint32_t bar) {
    asm volatile("cp.async.bulk.tensor.2d.shared::cluster.global.mbarrier::complete_tx::bytes [%0], [%1, {%3, %4}], [%2];"
                 ::"r"(dst), "l"(tm), "r"(bar), "r"(c0), "r"(c1) : "memory");
}
__device__ __forceinline__ void tma4d(uint32_t dst, const CUtensorMap* tm, int c0, int c1, int c2, int c3, uint32_t bar) {
    asm volatile("cp.async.bulk.tensor.4d.shared::cluster.global.mbarrier::complete_tx::bytes [%0], [%1, {%3, %4, %5, %6}], [%2];"
                 ::"r"(dst), "l"(tm), "r"(bar), "r"(c0), "r"(c1), "r"(c2), "r"(c3) : "memory");
}
__device__ __forceinline__ bool named_bar_or(int id, int n, bool v) {
    uint32_t r;
    asm volatile("{\n.reg .pred p, q;\nsetp.ne.u32 q, %3, 0;\nbar.red.or.pred p, %1, %2, q;\nselp.u32 %0, 1, 0, p;\n}"
                 : "=r"(r) : "r"(id), "r"(n), "r"((uint32_t)v) : "memory");
    return r;
}

template <uint32_t AHI, int ACC>
__device__ __forceinline__ void wgmma_n64_ss(float (&d)[32], uint32_t da, uint32_t db) {
    asm volatile(
        "{\n.reg .pred p;\n.reg .b64 da, db;\nsetp.ne.b32 p, %36, 0;\nmov.b64 da, {%32, %34};\nmov.b64 db, {%33, %35};\n"
        "wgmma.mma_async.sync.aligned.m64n64k16.f32.bf16.bf16 "
        "{%0,%1,%2,%3,%4,%5,%6,%7,%8,%9,%10,%11,%12,%13,%14,%15,%16,%17,%18,%19,%20,%21,%22,%23,%24,%25,%26,%27,%28,%29,%30,%31},"
        "da, db, p, 1, 1, 0, 1;\n}\n"
        : F16(d, 0), F16(d, 16)
        : "r"(da), "r"(db), "n"(AHI), "n"(HI128), "n"(ACC));
}


template <int ACC>
__device__ __forceinline__ void wgmma_n56_ss(float (&d)[28], uint32_t da, uint32_t db) {
    asm volatile(
        "{\n.reg .pred p;\n.reg .b64 da, db;\nsetp.ne.b32 p, %31, 0;\nmov.b64 da, {%28, %30};\nmov.b64 db, {%29, %30};\n"
        "wgmma.mma_async.sync.aligned.m64n56k16.f32.f16.f16 "
        "{%0,%1,%2,%3,%4,%5,%6,%7,%8,%9,%10,%11,%12,%13,%14,%15,%16,%17,%18,%19,%20,%21,%22,%23,%24,%25,%26,%27},"
        "da, db, p, 1, 1, 1, 0;\n}\n"
        : F16(d, 0), F8(d, 16), F4(d, 24)
        : "r"(da), "r"(db), "n"(HI128), "n"(ACC));
}

template <int SA>
__device__ __forceinline__ void wgmma_n160_h(uint32_t (&d)[40], uint32_t da, uint32_t db) {
    asm volatile(
        "{\n.reg .pred p;\n.reg .b64 da, db;\nsetp.eq.b32 p, 0, 0;\nmov.b64 da, {%40, %43};\nmov.b64 db, {%41, %43};\n"
        "wgmma.mma_async.sync.aligned.m64n160k16.f16.f16.f16 "
        "{%0,%1,%2,%3,%4,%5,%6,%7,%8,%9,%10,%11,%12,%13,%14,%15,%16,%17,%18,%19,%20,%21,%22,%23,%24,%25,%26,%27,"
        "%28,%29,%30,%31,%32,%33,%34,%35,%36,%37,%38,%39},"
        "da, db, p, %42, 1, 1, 0;\n}\n"
        : R8(d, 0), R8(d, 8), R8(d, 16), R8(d, 24), R8(d, 32)
        : "r"(da), "r"(db), "n"(SA), "n"(HI128));
}
template <int SA>
__device__ __forceinline__ void wgmma_n160_f(float (&d)[80], uint32_t da, uint32_t db) {
    asm volatile(
        "{\n.reg .pred p;\n.reg .b64 da, db;\nsetp.eq.b32 p, 0, 0;\nmov.b64 da, {%80, %83};\nmov.b64 db, {%81, %83};\n"
        "wgmma.mma_async.sync.aligned.m64n160k16.f32.bf16.bf16 "
        "{%0,%1,%2,%3,%4,%5,%6,%7,%8,%9,%10,%11,%12,%13,%14,%15,%16,%17,%18,%19,%20,%21,%22,%23,%24,%25,%26,%27,"
        "%28,%29,%30,%31,%32,%33,%34,%35,%36,%37,%38,%39,%40,%41,%42,%43,%44,%45,%46,%47,%48,%49,%50,%51,%52,%53,%54,%55,"
        "%56,%57,%58,%59,%60,%61,%62,%63,%64,%65,%66,%67,%68,%69,%70,%71,%72,%73,%74,%75,%76,%77,%78,%79},"
        "da, db, p, %82, 1, 1, 0;\n}\n"
        : F16(d, 0), F16(d, 16), F16(d, 32), F16(d, 48), F16(d, 64)
        : "r"(da), "r"(db), "n"(SA), "n"(HI128));
}

__device__ __forceinline__ uint32_t pack_f16(float lo, float hi) {
    uint32_t r;
    asm("cvt.rn.f16x2.f32 %0, %1, %2;" : "=r"(r) : "f"(hi), "f"(lo));
    return r;
}
__device__ __forceinline__ uint32_t mul_bf16x2(uint32_t a, uint32_t b) {
    uint32_t r;
    asm("mul.rn.bf16x2 %0, %1, %2;" : "=r"(r) : "r"(a), "r"(b));
    return r;
}
__device__ __forceinline__ void sts128(uint32_t p, uint32_t a, uint32_t b, uint32_t c, uint32_t d) {
    asm volatile("st.shared.v4.b32 [%0], {%1,%2,%3,%4};" ::"r"(p), "r"(a), "r"(b), "r"(c), "r"(d) : "memory");
}
__device__ __forceinline__ uint32_t pack_bf16(float lo, float hi) {
    uint32_t r;
    asm("cvt.rn.bf16x2.f32 %0, %1, %2;" : "=r"(r) : "f"(hi), "f"(lo));
    return r;
}
__device__ __forceinline__ void stg128(void* p, uint32_t a, uint32_t b, uint32_t c, uint32_t d) {
    asm volatile("st.global.v4.b32 [%0], {%1,%2,%3,%4};" ::"l"(p), "r"(a), "r"(b), "r"(c), "r"(d) : "memory");
}
__device__ __forceinline__ void stmatrix_x4_t(uint32_t addr, uint32_t a, uint32_t b, uint32_t c, uint32_t d) {
    asm volatile("stmatrix.sync.aligned.m8n8.x4.trans.shared.b16 [%0], {%1,%2,%3,%4};"
                 ::"r"(addr), "r"(a), "r"(b), "r"(c), "r"(d) : "memory");
}

constexpr uint32_t cos64(int k, bool half) {
    constexpr uint16_t q[17] = {0x3F80, 0x3F7F, 0x3F7B, 0x3F75, 0x3F6D, 0x3F62, 0x3F55, 0x3F46, 0x3F35, 0x3F22, 0x3F0E, 0x3EF1, 0x3EC4, 0x3E95, 0x3E48, 0x3DC9, 0x0000};
    constexpr uint16_t h[17] = {0x3C00, 0x3BF6, 0x3BD9, 0x3BA8, 0x3B64, 0x3B0E, 0x3AA7, 0x3A2F, 0x39A8, 0x3913, 0x3872, 0x378B, 0x361F, 0x34A5, 0x323E, 0x2E46, 0x0000};
    k &= 63;
    if (k > 32) k = 64 - k;
    const uint16_t* t = half ? h : q;
    return k <= 16 ? t[k] : (t[32 - k] | 0x8000u);
}
constexpr uint32_t fwd_coef(int s, int p, int t) { return (p && s == 0) ? cos64(32 * t, false) : cos64(s * t - 16 * p, false); }
constexpr uint32_t inv_coef(int l, int phi) {
    const int s = phi >> 1, p = phi & 1;
    if (l >= kMO) return 0;
    const uint32_t c = s == 0 ? cos64(32 * l * p, true) : cos64(s * l + 16 * p, true);
    return (c & 0x7FFF) ? c - ((s == 0 ? 6 : 5) << 10) : 0;
}
struct Tables {
    uint32_t fwd[2048];
    uint32_t inv[2048];
};
constexpr Tables make_tables() {
    Tables t = {};
    for (int i = 0; i < 2048; i++) {
        const int row = i >> 5, tt = 8 * (((i >> 2) & 7) ^ (row & 7)) + 2 * (i & 3), s = 8 * (row >> 4) + (row & 7), p = (row >> 3) & 1;
        t.fwd[i] = fwd_coef(s, p, tt) | (fwd_coef(s, p, tt + 1) << 16);
        t.inv[i] = inv_coef(row, tt) | (inv_coef(row, tt + 1) << 16);
    }
    return t;
}
__device__ __align__(128) const Tables g_tab = make_tables();

constexpr int NCTA = 128;
constexpr int NST = 4;
constexpr int HEND = 56;
constexpr int XB = kNT * 128;
constexpr int OFF_W1 = 0, OFF_X = OFF_W1 + NST * 8192, OFF_W0 = OFF_X + 4 * XB, OFF_RAW = OFF_W0 + NST * 8192;
constexpr int OFF_STG = OFF_RAW + 32768;
constexpr int OFF_U0 = OFF_W0, OFF_U1 = OFF_X, OFF_C1 = OFF_W1, OFF_TOT = OFF_W1 + 4096, OFF_DIR = OFF_W1 + 8192;
constexpr int OFF_F = OFF_RAW + 65536;
constexpr int OFF_G = OFF_F + 8192;
constexpr int OFF_C0 = OFF_G, OFF_NRM = OFF_G + 2560, OFF_HND = OFF_NRM + 1024;
constexpr int OFF_BAR = OFF_G + 4096;
constexpr int B_FULL = 0, B_EMPTY = 8 * NST, B_SIG = 16 * NST, B_YS = B_SIG + 8 * 33, B_T2 = B_YS + 8 * 4, B_GATE = B_T2 + 8, B_RDY = B_GATE + 8 * 32,
              B_TSEL = B_RDY + 8 * 33, B_PUB = B_TSEL + 8, B_UNIT = B_PUB + 8, B_FTAB = B_UNIT + 8 * 20, B_C1 = B_FTAB + 8, B_YP = B_C1 + 8, B_END = B_YP + 8 * 4;
constexpr int OFF_TS = OFF_BAR + B_END;
constexpr int OFF_PLAN = OFF_TS + 320;
constexpr int OFF_YT = OFF_PLAN + (V0 + 65) * 8;
constexpr int OFF_GB = OFF_YT + 4 * kNT * 4;
constexpr int MAIN_SMEM = OFF_GB + 1024;
static_assert(MAIN_SMEM <= 232448 && OFF_U0 + 10 * 8192 == OFF_STG + 16384, "shared memory");
constexpr int XPC = 2 * kNT;
constexpr unsigned PROBE_NEAR = 400;

__device__ __forceinline__ uint32_t raw_slot(uint32_t sbase, uint32_t v, int wg) { return sbase + OFF_RAW + ((v & 3) * 2 + wg) * 8192; }

template <bool DC, int I>
__device__ __forceinline__ void gemm_mma(uint32_t (&a0)[40], uint32_t (&a1)[40], uint32_t dx0, uint32_t dx1, uint32_t dw) {
    constexpr int ks = I >> 2;
    const uint32_t A0 = dw + ks * 128, A1 = A0 + 256, B0 = dx0 + ks * 2, B1 = dx1 + ks * 2;
    if ((I & 3) == 0) wgmma_n160_h<1>(a0, A0, B0);
    if ((I & 3) == 1) wgmma_n160_h<1>(a1, A1, DC ? B1 : B0);
    if ((I & 3) == 2 && !DC) wgmma_n160_h<1>(a0, A1, B1);
    if ((I & 3) == 3 && !DC) wgmma_n160_h<-1>(a1, A0, B1);
}

template <bool DC, int I0, int I1>
__device__ __forceinline__ void gemm_mmas(uint32_t (&a0)[40], uint32_t (&a1)[40], uint32_t dx0, uint32_t dx1, uint32_t dw) {
    if constexpr (I0 < I1) {
        gemm_mma<DC, I0>(a0, a1, dx0, dx1, dw);
        gemm_mmas<DC, I0 + 1, I1>(a0, a1, dx0, dx1, dw);
    }
}
__device__ __forceinline__ uint32_t y_unit(uint32_t db, uint32_t tau, uint32_t b, uint32_t pmask) {
    const uint32_t n = db * kNT + tau;
    return run_off(R_Y + n / 3, n % 3, b, pmask);
}
template <int R>
__device__ __forceinline__ void store_round(const uint32_t (&a0)[40], const uint32_t (&a1)[40], uint32_t stg, int t, int wg, uint8_t* sp,
                                            int slot, uint32_t ytab, int wsw) {
    const int w = t >> 5, lane = t & 31, m = lane >> 3, i8 = lane & 7;
    constexpr int N = R == 2 ? 4 : 8;
    named_bar(2 + wg, 128);
    const uint32_t addr = stg + i8 * 256 + (m >> 1) * 128 + (((2 * w + (m & 1)) ^ i8 ^ wsw) << 4);
#pragma unroll
    for (int j = 8 * R; j < 8 * R + N; j++) stmatrix_x4_t(addr + (j - 8 * R) * 2048, a0[2 * j], a0[2 * j + 1], a1[2 * j], a1[2 * j + 1]);
    named_bar(2 + wg, 128);
    const int row = 2 * w + (lane >> 4), phi = 2 * slot + (m & 1);
    const uint32_t src = stg + row * 256 + (m & 1) * 128 + ((i8 ^ row) << 4);
    uint8_t* dst = sp + phi * 128 + ((i8 ^ (phi & 7)) << 4);
    uint32_t v[N][4], o[N];
#pragma unroll
    for (int i = 0; i < N; i++) {
        asm volatile("ld.shared.u32 %0, [%1];" : "=r"(o[i]) : "r"(ytab + (64 * R + 8 * i + row) * 4) : "memory");
        asm volatile("ld.shared.v4.b32 {%0,%1,%2,%3}, [%4];" : "=r"(v[i][0]), "=r"(v[i][1]), "=r"(v[i][2]), "=r"(v[i][3])
                     : "r"(src + i * 2048) : "memory");
    }
#pragma unroll
    for (int i = 0; i < N; i++) stg128(dst + o[i], v[i][0], v[i][1], v[i][2], v[i][3]);
}

__device__ __forceinline__ int step_k(int h) { return h < HEND ? h >> 1 : 28 + (h & 3); }
__device__ __forceinline__ int step_m(int h) { return h < HEND ? h & 1 : (h >> 2) & 1; }
constexpr uint64_t x_mask() {
    uint64_t r = 2 | (3ull << 58);
    for (int v = 2; v < 58; v++)
        if ((0x6B >> (v & 7)) & 1) r |= 1ull << v;
    return r;
}
constexpr uint64_t XMASK = x_mask();
__device__ __forceinline__ int x_round(int v, int wg) {
    return v == 0 ? wg : (v < 60 && wg != (v & 1) && ((XMASK >> v) & 1)) ? 1 + __popcll(XMASK << (63 - v)) : -1;
}
__device__ __forceinline__ int w_step(int v, int wg) {
    return v == 0 ? -1 : v < 60 ? (wg == (v & 1) ? v - 1 : -1) : v < 62 ? 2 * v - 61 + wg : (v == 62 && wg == 0) ? 63 : -1;
}
constexpr int GMAX = (64 - RW) / 2 > 31 - 2 * RX ? (64 - RW) / 2 : 31 - 2 * RX;

__device__ __forceinline__ uint32_t plan_word(int v, int wg, int cta, uint32_t gr) {
    const int r = x_round(v, wg), h = w_step(v, wg);
    if (r < 0 && h < 0) return 0;
    const bool last = v >= 60 || (v & 1) || (v > 0 && wg == 0 && x_round(v + 1, 0) < 0);
    uint32_t off, row, gate;
    if (r >= 0) {
        const int u = r * NCTA + cta, cb = u / XPC, i = u - cb * XPC, b = i >= kNT, tau = i - b * kNT;
        row = tau & 63;
        off = (((cb % RX) * 64 + b) << 16) + ((tau >> 6) << 14) + b + 2;
        gate = cb >= RX ? 2 * (cb - RX) + 2 : 0;
    } else {
        const int cp = (gr >> 2) & 15, ring = (h + RW - 64 % RW) % RW;
        row = 8 * (cp & 3) + 2 * (cp >> 2);
        off = ((ring * 22) << 16) + (ring << 12) + 4;
        gate = h >= RW ? ((h - RW + 1) >> 1) + 1 : 0;
    }
    return (off + row * 128) | ((row & 7) << 4) | (last << 3) | ((v > 60) << 24) | (gate << 26);
}

struct Xf {
    uint32_t sbase;
    uint8_t *px, *pw;
    uint32_t cx, cw;
    uint32_t xsw;
    uint32_t dw;
    uint32_t e;
    int lane;
};
__device__ __forceinline__ uint32_t plan_load(const Xf& f, uint32_t v, int wg) {
    uint32_t e;
    asm volatile("ld.shared.u32 %0, [%1];" : "=r"(e) : "r"(f.sbase + OFF_PLAN + v * 8 + wg * 4));
    return __shfl_sync(0xffffffffu, e, 0);
}
template <bool W>
__device__ __forceinline__ void unit_mma(float (&acc)[32], const Xf& f, uint32_t raw) {
    const uint32_t dB = desc_lo(raw);
    if (W) {
        const uint32_t dG = desc_lo(f.sbase + OFF_G);
        wgmma_n64_ss<HI64, 0>(acc, dG, dB);
        wgmma_n64_ss<HI64, 1>(acc, dG + 2, dB + 128);
    } else {
        const uint32_t dF = desc_lo(f.sbase + OFF_F);
        wgmma_n64_ss<HI128, 0>(acc, dF, dB);
        wgmma_n64_ss<HI128, 1>(acc, dF + 2, dB + 128);
        wgmma_n64_ss<HI128, 1>(acc, dF + 4, dB + 256);
        wgmma_n64_ss<HI128, 1>(acc, dF + 6, dB + 384);
    }
    wg_commit();
}
constexpr int DROP = 3;
__device__ __forceinline__ uint32_t pack_sp(float lo, float hi) {
    const uint32_t r = pack_f16(lo, hi);
    return DROP ? (r + (0x10001u << DROP >> 1)) & ~(((1u << DROP) - 1) * 0x10001u) : r;
}
__device__ __forceinline__ void st_quad(uint8_t* p, const float (&acc)[32], int j0) {
    stg128(p, pack_sp(acc[j0], acc[j0 + 1]), pack_sp(acc[j0 + 4], acc[j0 + 5]), pack_sp(acc[j0 + 8], acc[j0 + 9]),
           pack_sp(acc[j0 + 12], acc[j0 + 13]));
}
template <bool W>
__device__ __forceinline__ void unit_store(float (&acc)[32], const Xf& f, uint32_t e) {
    const uint32_t sel = ((W ? f.cw >> (8 + ((e >> 12) & 15)) : e ^ (f.cx >> (8 + ((e >> 22) & 3)))) & 1) << 13;
    const uint32_t o = (e & (W ? 0xFF0F80u : 0xFFFF80u)) + ((e ^ (W ? f.cw : f.cx)) & 0x70);
    uint8_t* const b = W ? f.pw : f.px;
    uint8_t *p0 = b + (o + sel), *p1 = b + ((o ^ 64) + sel);
    reg_fence(acc);
    if (W) {
        st_quad(p0, acc, 0);
        st_quad(p1, acc, 16);
        st_quad(p0 + 4096, acc, 2);
        st_quad(p1 + 4096, acc, 18);
    } else {
        const int d = 131072 + 8192 - 2 * (int)sel;
        st_quad(p0, acc, 0);
        st_quad(p1, acc, 2);
        st_quad(p0 + d, acc, 16);
        st_quad(p1 + d, acc, 18);
    }
}
__device__ __forceinline__ void unit_done(const Xf& f, uint32_t e, uint32_t v) {
    if (e & 8) {
        __syncwarp();
        if (f.lane == 0) mbar_arrive(f.sbase + OFF_BAR + B_SIG + 8 * ((v >> 1) + ((e >> 24) & 1)));
    }
}
__device__ __forceinline__ void step_wait(Xf& f, uint32_t v, int wg) {
    const uint32_t bars = f.sbase + OFF_BAR;
    if (f.e >> 26) mbar_wait(bars + B_GATE - 8 + 8 * (f.e >> 26), 0);
    mbar_wait(bars + B_FULL + 8 * (v % NST), (v / NST) & 1);
}

template <bool DC, int KIND>
__device__ __forceinline__ void gemm_step(uint32_t (&a0)[40], uint32_t (&a1)[40], float (&at)[32], Xf& f, uint32_t v, uint32_t xs, int wg, bool first) {
    const uint32_t bars = f.sbase + OFF_BAR, sb = desc_lo(f.sbase), xb = sb + OFF_X / 16 + xs * (XB / 16), raw = raw_slot(f.sbase, v, wg);
    const uint32_t dx0 = xb + f.xsw, dx1 = xb + (f.xsw ^ 4), dw = f.dw + (v % NST) * 512, e = f.e;
    wg_fence();
    if (KIND) unit_mma<KIND != 1>(at, f, raw);
    constexpr int N1 = KIND == 0 ? 2 : NPRE;
    gemm_mmas<DC, 0, N1>(a0, a1, dx0, dx1, dw);
    wg_commit();
    f.e = plan_load(f, v + 1, wg);
    wg_wait<1>();
    if (!KIND && !first && f.lane == 0) mbar_arrive(bars + B_EMPTY + 8 * ((v - 1) % NST));
    if (KIND) unit_store<KIND != 1>(at, f, e);
    if (KIND) unit_done(f, e, v);
    gemm_mmas<DC, N1, 7>(a0, a1, dx0, dx1, dw);
    if (KIND && !first && f.lane == 0) mbar_arrive(bars + B_EMPTY + 8 * ((v - 1) % NST));
    gemm_mma<DC, 7>(a0, a1, dx0, dx1, dw);
    wg_commit();
}
template <bool DC>
__device__ __forceinline__ void any_step(uint32_t (&a0)[40], uint32_t (&a1)[40], float (&at)[32], Xf& f, uint32_t v, uint32_t xs, int wg, bool first) {
    step_wait(f, v, wg);
    const uint32_t kind = (f.e >> 1) & 3;
    if (kind == 1) gemm_step<DC, 1>(a0, a1, at, f, v, xs, wg, first);
    else if (kind == 2) gemm_step<DC, 2>(a0, a1, at, f, v, xs, wg, first);
    else gemm_step<DC, 0>(a0, a1, at, f, v, xs, wg, first);
}
template <bool DC>
__device__ __forceinline__ void gemm_main(uint32_t (&a0)[40], uint32_t (&a1)[40], uint32_t (&b0)[40], uint32_t (&b1)[40], Xf& f, int wg) {
    float at[32];
#pragma unroll 1
    for (uint32_t k = 0; k < HEND / 2; k++) {
        any_step<DC>(a0, a1, at, f, V0 + 2 * k, k & 3, wg, k == 0);
        any_step<DC>(b0, b1, at, f, V0 + 2 * k + 1, k & 3, wg, false);
    }
    wg_wait<0>();
    if (f.lane == 0) mbar_arrive(f.sbase + OFF_BAR + B_EMPTY + 8 * ((V0 + HEND - 1) % NST));
}
template <bool DC>
__device__ __forceinline__ void gemm_last(uint32_t (&a0)[40], uint32_t (&a1)[40], Xf& f, int wg, int m) {
    const uint32_t bars = f.sbase + OFF_BAR, sb = desc_lo(f.sbase);
    mbar_wait(bars + B_FULL + 8 * ((V0 + HEND) % NST), ((V0 + HEND) / NST + m) & 1);
    if (2 * m + wg > 0) named_bar(3 + 2 * m + wg, 256);
#pragma unroll 1
    for (uint32_t k = 0; k < 4; k++) {
        const uint32_t v = V0 + HEND + 4 * m + k, xb = sb + OFF_X / 16 + k * (XB / 16);
        wg_fence();
        gemm_mmas<DC, 0, 8>(a0, a1, xb + f.xsw, xb + (f.xsw ^ 4), f.dw + (v % NST) * 512);
        wg_commit();
        if (k == 3) break;
        mbar_wait(bars + B_FULL + 8 * ((v + 1) % NST), ((v + 1) / NST) & 1);
        wg_wait<1>();
        if (k && f.lane == 0) mbar_arrive(bars + B_EMPTY + 8 * ((v - 1) % NST));
    }
    if (2 * m + wg < 3) named_arrive(4 + 2 * m + wg, 256);
    wg_wait<1>();
    if (f.lane == 0) mbar_arrive(bars + B_EMPTY + 8 * ((V0 + HEND + 2) % NST));
    wg_wait<0>();
    if (f.lane == 0) {
        mbar_arrive(bars + B_EMPTY + 8 * ((V0 + HEND + 3) % NST));
        if (2 * m + wg == 2) mbar_arrive(bars + B_T2);
    }
}

__device__ __forceinline__ float gelu_half(float hv) {
    float th;
    asm("tanh.approx.f32 %0, %1;" : "=f"(th) : "f"(hv * fmaf(hv * hv, 8.0f * 0.7978845608028654f * 0.044715f, 2.0f * 0.7978845608028654f)));
    return fmaf(hv, th, hv);
}
__device__ __noinline__ void direct_block(const __nv_bfloat16* __restrict__ x, const __nv_bfloat16* __restrict__ w,
                                          const __nv_bfloat16* __restrict__ gamma, const __nv_bfloat16* __restrict__ beta,
                                          __nv_bfloat16* __restrict__ out, float* sm, int b, int db, int part, uint32_t epoch) {
    float *xs = sm, *ws = sm + 64 * 17, *red = ws + 16 * 65;
    const int tid = threadIdx.x, tx = tid & 15, ty = tid >> 4, row0 = part * 500, lim = min(500, kL - row0);
    float* h = g_direct + (size_t)((b * 8 + db) * 16 + part) * (500 * 64);
    for (int l0 = 0; l0 < lim; l0 += 64) {
        float acc[4][4] = {};
        for (int k0 = 0; k0 < 31 * 512; k0 += 16) {
            named_bar(1, 256);
            for (int i = tid; i < 1024; i += 256) {
                xs[(i >> 4) * 17 + (i & 15)] = __bfloat162float(x[((size_t)b * kRows + row0 + min(l0 + (i >> 4), lim - 1)) * 1024 + k0 + (i & 15)]);
                ws[(i >> 6) * 65 + (i & 63)] = __bfloat162float(w[(size_t)(k0 + (i >> 6)) * 512 + 64 * db + (i & 63)]);
            }
            named_bar(1, 256);
            for (int k = 0; k < 16; k++)
#pragma unroll
                for (int i = 0; i < 4; i++)
#pragma unroll
                    for (int j = 0; j < 4; j++) acc[i][j] = fmaf(xs[(ty * 4 + i) * 17 + k], ws[k * 65 + tx * 4 + j], acc[i][j]);
        }
#pragma unroll
        for (int i = 0; i < 4; i++)
#pragma unroll
            for (int j = 0; j < 4; j++)
                if (l0 + ty * 4 + i < lim) h[(l0 + ty * 4 + i) * 64 + tx * 4 + j] = acc[i][j];
    }
    const int c = tid & 63;
    float stat[2] = {0.f, 0.f};
    for (int r = 0; r < 2; r++) {
        named_bar(1, 256);
        float s = 0.f;
        for (int l = tid >> 6; l < lim; l += 4) {
            const float v = h[l * 64 + c] - stat[0];
            s += r ? v * v : v;
        }
        red[tid] = s;
        named_bar(1, 256);
        unsigned long long* p = g_dpart + ((r * 16 + b * 8 + db) * 16) * 64 + c;
        if (tid < 64)
            asm volatile("st.relaxed.gpu.global.v2.b32 [%0], {%1, %2};" ::"l"(p + part * 64),
                         "r"(__float_as_uint(red[c] + red[64 + c] + red[128 + c] + red[192 + c])), "r"(epoch) : "memory");
        s = 0.f;
        for (int k = 0; k < 16; k++) {
            unsigned long long v = 0;
#pragma unroll 1
            for (uint32_t n = 0; n < (1u << 20); n++) {
                asm volatile("ld.relaxed.gpu.global.u64 %0, [%1];" : "=l"(v) : "l"(p + k * 64) : "memory");
                if ((uint32_t)(v >> 32) == epoch) break;
                __nanosleep(200);
            }
            s += __uint_as_float((uint32_t)v);
        }
        stat[r] = s * (1.0f / kL);
    }
    const float a = __bfloat162float(gamma[64 * db + c]) / sqrtf(stat[1] + 1e-5f), be = __bfloat162float(beta[64 * db + c]);
    for (int l = tid >> 6; l < lim; l += 4)
        out[((size_t)b * kL + row0 + l) * 512 + 64 * db + c] = __float2bfloat16(gelu_half(0.5f * fmaf(h[l * 64 + c] - stat[0], a, be)));
    named_bar(1, 256);
}

__device__ __forceinline__ int tail_block(uint32_t gr, int h) { return ((gr >> 4) & 3) ^ (5 * h); }
__device__ __forceinline__ void tail_poll(const volatile uint32_t* ts, int h) {
    const uint32_t gr = ts[64];
#pragma unroll 1
    for (uint32_t n = 0; n < (1u << 15); n++) {
        unsigned v;
        asm volatile("ld.relaxed.gpu.global.u32 %0, [%1];" : "=r"(v) : "l"(&g_yready[((gr >> 6) * 8 + tail_block(gr, h)) * 32]) : "memory");
        if (v >= 32) break;
        __nanosleep(YSLEEP);
    }
    asm volatile("fence.acquire.gpu;" ::: "memory");
    asm volatile("fence.proxy.async.global;" ::: "memory");
}
__device__ __forceinline__ void tail_loads(uint32_t sbase, const uint8_t* sp, const volatile uint32_t* ts, int h, int u0, int u1, int lane) {
    const uint32_t gr = ts[64];
    if (lane >= u0 && lane < u1) {
        const uint32_t bar = sbase + OFF_BAR + B_UNIT + 8 * (10 * h + lane);
        mbar_expect_tx(bar, 8192);
        bulk_g2s(sbase + (h ? OFF_U1 : OFF_U0) + lane * 8192, sp + y_unit(tail_block(gr, h), (gr & 15) * 10 + lane, gr >> 6, ts[66]), 8192, bar);
    }
    __syncwarp();
}
__device__ __forceinline__ const float* corr_src(uint32_t gr, int h) { return &g_corr[(((gr >> 6) * 8 + tail_block(gr, h)) * kNT + (gr & 15) * 10) * 64]; }
__device__ __forceinline__ void corr_load(uint32_t sbase, uint32_t gr, int h, uint32_t bar) { bulk_g2s(sbase + (h ? OFF_C1 : OFF_C0), corr_src(gr, h), 2560, bar); }
__device__ __forceinline__ void tail_phase(uint32_t sbase, uint8_t* smem, uint8_t* sp, int wg, const __nv_bfloat16* __restrict__ x,
                                           const __nv_bfloat16* __restrict__ wt, const __nv_bfloat16* __restrict__ gamma,
                                           const __nv_bfloat16* __restrict__ beta, __nv_bfloat16* __restrict__ out) {
    const uint32_t* ts = reinterpret_cast<const uint32_t*>(smem + OFF_TS);
    const uint32_t gr = ts[64];
    const float sx = __uint_as_float(ts[74]), sw = __uint_as_float(ts[75]);
    const uint32_t epoch = ts[76];
    float* tot = reinterpret_cast<float*>(smem + OFF_TOT);
    float* nrm = reinterpret_cast<float*>(smem + OFF_NRM);
    const int tid = threadIdx.x, w = (tid >> 5) & 3, lane = tid & 31, g = lane >> 2, q = lane & 3;
    const int b = gr >> 6, late = (gr >> 4) & 1, part = gr & 15;
    unsigned exits = 0;
    bool bad = false;
    mbar_wait(sbase + OFF_BAR + B_FTAB, 0);
#pragma unroll 1
    for (int rd = 0; rd < 3; rd++) {
        if (rd < 2) {
            float acc[28], acc2[28], s[8] = {0.f, 0.f, 0.f, 0.f, 0.f, 0.f, 0.f, 0.f};
            const float swq = q == 0 ? sw : 0.f;
            const uint32_t ub = sbase + (rd ? OFF_U1 : OFF_U0), ubar = sbase + OFF_BAR + B_UNIT + 80 * rd;
            const float* c1 = reinterpret_cast<const float*>(smem + (rd ? OFF_C1 : OFF_C0)) + 16 * w + g;
            const uint32_t ka = ub + (lane >> 4) * 1024 + (lane & 7) * 128 + (((2 * w + ((lane >> 3) & 1)) ^ (lane & 7)) << 4);
            auto inverse = [&](float (&d)[28], int u) {
                const uint32_t dA = desc_lo(ub + u * 8192), dB = desc_lo(sbase + OFF_F);
                wg_fence();
                wgmma_n56_ss<0>(d, dA, dB);
                wgmma_n56_ss<1>(d, dA + 128, dB + 2);
                wgmma_n56_ss<1>(d, dA + 256, dB + 4);
                wgmma_n56_ss<1>(d, dA + 384, dB + 6);
                wg_commit();
            };
            auto keep = [&](float (&d)[28], int u, int un) {
                const bool ok = mbar_try(ubar + 8 * un, 0);
                reg_fence(d);
                d[25] = fmaf(c1[u * 64] * sx, swq, d[25]);
                d[27] = fmaf(c1[u * 64 + 8] * sx, swq, d[27]);
                if (part == 15 && u == 9) {
                    if (q >= 2) d[16] = d[18] = 0.f;
                    if (q >= 1) d[17] = d[19] = 0.f;
#pragma unroll
                    for (int i = 20; i < 28; i++) d[i] = 0.f;
                }
                const uint32_t a = ka + u * 8192;
#pragma unroll
                for (int j = 0; j < 6; j += 2)
                    stmatrix_x4_t(a + j * 1024, pack_f16(d[4 * j], d[4 * j + 1]), pack_f16(d[4 * j + 2], d[4 * j + 3]),
                                  pack_f16(d[4 * j + 4], d[4 * j + 5]), pack_f16(d[4 * j + 6], d[4 * j + 7]));
                asm volatile("stmatrix.sync.aligned.m8n8.x2.trans.shared.b16 [%0], {%1,%2};"
                             ::"r"(a + 6 * 1024), "r"(pack_f16(d[24], d[25])), "r"(pack_f16(d[26], d[27])) : "memory");
#pragma unroll
                for (int i = 0; i < 28; i++) {
                    s[i & 3] += d[i];
                    s[4 + (i & 3)] = fmaf(d[i], d[i], s[4 + (i & 3)]);
                }
#pragma unroll
                for (int i = 0; i < 8; i++) asm volatile("" : "+f"(s[i]));
                if (!ok) mbar_wait(ubar + 8 * un, 0);
                wg_wait<0>();
            };
            const int cut = rd ? NU1 : late ? NU1 : NU0, u0 = wg ? cut : 0, u1 = wg ? 10 : cut;
            if (rd) mbar_wait(sbase + OFF_BAR + B_C1, 0);
            mbar_wait(ubar + 8 * u0, 0);
            inverse(acc, u0);
            mbar_wait(ubar + 8 * (u0 + 1), 0);
            wg_wait<0>();
#pragma unroll 1
            for (int u = u0; u < u1; u += 2) {
                const int u2 = min(u + 2, u1 - 1);
                inverse(acc2, min(u + 1, u1 - 1));
                keep(acc, u, u2);
                if (u + 1 == u1) break;
                inverse(acc, u2);
                keep(acc2, u + 1, min(u + 3, u1 - 1));
            }
#pragma unroll
            for (int i = 0; i < 8; i += 2) {
                s[i] += s[i + 1];
                s[i] += __shfl_xor_sync(0xffffffffu, s[i], 1);
                s[i] += __shfl_xor_sync(0xffffffffu, s[i], 2);
            }
            float2* hnd = reinterpret_cast<float2*>(smem + (rd ? OFF_C1 + 2560 : OFF_HND)) + 16 * w + 8 * (q & 1) + g;
            const float2 mine = make_float2(q & 1 ? s[2] : s[0], q & 1 ? s[6] : s[4]);
            if (wg == 0) {
                if (q < 2) *hnd = mine;
                named_arrive(7 + rd, 256);
            } else {
                named_bar(7 + rd, 256);
                const float2 o = *hnd;
                if (q < 2)
                    asm volatile("st.relaxed.gpu.global.v2.b32 [%0], {%1, %2};" ::"l"(part_sums(sp, b, tail_block(gr, rd)) + part * 64 + 16 * w + 8 * q + g),
                                 "r"((__float_as_uint(mine.x + o.x) & ~15u) | (epoch & 15)),
                                 "r"((__float_as_uint(mine.y + o.y) & ~15u) | ((epoch >> 4) & 15)) : "memory");
            }
        }
        const int h = rd >> 1, db = tail_block(gr, h);
        if (rd == 0 && late) continue;
        if (rd != 1 || late) {
            const unsigned long long* ps = part_sums(sp, b, db) + (tid >> 6) * 256 + (tid & 63);
            if (rd < 2) named_bar(1, 256);
            uint32_t pv[4][2];
#pragma unroll 1
            for (uint32_t n = 0; n < (1u << 19); n++) {
                uint32_t dif = 0;
#pragma unroll
                for (int k = 0; k < 4; k++)
                    asm volatile("{\n.reg .b64 t;\nld.relaxed.gpu.global.u64 t, [%2];\nmov.b64 {%0, %1}, t;\n}" : "=r"(pv[k][0]), "=r"(pv[k][1]) : "l"(ps + k * 64) : "memory");
#pragma unroll
                for (int k = 0; k < 4; k++) dif |= (pv[k][0] ^ epoch) | (pv[k][1] ^ (epoch >> 4));
                if (!(dif & 15)) break;
            }
#pragma unroll
            for (int k = 0; k < 2; k++)
                tot[256 * k + tid] = (__uint_as_float(pv[0][k] & ~15u) + __uint_as_float(pv[1][k] & ~15u)) + (__uint_as_float(pv[2][k] & ~15u) + __uint_as_float(pv[3][k] & ~15u));
            named_bar(1, 256);
            bad = false;
            if (tid < 64) {
                const float* tt = tot + tid;
                const float mean = ((tt[0] + tt[64]) + (tt[128] + tt[192])) * (1.0f / kL), sq = ((tt[256] + tt[320]) + (tt[384] + tt[448])) * (1.0f / kL);
                const float2 gb = reinterpret_cast<const float2*>(smem + OFF_GB)[64 * h + tid];
                const float den = fmaxf(sq - mean * mean, 0.f) + 1e-5f * sx * sw * sx * sw, a = gb.x / sqrtf(den);
                nrm[h * 128 + tid] = 0.5f * a;
                nrm[h * 128 + 64 + tid] = 0.5f * (gb.y - mean * a);
                bad = !(sq < 1e9f) || !(den >= 0x1p-22f);
            }
            bad = named_bar_or(1, 256, bad);
            if (h == 1 && tid == 0) exits = atomicAdd(&g_exit, 1);
            if (bad) direct_block(x, wt, gamma, beta, out, reinterpret_cast<float*>(smem + OFF_DIR), b, db, part, epoch);
        }
        if (bad) continue;
        const int jh = w & 1, r0 = 8 * (w >> 1), cut = h || late ? 256 : FC0, mid = wg ? FC0 + FA1 : FA0;
        const int i0 = rd == 1 && !late ? mid : wg ? cut : 0, i1 = rd == 0 ? mid : wg ? 512 : cut;
        const int lim = min(500, kL - part * 500) - r0 - g;
        float na[8], nb[8];
#pragma unroll
        for (int i = 0; i < 8; i++) {
            const int col = 32 * jh + 8 * (i >> 1) + 2 * q + (i & 1);
            na[i] = nrm[h * 128 + col];
            nb[i] = nrm[h * 128 + 64 + col];
        }
        __nv_bfloat16* o = out + ((size_t)b * kL + part * 500 + i0 + r0 + g) * 512 + 64 * db + 32 * jh + 8 * q;
        const int row = i0 + r0 + (lane & 7);
        int l = row % kMO;
        uint32_t ra = sbase + (h ? OFF_U1 : OFF_U0) + row / kMO * 8192 + l * 128;
        const int cc = 4 * jh + (lane >> 3);
        auto fetch = [&](uint32_t (&r)[4]) {
            asm volatile("ldmatrix.sync.aligned.m8n8.x4.shared.b16 {%0,%1,%2,%3}, [%4];"
                         : "=r"(r[0]), "=r"(r[1]), "=r"(r[2]), "=r"(r[3]) : "r"(ra + (((cc ^ l) & 7) << 4)) : "memory");
            const bool wrap = l >= kMO - 16;
            l += wrap ? 16 - kMO : 16;
            ra += wrap ? 2048 + 8192 - kMO * 128 : 2048;
        };
        auto gelu8 = [&](const uint32_t (&r)[4], uint32_t (&p)[4]) {
#pragma unroll
            for (int i = 0; i < 4; i++) {
                float lo, hi;
                asm("{\n.reg .b16 a, b;\nmov.b32 {a, b}, %2;\ncvt.f32.f16 %0, a;\ncvt.f32.f16 %1, b;\n}" : "=f"(lo), "=f"(hi) : "r"(r[i]));
                p[i] = pack_bf16(gelu_half(fmaf(lo, na[2 * i], nb[2 * i])), gelu_half(fmaf(hi, na[2 * i + 1], nb[2 * i + 1])));
            }
        };
        uint32_t r[2][4], rn[2][4];
        fetch(r[0]);
        fetch(r[1]);
#pragma unroll 1
        for (int i = i0; i < i1; i += 32) {
            fetch(rn[0]);
            fetch(rn[1]);
            uint32_t p0[4], p1[4];
            gelu8(r[0], p0);
            gelu8(r[1], p1);
            if (i < lim) stg128(o, p0[0], p0[1], p0[2], p0[3]);
            if (i + 16 < lim) stg128(o + 16 * 512, p1[0], p1[1], p1[2], p1[3]);
            o += 32 * 512;
#pragma unroll
            for (int k = 0; k < 4; k++) { r[0][k] = rn[0][k]; r[1][k] = rn[1][k]; }
        }
    }
    if (tid < 32) {
        if (__shfl_sync(0xffffffffu, exits, 0) == NCTA - 1) {
            for (int i = 0; i < 4; i++) *chunk_flag(sp, i >> 1, i & 1, lane) = 0;
            if (lane < 2) *chunk_flag(sp, 0, lane, 32) = 0;
            g_tsel[lane] = 0;
            if (lane < 16) g_yready[lane * 32] = 0;
            if (lane == 0) { g_exit = 0; g_epoch = epoch; }
        }
    }
}

__device__ __forceinline__ void publish_tiles(uint32_t bars, int cta, int wg) {
#pragma unroll 1
    for (int m = 0; m < 2; m++) {
        mbar_wait(bars + B_YS + 8 * (2 * m + wg), 0);
        asm volatile("fence.acq_rel.gpu;" ::: "memory");
        red_relaxed(&g_yready[((cta & 2) * 4 + 4 * m + 2 * (cta & 1) + wg) * 32]);
        mbar_arrive(bars + B_YP + 8 * (2 * m + wg));
    }
}

__global__ void __launch_bounds__(384, 1)
main_kernel(const __grid_constant__ CUtensorMap tmx, const __grid_constant__ CUtensorMap tmw0, const __grid_constant__ CUtensorMap tmw1,
            const __nv_bfloat16* __restrict__ x, const __nv_bfloat16* __restrict__ wt, const __nv_bfloat16* __restrict__ gamma,
            const __nv_bfloat16* __restrict__ beta, __nv_bfloat16* __restrict__ out) {
    extern __shared__ __align__(1024) uint8_t smem_raw[];
    const uint32_t sbase = smem_u32(smem_raw) & ~1023u;
    const uint32_t bars = sbase + OFF_BAR;
    const int tid = threadIdx.x, wg = __shfl_sync(0xffffffffu, tid >> 7, 0), lane = tid & 31;
    const int cta = blockIdx.x;
    volatile uint32_t* ts = reinterpret_cast<volatile uint32_t*>(smem_raw + OFF_TS);
    uint8_t* const sp = reinterpret_cast<uint8_t*>((reinterpret_cast<uintptr_t>(g_sp) + (2u << 20) - 1) & ~(uintptr_t)((2u << 20) - 1));
    const bool probing = (cta & 3) == 0 && lane == 0 && tid < 128;
    unsigned* pw = reinterpret_cast<unsigned*>(sp + (tid < 64 ? ((cta >> 2) << 21) + ((tid & 32) ? 15 : 13) * 4096
                                                              : ((tid & 32) ? 0 : 14) * 4096 + (cta >> 2) * 128));
    unsigned pv = 0;
    if (probing) {
        stg128(pw, 0, 0, 0, 0);
        stg128(pw + 4, 0, 0, 0, 0);
        asm volatile("atom.relaxed.gpu.global.exch.b32 %0, [%1], %2;" : "=r"(pv) : "l"(pw), "r"(7) : "memory");
    }
    if (tid < B_END / 8) {
        const int o = 8 * tid;
        mbar_init(bars + o, o < B_EMPTY ? 2 : o < B_YS - 8 ? 8 : o < B_GATE ? 4 : 1);
        fence_mbar_init();
        fence_proxy_async_smem();
    }
    if (tid >= 256 && tid < 262) ts[68 + tid - 256] = tid < 260 ? 0xffffu : 0;
    if (tid == 383) asm volatile("griddepcontrol.launch_dependents;");
    __syncthreads();

    if (wg == 2) {
        asm volatile("setmaxnreg.dec.sync.aligned.u32 40;");
        const int role = (tid >> 5) & 3;
        if (role == 3) {
            unsigned v = 0;
#pragma unroll 1
            for (uint32_t n = 0; n < (1u << 15); n++) {
                asm volatile("ld.relaxed.gpu.global.u32 %0, [%1];" : "=r"(v) : "l"(&g_tsel[lane]) : "memory");
                if (__all_sync(0xffffffffu, v & 16)) break;
                __nanosleep(200);
            }
            const uint32_t m1 = __ballot_sync(0xffffffffu, v & 8), below = (1u << lane) - 1;
            const int rank = (v & 8) ? 32 - __popc(m1) + __popc(m1 & below) : __popc(~m1 & below);
            ts[lane] = rank;
            ts[32 + rank] = lane;
            const uint32_t p0 = __ballot_sync(0xffffffffu, v & 1);
            if (lane == 0) ts[66] = p0;
            if (lane == (cta >> 2)) ts[64] = rank * 4 + (cta & 3);
            const int part = (m1 >> (cta >> 2)) & 1;
            __syncwarp();
            if (lane == 0) { mbar_arrive(bars + B_TSEL); }
            mbar_wait(bars + B_PUB, 0);
            int gc = 0;
            const int gend = lane == 0 ? 33 : lane == 1 ? GMAX + 1 : 0;
#pragma unroll 1
            for (uint32_t n = 0; n < (1u << 16) && __any_sync(0xffffffffu, gc < gend); n++) {
                asm volatile("ld.relaxed.gpu.global.u32 %0, [%1];" : "=r"(v) : "l"(chunk_flag(sp, lane == 1, part, min(gc, 32 - (lane & 1)))) : "memory");
                if (gc < gend && v >= NCTA) {
                    asm volatile("fence.acquire.gpu;" ::: "memory");
                    mbar_arrive(bars + (lane == 0 ? B_RDY : B_GATE) + 8 * gc);
                    gc++;
                }
            }
            if (lane == 0) publish_tiles(bars, cta, 1);
        } else if (role == 0) {
            const int b = (cta >> 1) & 1, dq = cta & 1;
            for (int v = 0; v < V0; v++) {
                mbar_wait(bars + B_EMPTY + 8 * (v % NST), ((v / NST) & 1) ^ 1);
                if (lane == 0) mbar_arrive(bars + B_FULL + 8 * (v % NST));
            }
            mbar_wait(bars + B_TSEL, 0);
            const uint32_t gr = ts[64], grp = gr >> 6, idx = (gr >> 2) & 15, pmask = ts[66];
            const uint32_t n0 = idx * 4 + 2 * dq + ((lane & 1) ^ 1), r0 = lane < 3 ? idx * 4 + b : R_W + n0 / 3;
            const uint32_t base = (r0 << 16) + 4096 + ((lane < 3 ? lane : n0 % 3) << 14), step = (lane < 3 ? 64 : 22) << 16;
            uint32_t sels = 0;
            for (int i = 0; i < 12; i++) sels |= run_sel(r0 + i * (step >> 16), grp, pmask) << i;
            int ld = 0;
            const uint32_t bytes = lane == 2 ? XB - 16384 : 8192;
#pragma unroll 1
            for (int h = 0; h < 64; h++) {
                const int s = step_k(h), st = (h + V0) % NST;
                const bool newx = h < HEND ? !(h & 1) : h < HEND + 4;
                const uint32_t fb = bars + B_FULL + 8 * st;
                const uint32_t k = lane < 3 ? (s >> 1) % RX : (h + RW - 64 % RW) % RW, half = lane < 3 ? s & 1 : 0;
                const uint8_t* gsrc = sp + (base + k * step + (half << 17) + ((((sels >> k) ^ half) & 1) << 13));
                const uint32_t dst = sbase + (lane < 3 ? OFF_X + (s & 3) * XB + lane * 8192 : st * 8192 + (lane == 3 ? OFF_W0 : OFF_W1));
                auto landed = [&]() {
                    if (ld < h && mbar_test(bars + B_FULL + 8 * ((ld + V0) % NST), ((ld + V0) / NST) & 1)) {
                        if (!(ld & 1) && (ld >> 1) <= GMAX && lane < 2) red_relaxed(chunk_flag(sp, 1, lane, ld >> 1));
                        ld++;
                    }
                };
                if ((h & 1) || h == 0) {
#pragma unroll 1
                    for (uint32_t n = 0; n < (1u << 19) && !mbar_test(bars + B_RDY + 8 * ((h + 1) >> 1), 0); n++) landed();
                    asm volatile("fence.proxy.async.global;" ::: "memory");
                }
#pragma unroll 1
                for (uint32_t n = 0; n < (1u << 19) && !mbar_test(bars + B_EMPTY + 8 * st, (((h + V0) / NST) & 1) ^ 1); n++) landed();
#pragma unroll 1
                for (uint32_t n = 0; n < (1u << 19) && ld <= h - NST; n++) landed();
                if (lane == 0) mbar_expect_tx(fb, newx ? 16384 + XB : 16384);
                __syncwarp();
                if (lane < 3 ? newx : lane < 5) bulk_g2s(dst, gsrc, bytes, fb);
            }
            const int late = (gr >> 4) & 1;
            tail_poll(ts, 0);
            mbar_wait(bars + B_T2, 0);
            tail_loads(sbase, sp, ts, 0, 0, 8, lane);
            mbar_wait(bars + (GP1 ? B_YP : B_YS) + 16, 0);
            tail_loads(sbase, sp, ts, 0, 8, 10, lane);
            for (int v = V0 + 64; v < V0 + 64 + NST; v++) mbar_wait(bars + B_EMPTY + 8 * (v % NST), ((v / NST) & 1) ^ 1);
            tail_poll(ts, 1);
            if (lane == 0) {
                mbar_expect_tx(bars + B_C1, 2560);
                corr_load(sbase, gr, 1, bars + B_C1);
            }
            tail_loads(sbase, sp, ts, 1, 0, 10, lane);
        } else if (role == 1) {
            uint32_t gr = 0;
#pragma unroll 1
            for (int v = 0; v < V0 + 64; v++) {
                mbar_wait(bars + B_EMPTY + 8 * (v % NST), ((v / NST) & 1) ^ 1);
                if (v == NST) mbar_wait(bars + B_PUB, 0);
                if (v == 1) {
                    mbar_wait(bars + B_TSEL, 0);
                    gr = ts[64];
                }
                __syncwarp();
                const int r = lane < 2 ? x_round(v, lane) : -1, h = lane < 2 ? w_step(v, lane) : -1;
                const uint32_t fb = bars + B_FULL + 8 * (v % NST);
                const uint32_t bytes = __reduce_add_sync(0xffffffffu, r >= 0 ? 8192 : h >= 0 ? 4096 : 0);
                if (lane == 0) mbar_expect_tx(fb, bytes);
                __syncwarp();
                if (r >= 0) {
                    const int u = r * NCTA + cta, i = u % XPC, b = i >= kNT;
                    tma3d(raw_slot(sbase, v, lane), &tmx, u / XPC * 64, (i - b * kNT) * kMO, b, fb);
                } else if (h >= 0) {
                    const int c = 32 * step_k(h) + ((gr >> 1) & 30);
                    tma3d_ef(raw_slot(sbase, v, lane), c < 512 ? &tmw0 : &tmw1, step_m(h) * 256 + (gr & 3) * 64, 0, c & 511, fb);
                }
                if (v == 24) {
                    uint32_t epoch;
                    asm volatile("ld.relaxed.gpu.global.u32 %0, [%1];" : "=r"(epoch) : "l"(&g_epoch) : "memory");
#pragma unroll
                    for (int i = lane; i < 128; i += 32) {
                        const int d = 64 * tail_block(gr, i >> 6) + (i & 33) + 8 * ((i >> 1) & 3) + 2 * ((i >> 3) & 3);
                        ts[(OFF_GB - OFF_TS) / 4 + 2 * i] = (uint32_t)__bfloat16_as_ushort(gamma[d]) << 16;
                        ts[(OFF_GB - OFF_TS) / 4 + 2 * i + 1] = (uint32_t)__bfloat16_as_ushort(beta[d]) << 16;
                    }
                    if (lane == 0) ts[76] = epoch + 1;
#pragma unroll 1
                    for (uint32_t n = 0; n < (1u << 15); n++) {
                        unsigned c;
                        asm volatile("ld.acquire.gpu.global.u32 %0, [%1];" : "=r"(c) : "l"(&g_cready[((gr >> 6) * 2 + (lane & 1)) * 32]) : "memory");
                        if (__all_sync(0xffffffffu, c == epoch + 1)) break;
                        __nanosleep(500);
                    }
                    asm volatile("fence.proxy.async.global;" ::: "memory");
                }
                if (v >= 63 && v < 67) {
                    if (v == 66 && lane == 0) {
                        mbar_expect_tx(bars + B_FTAB, 8192 + 2560);
                        bulk_g2s(sbase + OFF_F, g_tab.inv, 8192, bars + B_FTAB);
                        corr_load(sbase, gr, 0, bars + B_FTAB);
                        asm volatile("cp.async.bulk.prefetch.L2.global [%0], 2560;" ::"l"(corr_src(gr, 1)) : "memory");
                    }
                    const int t = v - 63;
                    for (int i = lane; i < kNT; i += 32)
                        ts[(OFF_YT - OFF_TS) / 4 + t * kNT + i] = y_unit(4 * (t >> 1) + 2 * (cta & 1) + (t & 1), i, (cta >> 1) & 1, ts[66]);
                }
            }
        } else if (lane == 0) {
#pragma unroll 1
            for (int gc = 0; gc < 33;) {
                mbar_wait(bars + B_SIG + 8 * gc, 0);
                int ge = gc + 1;
                while (ge < 33 && mbar_test(bars + B_SIG + 8 * ge, 0)) ge++;
                asm volatile("fence.acq_rel.gpu;" ::: "memory");
                for (; gc < ge; gc++) {
                    red_relaxed(chunk_flag(sp, 0, 0, gc));
                    red_relaxed(chunk_flag(sp, 0, 1, gc));
                    if (gc == 0) mbar_arrive(bars + B_PUB);
                }
            }
            publish_tiles(bars, cta, 0);
        }
    } else {
        asm volatile("setmaxnreg.inc.sync.aligned.u32 232;");
        if ((cta & 3) == 0) {
            if (probing) {
                const int w = tid >> 5;
                unsigned best = 0xffffu;
#pragma unroll 1
                for (int r = 0; r < 6; r++) {
                    unsigned t0, t1;
                    asm volatile("{\n.reg .pred p;\nsetp.eq.u32 p, %1, 0xffffffff;\nmov.u32 %0, 0;\n@!p mov.u32 %0, %%clock;\n}"
                                 : "=r"(t0) : "r"(pv) : "memory");
                    asm volatile("atom.relaxed.gpu.global.exch.b32 %0, [%1], %2;" : "=r"(pv) : "l"(pw), "r"(r) : "memory");
                    asm volatile("{\n.reg .pred p;\nsetp.eq.u32 p, %1, 0xffffffff;\nmov.u32 %0, 0;\n@!p mov.u32 %0, %%clock;\n}"
                                 : "=r"(t1) : "r"(pv) : "memory");
                    ts[68 + w] = best = min(best, t1 - t0);
                    const unsigned other = ts[68 + (w ^ 1)];
                    if (min(best, other) < PROBE_NEAR && max(best, other) > PROBE_NEAR) break;
                }
            }
            if (wg == 0) {
                named_bar(2, 128);
                if (tid == 0) {
                    const uint32_t part = ts[71] < ts[70];
                    const uint32_t v = 16 | (part << 3) | ((ts[69] < ts[68]) ^ part);
                    asm volatile("st.relaxed.gpu.global.u32 [%0], %1;" ::"l"(&g_tsel[cta >> 2]), "r"(v) : "memory");
                }
            }
        }
        uint4 fw[2], sm[8];
#pragma unroll
        for (int j = 0; j < 2; j++) fw[j] = __ldg(reinterpret_cast<const uint4*>(g_tab.fwd) + tid + 256 * j);
#pragma unroll
        for (int j = 0; j < 4; j++) {
            const int rx = 2 * j + (tid >> 7), rw = 4 * j + (tid >> 6);
            sm[j] = __ldg(reinterpret_cast<const uint4*>(x) + ((rx >> 2) * kRows + 1000 + 2000 * (rx & 3)) * 128 + (tid & 127));
            sm[4 + j] = __ldg(reinterpret_cast<const uint4*>(wt) + (2 * rw * 512 + 33 * rw + 7) * 64 + (tid & 63));
        }
        {
#pragma unroll
            for (int k = 0; k < 2; k++) {
                uint32_t mx = 0;
#pragma unroll
                for (int j = 4 * k; j < 4 * k + 4; j++)
                    mx = __vmaxu2(__vmaxu2(mx, __vmaxu2(sm[j].x & 0x7FFF7FFFu, sm[j].y & 0x7FFF7FFFu)), __vmaxu2(sm[j].z & 0x7FFF7FFFu, sm[j].w & 0x7FFF7FFFu));
                mx = __reduce_max_sync(0xffffffffu, max(mx & 0xFFFFu, mx >> 16));
                if (lane == 0) atomicMax(const_cast<uint32_t*>(ts) + 72 + k, mx);
            }
            named_bar(1, 256);
            const uint32_t ex = max(251 - (int)(ts[72] >> 7), 8), ew = max(251 - (int)(ts[73] >> 7), 8);
            if (tid == 0) { ts[74] = ex << 23; ts[75] = ew << 23; }
            const uint32_t sx = ex * 0x800080u, sw = ew * 0x800080u;
#pragma unroll
            for (int j = 0; j < 2; j++) {
                const int i = tid + 256 * j, row = i >> 3, c = (i ^ row) & 7;
                sts128(sbase + OFF_F + 16 * i, mul_bf16x2(fw[j].x, sx), mul_bf16x2(fw[j].y, sx), mul_bf16x2(fw[j].z, sx), mul_bf16x2(fw[j].w, sx));
                if (c < 2) sts128(sbase + row * 32 + c * 16, mul_bf16x2(fw[j].x, sw), mul_bf16x2(fw[j].y, sw), mul_bf16x2(fw[j].z, sw), mul_bf16x2(fw[j].w, sw));
            }
            named_bar(1, 256);
        }
        const int t = tid & 127;
        Xf f;
        f.sbase = sbase; f.lane = lane; f.xsw = cta & 4; f.dw = desc_lo(sbase + (wg ? OFF_W1 : OFF_W0));
        mbar_wait(bars + B_TSEL, 0);
        {
            const uint32_t gr = ts[64], pmask = ts[66];
            const int w = t >> 5;
            const uint32_t rx = ts[8 * w + (lane >> 2)], nw = (8 * (w & 1) + (lane >> 2)) * 4 + (gr & 3);
            f.px = sp + ((rx & 15) << 18) + 4096;
            f.pw = sp + ((R_W + nw / 3) << 16) + 4096 + ((nw % 3) << 14) + (w >> 1) * 128;
            f.cx = (lane & 7) << 4;
            f.cw = ((lane & 7) ^ (w >> 1)) << 4;
            for (int i = 0; i < RX; i++) f.cx |= run_sel((i * 16 + (rx & 15)) * 4, rx >> 4, pmask) << (8 + i);
            for (int i = 0; i < RW; i++) f.cw |= run_sel(R_W + i * 22 + nw / 3, gr >> 6, pmask) << (8 + i);
            if (tid < 2 * (V0 + 65)) ts[(OFF_PLAN - OFF_TS) / 4 + tid] = plan_word(tid >> 1, tid & 1, cta, gr);
            const int row = tid >> 2, ch = tid & 3, s = ts[32 + (gr >> 6) * 16 + ((row >> 1) & 8) + (row & 7)], p = (row >> 3) & 1;
            const int frow = 16 * (s >> 3) + 8 * p + (s & 7);
            uint32_t v[4] = {0, 0, 0, 0};
            if ((ch >> 1) == (row >> 5))
                asm volatile("ld.shared.v4.b32 {%0,%1,%2,%3}, [%4];" : "=r"(v[0]), "=r"(v[1]), "=r"(v[2]), "=r"(v[3])
                             : "r"(sbase + frow * 32 + (ch & 1) * 16) : "memory");
            sts128(sbase + OFF_G + row * 64 + ((ch ^ ((row >> 1) & 3)) << 4), v[0], v[1], v[2], v[3]);
            fence_proxy_async_smem();
            named_bar(1, 256);
        }
        {
            float at[32];
#pragma unroll 1
            for (uint32_t v = 0; v < V0; v++) {
                const uint32_t e = plan_load(f, v, wg), raw = raw_slot(sbase, v, wg);
                mbar_wait(bars + B_FULL + 8 * (v % NST), (v / NST) & 1);
                wg_fence();
                if ((e & 6) == 2) {
                    unit_mma<false>(at, f, raw);
                    wg_wait<0>();
                    unit_store<false>(at, f, e);
                } else if (e & 4) {
                    unit_mma<true>(at, f, raw);
                    wg_wait<0>();
                    unit_store<true>(at, f, e);
                }
                if (lane == 0) mbar_arrive(bars + B_EMPTY + 8 * (v % NST));
                unit_done(f, e, v);
            }
        }
        const int slot = cta >> 2;
        f.e = plan_load(f, V0, wg);
        uint32_t a0[40], a1[40], b0[40], b1[40];
#pragma unroll
        for (int i = 0; i < 40; i++) a0[i] = a1[i] = b0[i] = b1[i] = 0;
        if (slot == 0) gemm_main<true>(a0, a1, b0, b1, f, wg);
        else gemm_main<false>(a0, a1, b0, b1, f, wg);
#pragma unroll 1
        for (int m = 0; m < 2; m++) {
            if (slot == 0) gemm_last<true>(a0, a1, f, wg, m);
            else gemm_last<false>(a0, a1, f, wg, m);
            reg_fence(a0);
            reg_fence(a1);
            const int wsw = ts[64] & 4;
            const uint32_t ytab = sbase + OFF_YT + (m * 2 + wg) * (kNT * 4);
            store_round<0>(a0, a1, sbase + OFF_STG + wg * 16384, t, wg, sp, slot, ytab, wsw);
            store_round<1>(a0, a1, sbase + OFF_STG + wg * 16384, t, wg, sp, slot, ytab, wsw);
            store_round<2>(a0, a1, sbase + OFF_STG + wg * 16384, t, wg, sp, slot, ytab, wsw);
            __syncwarp();
            if (lane == 0) mbar_arrive(bars + B_YS + 8 * (2 * m + wg));
#pragma unroll
            for (int i = 0; i < 40; i++) { a0[i] = b0[i]; a1[i] = b1[i]; }
        }
        tail_phase(sbase, smem_raw, sp, wg, x, wt, gamma, beta, out);
    }
}

constexpr int C_STAGE = 32768 + 2 * XB, C_SMEM = 3 * C_STAGE + 64;
__global__ void __launch_bounds__(256, 1) corr_kernel(const __grid_constant__ CUtensorMap tmx, const __grid_constant__ CUtensorMap tmw) {
    extern __shared__ __align__(1024) uint8_t smem_raw[];
    const uint32_t sbase = smem_u32(smem_raw) & ~1023u, bars = sbase + 3 * C_STAGE;
    const int tid = threadIdx.x, wg = __shfl_sync(0xffffffffu, tid >> 7, 0), b = blockIdx.x >> 1, dh = blockIdx.x & 1;
    auto load = [&](int k) {
        const uint32_t st = sbase + (k % 3) * C_STAGE, bar = bars + 8 * (k % 3);
        mbar_expect_tx(bar, C_STAGE);
        for (int i = 0; i < 4; i++) tma2d(st + i * 8192, &tmw, 256 * dh + 64 * i, 64 * k, bar);
        tma4d(st + 32768, &tmx, 64 * k, 64 - kMO, 1, b, bar);
        tma4d(st + 32768 + XB, &tmx, 64 * k, 0, 0, b, bar);
    };
    uint32_t epoch = 0;
    if (tid == 0) {
        for (int i = 0; i < 3; i++) mbar_init(bars + 8 * i, 1);
        fence_mbar_init();
        fence_proxy_async_smem();
        for (int k = 0; k < 3; k++) load(k);
        asm volatile("ld.relaxed.gpu.global.u32 %0, [%1];" : "=r"(epoch) : "l"(&g_epoch) : "memory");
    }
    __syncthreads();
    float a[2][80];
#pragma unroll
    for (int i = 0; i < 80; i++) a[0][i] = a[1][i] = 0.f;
#pragma unroll 1
    for (int k = 0; k < 8; k++) {
        const uint32_t dA = desc_lo(sbase + (k % 3) * C_STAGE + wg * 16384), dB = desc_lo(sbase + (k % 3) * C_STAGE + 32768);
        mbar_wait(bars + 8 * (k % 3), (k / 3) & 1);
        wg_fence();
#pragma unroll
        for (int i = 0; i < 8; i++) {
            wgmma_n160_f<1>(a[i & 1], dA + (i & 1) * 512 + (i >> 1) * 128, dB + (i >> 1) * 2);
            wgmma_n160_f<-1>(a[i & 1], dA + (i & 1) * 512 + (i >> 1) * 128, dB + XB / 16 + (i >> 1) * 2);
        }
        wg_commit();
        wg_wait<0>();
        __syncthreads();
        if (tid == 0 && k + 3 < 8) load(k + 3);
    }
    reg_fence(a[0]);
    reg_fence(a[1]);
    const int w = (tid >> 5) & 3, g = (tid & 31) >> 2, q = tid & 3;
#pragma unroll
    for (int i = 0; i < 160; i++) {
        const int m = i / 80, j = i % 80, d = 16 * w + 8 * ((j >> 1) & 1) + g;
        g_corr[((b * 8 + 4 * dh + 2 * wg + m) * kNT + 8 * (j >> 2) + 2 * q + (j & 1)) * 64 + (d & 33) + 8 * ((d >> 1) & 3) + 2 * ((d >> 3) & 3)] = a[m][j];
    }
    __syncthreads();
    if (tid == 0) {
        asm volatile("fence.acq_rel.gpu;" ::: "memory");
        asm volatile("st.relaxed.gpu.global.u32 [%0], %1;" ::"l"(&g_cready[blockIdx.x * 32]), "r"(epoch + 1) : "memory");
    }
}

__global__ void __launch_bounds__(256) plain_conv(const __nv_bfloat16* __restrict__ x, const __nv_bfloat16* __restrict__ w) {
    __shared__ float xs[64][17], ws[16][65];
    float* h = reinterpret_cast<float*>(g_sp + (8u << 20));
    const int b = blockIdx.z, l0 = blockIdx.x * 64, d0 = blockIdx.y * 64, tx = threadIdx.x & 15, ty = threadIdx.x >> 4;
    float acc[4][4] = {};
    for (int k0 = 0; k0 < 31 * 512; k0 += 16) {
        for (int i = threadIdx.x; i < 1024; i += 256) {
            const int l = min(l0 + (i >> 4), kL - 1);
            xs[i >> 4][i & 15] = __bfloat162float(x[((size_t)b * kRows + l) * 1024 + k0 + (i & 15)]);
            ws[i >> 6][i & 63] = __bfloat162float(w[(size_t)(k0 + (i >> 6)) * 512 + d0 + (i & 63)]);
        }
        __syncthreads();
        for (int k = 0; k < 16; k++)
            for (int i = 0; i < 4; i++)
                for (int j = 0; j < 4; j++) acc[i][j] = fmaf(xs[ty * 4 + i][k], ws[k][tx * 4 + j], acc[i][j]);
        __syncthreads();
    }
    for (int i = 0; i < 4; i++)
        for (int j = 0; j < 4; j++)
            if (l0 + ty * 4 + i < kL) h[((size_t)b * kL + l0 + ty * 4 + i) * 512 + d0 + tx * 4 + j] = acc[i][j];
}
__global__ void __launch_bounds__(256) plain_norm(const __nv_bfloat16* __restrict__ gamma, const __nv_bfloat16* __restrict__ beta,
                                                  __nv_bfloat16* __restrict__ out) {
    __shared__ float s1[8][32], s2[8][32];
    const int c = threadIdx.x & 31, r = threadIdx.x >> 5, d = blockIdx.x * 32 + c;
    const float* h = reinterpret_cast<const float*>(g_sp + (8u << 20)) + (size_t)blockIdx.y * kL * 512 + d;
    float a = 0.f, q = 0.f;
    for (int l = r; l < kL; l += 8) { const float v = h[(size_t)l * 512]; a += v; q = fmaf(v, v, q); }
    s1[r][c] = a; s2[r][c] = q;
    __syncthreads();
    a = q = 0.f;
    for (int i = 0; i < 8; i++) { a += s1[i][c]; q += s2[i][c]; }
    const float mean = a * (1.0f / kL), sc = __bfloat162float(gamma[d]) / sqrtf(fmaxf(q * (1.0f / kL) - mean * mean, 0.f) + 1e-5f);
    const float sh = __bfloat162float(beta[d]) - mean * sc;
    for (int l = r; l < kL; l += 8)
        out[((size_t)blockIdx.y * kL + l) * 512 + d] = __float2bfloat16(gelu_half(0.5f * fmaf(h[(size_t)l * 512], sc, sh)));
}

typedef CUresult (*EncodeTiledFn)(CUtensorMap*, CUtensorMapDataType, cuuint32_t, void*, const cuuint64_t*, const cuuint64_t*,
                                  const cuuint32_t*, const cuuint32_t*, CUtensorMapInterleave, CUtensorMapSwizzle,
                                  CUtensorMapL2promotion, CUtensorMapFloatOOBfill);

void encode(EncodeTiledFn fn, CUtensorMap* tm, const void* ptr, int rank, const cuuint64_t* dims, const cuuint64_t* strides,
            const cuuint32_t* box, CUtensorMapL2promotion promo, CUtensorMapSwizzle swz = CU_TENSOR_MAP_SWIZZLE_128B) {
    const cuuint32_t es[5] = {1, 1, 1, 1, 1};
    fn(tm, CU_TENSOR_MAP_DATA_TYPE_BFLOAT16, rank, const_cast<void*>(ptr), dims, strides, box, es, CU_TENSOR_MAP_INTERLEAVE_NONE,
       swz, promo, CU_TENSOR_MAP_FLOAT_OOB_FILL_NONE);
}

}

extern "C" void kernel_launch(void* const* d_in, const int* in_sizes, int n_in, void* d_out, int out_size) {
    const __nv_bfloat16* x = (const __nv_bfloat16*)d_in[0];
    const __nv_bfloat16* w = (const __nv_bfloat16*)d_in[1];
    const __nv_bfloat16* gamma = (const __nv_bfloat16*)d_in[2];
    const __nv_bfloat16* beta = (const __nv_bfloat16*)d_in[3];
    static EncodeTiledFn enc = nullptr;
    static int resident = 0;
    if (!enc) {
        void* fn = nullptr;
        cudaDriverEntryPointQueryResult qr;
        cudaGetDriverEntryPoint("cuTensorMapEncodeTiled", &fn, cudaEnableDefault, &qr);
        enc = (EncodeTiledFn)fn;
        cudaFuncSetAttribute(main_kernel, cudaFuncAttributeMaxDynamicSharedMemorySize, MAIN_SMEM);
        cudaFuncSetAttribute(corr_kernel, cudaFuncAttributeMaxDynamicSharedMemorySize, C_SMEM);
        int dev = 0, per_sm = 0;
        cudaGetDevice(&dev);
        cudaDeviceGetAttribute(&resident, cudaDevAttrMultiProcessorCount, dev);
        cudaOccupancyMaxActiveBlocksPerMultiprocessor(&per_sm, main_kernel, 384, MAIN_SMEM);
        resident *= per_sm;
    }
    if (resident < NCTA + 4) {
        plain_conv<<<dim3((kL + 63) / 64, 8, 2), 256>>>(x, w);
        plain_norm<<<dim3(16, 2), 256>>>(gamma, beta, (__nv_bfloat16*)d_out);
        return;
    }
    CUtensorMap tmx, tmw0, tmw1, tmcx, tmcw;
    {
        const cuuint64_t dims[3] = {1024, kRows, 2}, strides[2] = {2048, (cuuint64_t)kRows * 2048};
        const cuuint32_t box[3] = {64, 64, 1};
        encode(enc, &tmx, x, 3, dims, strides, box, CU_TENSOR_MAP_L2_PROMOTION_L2_128B);
    }
    {
        const cuuint64_t dims0[3] = {512, 16, 512}, dims1[3] = {512, 15, 512}, strides[2] = {2 * 512 * 512 * 2, 1024};
        const cuuint32_t box[3] = {64, 16, 2};
        encode(enc, &tmw0, w, 3, dims0, strides, box, CU_TENSOR_MAP_L2_PROMOTION_L2_128B);
        encode(enc, &tmw1, w + 512 * 512, 3, dims1, strides, box, CU_TENSOR_MAP_L2_PROMOTION_L2_128B);
    }
    {
        const cuuint64_t dims[4] = {512, kMO, kNT, 2}, strides[3] = {2048, kMO * 2048, (cuuint64_t)kRows * 2048};
        const cuuint32_t box[4] = {64, 1, kNT, 1};
        encode(enc, &tmcx, x, 4, dims, strides, box, CU_TENSOR_MAP_L2_PROMOTION_L2_128B);
        const cuuint64_t dimw[2] = {512, 512}, stridew[1] = {1024};
        const cuuint32_t boxw[2] = {64, 64};
        encode(enc, &tmcw, w + 30 * 512 * 512, 2, dimw, stridew, boxw, CU_TENSOR_MAP_L2_PROMOTION_L2_128B);
    }
    main_kernel<<<NCTA, 384, MAIN_SMEM>>>(tmx, tmw0, tmw1, x, w, gamma, beta, (__nv_bfloat16*)d_out);
    cudaLaunchConfig_t cfg = {};
    cudaLaunchAttribute at[1];
    cfg.gridDim = 4;
    cfg.blockDim = 256;
    cfg.dynamicSmemBytes = C_SMEM;
    cfg.stream = cudaStreamPerThread;
    at[0].id = cudaLaunchAttributeProgrammaticStreamSerialization;
    at[0].val.programmaticStreamSerializationAllowed = 1;
    cfg.attrs = at;
    cfg.numAttrs = 1;
    cudaLaunchKernelEx(&cfg, corr_kernel, tmcx, tmcw);
}
```

```cpp
#include <cuda_runtime.h>
#include <cuda_bf16.h>
#include <cuda.h>
#include <stdint.h>

namespace {

constexpr int kL    = 7985;
constexpr int kRows = 8000;
constexpr int kMO   = 50;
constexpr int kNT   = 160;

constexpr int V0 = 7;
constexpr int NPRE = 6;
constexpr int RX = 4;
constexpr int YSLEEP = 100;
constexpr int PRE1 = 4;
constexpr int TSLEEP = 200;
constexpr int MERGE = 1;
constexpr int NU0 = 7;
constexpr int FA0 = 128;
constexpr int FA1 = 128;
constexpr int FC0 = 256;
constexpr int RW = 10;

static_assert(V0 >= 7 && V0 <= 9 && RX >= 2 && RX <= 4 && RW >= V0 - 1 && RW <= 12, "rings must fit and be as deep as the look-ahead");
constexpr uint32_t HOME_MASK = 0xB;
constexpr uint32_t R_W = 64 * RX, R_Y = R_W + 22 * RW, NPAGES = 32;
static_assert(R_Y + 427 <= 32 * NPAGES, "scratch size");

__device__ __align__(1024) uint8_t g_sp[(size_t)(NPAGES + 1) * (2u << 20)];
__device__ unsigned g_tsel[32];
__device__ __forceinline__ uint32_t run_sel(uint32_t r, uint32_t group, uint32_t pmask) {
    return ((pmask >> (r >> 5)) ^ __popc(r & HOME_MASK) ^ group) & 1;
}
__device__ __forceinline__ uint32_t run_off(uint32_t r, uint32_t run, uint32_t group, uint32_t pmask) {
    return (r << 16) + 4096 + (run_sel(r, group, pmask) << 13) + (run << 14);
}
__device__ __forceinline__ unsigned* chunk_flag(uint8_t* sp, int done, int part, int chunk) {
    return reinterpret_cast<unsigned*>(sp + (4 + 3 * (chunk >> 5)) * 65536 + (done ? (part ? 15 : 13) : (part ? 0 : 14)) * 4096 + (chunk & 31) * 128);
}
__device__ __forceinline__ unsigned long long* part_sums(uint8_t* sp, int b, int db) {
    return reinterpret_cast<unsigned long long*>(sp + (8 + 2 * db + ((__popc((8 + 2 * db) & HOME_MASK) ^ b) & 1)) * 65536 + 13 * 4096);
}
__device__ unsigned g_yready[16 * 32];
__device__ __align__(256) float g_corr[16 * kNT * 64];
__device__ unsigned g_cready[4 * 32];
__device__ float g_direct[256 * 500 * 64];
__device__ unsigned long long g_dpart[2 * 256 * 64];
__device__ unsigned g_exit, g_epoch;

__device__ __forceinline__ uint32_t smem_u32(const void* p) { return (uint32_t)__cvta_generic_to_shared(p); }

__device__ __forceinline__ void mbar_init(uint32_t bar, uint32_t count) {
    asm volatile("mbarrier.init.shared::cta.b64 [%0], %1;" ::"r"(bar), "r"(count) : "memory");
}
__device__ __forceinline__ void mbar_expect_tx(uint32_t bar, uint32_t bytes) {
    asm volatile("mbarrier.arrive.expect_tx.shared::cta.b64 _, [%0], %1;" ::"r"(bar), "r"(bytes) : "memory");
}
__device__ __forceinline__ void mbar_arrive(uint32_t bar) {
    asm volatile("mbarrier.arrive.shared::cta.b64 _, [%0];" ::"r"(bar) : "memory");
}
__device__ __forceinline__ bool mbar_try(uint32_t bar, uint32_t parity) {
    uint32_t ok;
    asm volatile(
        "{\n.reg .pred p;\n"
        "mbarrier.try_wait.parity.shared::cta.b64 p, [%1], %2;\n"
        "selp.u32 %0, 1, 0, p;\n}\n"
        : "=r"(ok) : "r"(bar), "r"(parity) : "memory");
    return ok;
}
__device__ __forceinline__ bool mbar_test(uint32_t bar, uint32_t parity) {
    uint32_t ok;
    asm volatile(
        "{\n.reg .pred p;\n"
        "mbarrier.test_wait.parity.shared::cta.b64 p, [%1], %2;\n"
        "selp.u32 %0, 1, 0, p;\n}\n"
        : "=r"(ok) : "r"(bar), "r"(parity) : "memory");
    return ok;
}
__device__ __forceinline__ void mbar_wait(uint32_t bar, uint32_t parity) {
#pragma unroll 1
    for (uint32_t n = 0; n < (1u << 14); n++)
        if (mbar_try(bar, parity)) break;
}
__device__ __forceinline__ void fence_proxy_async_smem() { asm volatile("fence.proxy.async.shared::cta;" ::: "memory"); }
__device__ __forceinline__ void fence_mbar_init() { asm volatile("fence.mbarrier_init.release.cluster;" ::: "memory"); }

__device__ __forceinline__ void bulk_g2s(uint32_t dst, const void* src, uint32_t bytes, uint32_t bar) {
    asm volatile("cp.async.bulk.shared::cluster.global.mbarrier::complete_tx::bytes [%0], [%1], %2, [%3];"
                 ::"r"(dst), "l"(src), "r"(bytes), "r"(bar) : "memory");
}
__device__ __forceinline__ void bulk_g2s_ef(uint32_t dst, const void* src, uint32_t bytes, uint32_t bar) {
    asm volatile("{\n.reg .b64 pol;\ncreatepolicy.fractional.L2::evict_first.b64 pol, 1.0;\n"
                 "cp.async.bulk.shared::cluster.global.mbarrier::complete_tx::bytes.L2::cache_hint [%0], [%1], %2, [%3], pol;\n}"
                 ::"r"(dst), "l"(src), "r"(bytes), "r"(bar) : "memory");
}
__device__ __forceinline__ void tma3d_ef(uint32_t dst, const CUtensorMap* tm, int c0, int c1, int c2, uint32_t bar) {
    asm volatile("{\n.reg .b64 pol;\ncreatepolicy.fractional.L2::evict_first.b64 pol, 1.0;\n"
                 "cp.async.bulk.tensor.3d.shared::cluster.global.mbarrier::complete_tx::bytes.L2::cache_hint [%0], [%1, {%3, %4, %5}], [%2], pol;\n}"
                 ::"r"(dst), "l"(tm), "r"(bar), "r"(c0), "r"(c1), "r"(c2) : "memory");
}
__device__ __forceinline__ void tma3d(uint32_t dst, const CUtensorMap* tm, int c0, int c1, int c2, uint32_t bar) {
    asm volatile("cp.async.bulk.tensor.3d.shared::cluster.global.mbarrier::complete_tx::bytes [%0], [%1, {%3, %4, %5}], [%2];"
                 ::"r"(dst), "l"(tm), "r"(bar), "r"(c0), "r"(c1), "r"(c2) : "memory");
}
__device__ __forceinline__ void poll_ge(const unsigned* p, unsigned target) {
#pragma unroll 1
    for (uint32_t n = 0; n < (1u << 15); n++) {
        unsigned v;
        asm volatile("ld.acquire.gpu.global.u32 %0, [%1];" : "=r"(v) : "l"(p) : "memory");
        if (v >= target) break;
        __nanosleep(32);
    }
}
__device__ __forceinline__ void red_relaxed(unsigned* p) { asm volatile("red.relaxed.gpu.global.add.u32 [%0], 1;" ::"l"(p) : "memory"); }
__device__ __forceinline__ void named_arrive(int id, int n) { asm volatile("bar.arrive %0, %1;" ::"r"(id), "r"(n) : "memory"); }
__device__ __forceinline__ void named_bar(int id, int n) { asm volatile("bar.sync %0, %1;" ::"r"(id), "r"(n) : "memory"); }

__device__ __forceinline__ void wg_fence() { asm volatile("wgmma.fence.sync.aligned;" ::: "memory"); }
__device__ __forceinline__ void wg_commit() { asm volatile("wgmma.commit_group.sync.aligned;" ::: "memory"); }
template <int N> __device__ __forceinline__ void wg_wait() { asm volatile("wgmma.wait_group.sync.aligned %0;" ::"n"(N) : "memory"); }
template <int N> __device__ __forceinline__ void reg_fence(float (&d)[N]) {
#pragma unroll
    for (int i = 0; i < N; i++) asm volatile("" : "+f"(d[i])::"memory");
}

#define F4(a, i) "+f"(a[i]), "+f"(a[i + 1]), "+f"(a[i + 2]), "+f"(a[i + 3])
#define F8(a, i) F4(a, i), F4(a, i + 4)
#define F16(a, i) F8(a, i), F8(a, i + 8)

constexpr uint32_t HI128 = 0x40000040u, HI64 = 0x80000020u;
__device__ __forceinline__ uint32_t desc_lo(uint32_t addr) { return (addr >> 4) | 0x10000u; }


#define R4(a, i) "+r"(a[i]), "+r"(a[i + 1]), "+r"(a[i + 2]), "+r"(a[i + 3])
#define R8(a, i) R4(a, i), R4(a, i + 4)
template <int N> __device__ __forceinline__ void reg_fence(uint32_t (&d)[N]) {
#pragma unroll
    for (int i = 0; i < N; i++) asm volatile("" : "+r"(d[i])::"memory");
}
__device__ __forceinline__ void tma2d(uint32_t dst, const CUtensorMap* tm, int c0, int c1, uint32_t bar) {
    asm volatile("cp.async.bulk.tensor.2d.shared::cluster.global.mbarrier::complete_tx::bytes [%0], [%1, {%3, %4}], [%2];"
                 ::"r"(dst), "l"(tm), "r"(bar), "r"(c0), "r"(c1) : "memory");
}
__device__ __forceinline__ void tma4d(uint32_t dst, const CUtensorMap* tm, int c0, int c1, int c2, int c3, uint32_t bar) {
    asm volatile("cp.async.bulk.tensor.4d.shared::cluster.global.mbarrier::complete_tx::bytes [%0], [%1, {%3, %4, %5, %6}], [%2];"
                 ::"r"(dst), "l"(tm), "r"(bar), "r"(c0), "r"(c1), "r"(c2), "r"(c3) : "memory");
}
__device__ __forceinline__ bool named_bar_or(int id, int n, bool v) {
    uint32_t r;
    asm volatile("{\n.reg .pred p, q;\nsetp.ne.u32 q, %3, 0;\nbar.red.or.pred p, %1, %2, q;\nselp.u32 %0, 1, 0, p;\n}"
                 : "=r"(r) : "r"(id), "r"(n), "r"((uint32_t)v) : "memory");
    return r;
}

template <uint32_t AHI, int ACC>
__device__ __forceinline__ void wgmma_n64_ss(float (&d)[32], uint32_t da, uint32_t db) {
    asm volatile(
        "{\n.reg .pred p;\n.reg .b64 da, db;\nsetp.ne.b32 p, %36, 0;\nmov.b64 da, {%32, %34};\nmov.b64 db, {%33, %35};\n"
        "wgmma.mma_async.sync.aligned.m64n64k16.f32.bf16.bf16 "
        "{%0,%1,%2,%3,%4,%5,%6,%7,%8,%9,%10,%11,%12,%13,%14,%15,%16,%17,%18,%19,%20,%21,%22,%23,%24,%25,%26,%27,%28,%29,%30,%31},"
        "da, db, p, 1, 1, 0, 1;\n}\n"
        : F16(d, 0), F16(d, 16)
        : "r"(da), "r"(db), "n"(AHI), "n"(HI128), "n"(ACC));
}


template <int ACC>
__device__ __forceinline__ void wgmma_n56_ss(float (&d)[28], uint32_t da, uint32_t db) {
    asm volatile(
        "{\n.reg .pred p;\n.reg .b64 da, db;\nsetp.ne.b32 p, %31, 0;\nmov.b64 da, {%28, %30};\nmov.b64 db, {%29, %30};\n"
        "wgmma.mma_async.sync.aligned.m64n56k16.f32.f16.f16 "
        "{%0,%1,%2,%3,%4,%5,%6,%7,%8,%9,%10,%11,%12,%13,%14,%15,%16,%17,%18,%19,%20,%21,%22,%23,%24,%25,%26,%27},"
        "da, db, p, 1, 1, 1, 0;\n}\n"
        : F16(d, 0), F8(d, 16), F4(d, 24)
        : "r"(da), "r"(db), "n"(HI128), "n"(ACC));
}

template <int SA>
__device__ __forceinline__ void wgmma_n160_h(uint32_t (&d)[40], uint32_t da, uint32_t db) {
    asm volatile(
        "{\n.reg .pred p;\n.reg .b64 da, db;\nsetp.eq.b32 p, 0, 0;\nmov.b64 da, {%40, %43};\nmov.b64 db, {%41, %43};\n"
        "wgmma.mma_async.sync.aligned.m64n160k16.f16.f16.f16 "
        "{%0,%1,%2,%3,%4,%5,%6,%7,%8,%9,%10,%11,%12,%13,%14,%15,%16,%17,%18,%19,%20,%21,%22,%23,%24,%25,%26,%27,"
        "%28,%29,%30,%31,%32,%33,%34,%35,%36,%37,%38,%39},"
        "da, db, p, %42, 1, 1, 0;\n}\n"
        : R8(d, 0), R8(d, 8), R8(d, 16), R8(d, 24), R8(d, 32)
        : "r"(da), "r"(db), "n"(SA), "n"(HI128));
}
template <int SA>
__device__ __forceinline__ void wgmma_n160_f(float (&d)[80], uint32_t da, uint32_t db) {
    asm volatile(
        "{\n.reg .pred p;\n.reg .b64 da, db;\nsetp.eq.b32 p, 0, 0;\nmov.b64 da, {%80, %83};\nmov.b64 db, {%81, %83};\n"
        "wgmma.mma_async.sync.aligned.m64n160k16.f32.bf16.bf16 "
        "{%0,%1,%2,%3,%4,%5,%6,%7,%8,%9,%10,%11,%12,%13,%14,%15,%16,%17,%18,%19,%20,%21,%22,%23,%24,%25,%26,%27,"
        "%28,%29,%30,%31,%32,%33,%34,%35,%36,%37,%38,%39,%40,%41,%42,%43,%44,%45,%46,%47,%48,%49,%50,%51,%52,%53,%54,%55,"
        "%56,%57,%58,%59,%60,%61,%62,%63,%64,%65,%66,%67,%68,%69,%70,%71,%72,%73,%74,%75,%76,%77,%78,%79},"
        "da, db, p, %82, 1, 1, 0;\n}\n"
        : F16(d, 0), F16(d, 16), F16(d, 32), F16(d, 48), F16(d, 64)
        : "r"(da), "r"(db), "n"(SA), "n"(HI128));
}

__device__ __forceinline__ uint32_t pack_f16(float lo, float hi) {
    uint32_t r;
    asm("cvt.rn.f16x2.f32 %0, %1, %2;" : "=r"(r) : "f"(hi), "f"(lo));
    return r;
}
__device__ __forceinline__ uint32_t mul_bf16x2(uint32_t a, uint32_t b) {
    uint32_t r;
    asm("mul.rn.bf16x2 %0, %1, %2;" : "=r"(r) : "r"(a), "r"(b));
    return r;
}
__device__ __forceinline__ void sts128(uint32_t p, uint32_t a, uint32_t b, uint32_t c, uint32_t d) {
    asm volatile("st.shared.v4.b32 [%0], {%1,%2,%3,%4};" ::"r"(p), "r"(a), "r"(b), "r"(c), "r"(d) : "memory");
}
__device__ __forceinline__ uint32_t pack_bf16(float lo, float hi) {
    uint32_t r;
    asm("cvt.rn.bf16x2.f32 %0, %1, %2;" : "=r"(r) : "f"(hi), "f"(lo));
    return r;
}
__device__ __forceinline__ void stg128(void* p, uint32_t a, uint32_t b, uint32_t c, uint32_t d) {
    asm volatile("st.global.v4.b32 [%0], {%1,%2,%3,%4};" ::"l"(p), "r"(a), "r"(b), "r"(c), "r"(d) : "memory");
}
__device__ __forceinline__ void stmatrix_x4_t(uint32_t addr, uint32_t a, uint32_t b, uint32_t c, uint32_t d) {
    asm volatile("stmatrix.sync.aligned.m8n8.x4.trans.shared.b16 [%0], {%1,%2,%3,%4};"
                 ::"r"(addr), "r"(a), "r"(b), "r"(c), "r"(d) : "memory");
}

constexpr uint32_t cos64(int k, bool half) {
    constexpr uint16_t q[17] = {0x3F80, 0x3F7F, 0x3F7B, 0x3F75, 0x3F6D, 0x3F62, 0x3F55, 0x3F46, 0x3F35, 0x3F22, 0x3F0E, 0x3EF1, 0x3EC4, 0x3E95, 0x3E48, 0x3DC9, 0x0000};
    constexpr uint16_t h[17] = {0x3C00, 0x3BF6, 0x3BD9, 0x3BA8, 0x3B64, 0x3B0E, 0x3AA7, 0x3A2F, 0x39A8, 0x3913, 0x3872, 0x378B, 0x361F, 0x34A5, 0x323E, 0x2E46, 0x0000};
    k &= 63;
    if (k > 32) k = 64 - k;
    const uint16_t* t = half ? h : q;
    return k <= 16 ? t[k] : (t[32 - k] | 0x8000u);
}
constexpr uint32_t fwd_coef(int s, int p, int t) { return (p && s == 0) ? cos64(32 * t, false) : cos64(s * t - 16 * p, false); }
constexpr uint32_t inv_coef(int l, int phi) {
    const int s = phi >> 1, p = phi & 1;
    if (l >= kMO) return 0;
    const uint32_t c = s == 0 ? cos64(32 * l * p, true) : cos64(s * l + 16 * p, true);
    return (c & 0x7FFF) ? c - ((s == 0 ? 6 : 5) << 10) : 0;
}
struct Tables {
    uint32_t fwd[2048];
    uint32_t inv[2048];
};
constexpr Tables make_tables() {
    Tables t = {};
    for (int i = 0; i < 2048; i++) {
        const int row = i >> 5, tt = 8 * (((i >> 2) & 7) ^ (row & 7)) + 2 * (i & 3), s = 8 * (row >> 4) + (row & 7), p = (row >> 3) & 1;
        t.fwd[i] = fwd_coef(s, p, tt) | (fwd_coef(s, p, tt + 1) << 16);
        t.inv[i] = inv_coef(row, tt) | (inv_coef(row, tt + 1) << 16);
    }
    return t;
}
__device__ __align__(128) const Tables g_tab = make_tables();

constexpr int NCTA = 128;
constexpr int NST = 4;
constexpr int HEND = 56;
constexpr int XB = kNT * 128;
constexpr int OFF_W1 = 0, OFF_X = OFF_W1 + NST * 8192, OFF_W0 = OFF_X + 4 * XB, OFF_RAW = OFF_W0 + NST * 8192;
constexpr int OFF_STG = OFF_RAW + 32768;
constexpr int OFF_U0 = OFF_W0, OFF_U1 = OFF_X, OFF_C1 = OFF_W1, OFF_DIR = OFF_W1 + 8192;
constexpr int OFF_F = OFF_RAW + 65536;
constexpr int OFF_G = OFF_F + 8192;
constexpr int OFF_C0 = OFF_G, OFF_NRM = OFF_G + 2560;
constexpr int OFF_BAR = OFF_G + 4096;
constexpr int B_FULL = 0, B_EMPTY = 8 * NST, B_TSEL = 16 * NST, B_PRE = B_TSEL + 8, B_SIG = B_PRE + 16 * V0, B_YS = B_SIG + 8 * 33,
              B_T2 = B_YS + 8 * 4, B_SUM = B_T2 + 8, B_GATE = B_SUM + 16, B_RDY = B_GATE + 8 * 32, B_PUB = B_RDY + 8 * 33, B_UNIT = B_PUB + 8,
              B_FTAB = B_UNIT + 8 * 20, B_C1 = B_FTAB + 8, B_NRM = B_C1 + 8, B_END = B_NRM + 16;
template <int O0, int O1>
__device__ __forceinline__ void bar_setup(uint32_t bars) {
#pragma unroll
    for (int o = O0; o < O1; o += 8)
        mbar_init(bars + o, o < B_EMPTY ? 2 : o < B_TSEL ? 8 : o == B_TSEL ? 2 : o < B_SIG ? 1 : o < B_YS - 8 ? 8 : o < B_SUM ? 4 : o < B_GATE ? 8 : 1);
    fence_mbar_init();
    fence_proxy_async_smem();
}
constexpr int OFF_TS = OFF_BAR + B_END;
constexpr int OFF_PLAN = OFF_TS + 320;
constexpr int OFF_YT = OFF_PLAN + (V0 + 65) * 8;
constexpr int OFF_GB = OFF_YT + 4 * kNT * 4;
constexpr int MAIN_SMEM = OFF_GB + 1024;
static_assert(MAIN_SMEM <= 232448 && OFF_U0 + 10 * 8192 == OFF_STG + 16384, "shared memory");
constexpr int XPC = 2 * kNT;
constexpr unsigned PROBE_NEAR = 400;

__device__ __forceinline__ uint32_t raw_slot(uint32_t sbase, uint32_t v, int wg) { return sbase + OFF_RAW + ((v & 3) * 2 + wg) * 8192; }

__device__ __forceinline__ uint32_t pre_slot(uint32_t sbase, uint32_t v, int wg) {
    return v < 4 ? raw_slot(sbase, v, wg) : v < 8 ? sbase + OFF_X + (v - 4) * XB + wg * 8192 : sbase + (wg ? OFF_W1 : OFF_W0) + ((V0 + 3) % NST) * 8192;
}
constexpr int OFF_TMP = OFF_W1 + 8192;

template <bool DC, int I>
__device__ __forceinline__ void gemm_mma(uint32_t (&a0)[40], uint32_t (&a1)[40], uint32_t dx0, uint32_t dx1, uint32_t dw) {
    constexpr int ks = I >> 2;
    const uint32_t A0 = dw + ks * 128, A1 = A0 + 256, B0 = dx0 + ks * 2, B1 = dx1 + ks * 2;
    if ((I & 3) == 0) wgmma_n160_h<1>(a0, A0, B0);
    if ((I & 3) == 1) wgmma_n160_h<1>(a1, A1, DC ? B1 : B0);
    if ((I & 3) == 2 && !DC) wgmma_n160_h<1>(a0, A1, B1);
    if ((I & 3) == 3 && !DC) wgmma_n160_h<-1>(a1, A0, B1);
}

template <bool DC, int I0, int I1>
__device__ __forceinline__ void gemm_mmas(uint32_t (&a0)[40], uint32_t (&a1)[40], uint32_t dx0, uint32_t dx1, uint32_t dw) {
    if constexpr (I0 < I1) {
        gemm_mma<DC, I0>(a0, a1, dx0, dx1, dw);
        gemm_mmas<DC, I0 + 1, I1>(a0, a1, dx0, dx1, dw);
    }
}
__device__ __forceinline__ uint32_t y_unit(uint32_t db, uint32_t tau, uint32_t b, uint32_t pmask) {
    const uint32_t n = db * kNT + tau;
    return run_off(R_Y + n / 3, n % 3, b, pmask);
}
template <int R>
__device__ __forceinline__ void store_round(const uint32_t (&a0)[40], const uint32_t (&a1)[40], uint32_t stg, int t, int wg, uint8_t* sp,
                                            int slot, uint32_t ytab, int wsw) {
    const int w = t >> 5, lane = t & 31, m = lane >> 3, i8 = lane & 7;
    constexpr int N = R == 2 ? 4 : 8;
    named_bar(2 + wg, 128);
    const uint32_t addr = stg + i8 * 256 + (m >> 1) * 128 + (((2 * w + (m & 1)) ^ i8 ^ wsw) << 4);
#pragma unroll
    for (int j = 8 * R; j < 8 * R + N; j++) stmatrix_x4_t(addr + (j - 8 * R) * 2048, a0[2 * j], a0[2 * j + 1], a1[2 * j], a1[2 * j + 1]);
    named_bar(2 + wg, 128);
    const int row = 2 * w + (lane >> 4), phi = 2 * slot + (m & 1);
    const uint32_t src = stg + row * 256 + (m & 1) * 128 + ((i8 ^ row) << 4);
    uint8_t* dst = sp + phi * 128 + ((i8 ^ (phi & 7)) << 4);
    uint32_t v[N][4], o[N];
#pragma unroll
    for (int i = 0; i < N; i++) {
        asm volatile("ld.shared.u32 %0, [%1];" : "=r"(o[i]) : "r"(ytab + (64 * R + 8 * i + row) * 4) : "memory");
        asm volatile("ld.shared.v4.b32 {%0,%1,%2,%3}, [%4];" : "=r"(v[i][0]), "=r"(v[i][1]), "=r"(v[i][2]), "=r"(v[i][3])
                     : "r"(src + i * 2048) : "memory");
    }
#pragma unroll
    for (int i = 0; i < N; i++) stg128(dst + o[i], v[i][0], v[i][1], v[i][2], v[i][3]);
}

__device__ __forceinline__ int step_k(int h) { return h < HEND ? h >> 1 : 28 + (h & 3); }
__device__ __forceinline__ int step_m(int h) { return h < HEND ? h & 1 : (h >> 2) & 1; }
constexpr uint64_t x_mask() {
    uint64_t r = 2 | (3ull << 58);
    for (int v = 2; v < 58; v++)
        if ((0x6B >> (v & 7)) & 1) r |= 1ull << v;
    return r;
}
constexpr uint64_t XMASK = x_mask();
__device__ __forceinline__ int x_round(int v, int wg) {
    return v == 0 ? wg : (v < 60 && wg != (v & 1) && ((XMASK >> v) & 1)) ? 1 + __popcll(XMASK << (63 - v)) : -1;
}
__device__ __forceinline__ int w_step(int v, int wg) {
    return v == 0 ? -1 : v < 60 ? (wg == (v & 1) ? v - 1 : -1) : v < 62 ? 2 * v - 61 + wg : (v == 62 && wg == 0) ? 63 : -1;
}
constexpr int GMAX = (64 - RW) / 2 > 31 - 2 * RX ? (64 - RW) / 2 : 31 - 2 * RX;

__device__ __forceinline__ uint32_t plan_word(int v, int wg, int cta) {
    const int r = x_round(v, wg), h = w_step(v, wg);
    if (r < 0 && h < 0) return 0;
    const bool last = v >= 60 || (v & 1) || (v > 0 && wg == 0 && x_round(v + 1, 0) < 0);
    uint32_t off, row, gate;
    if (r >= 0) {
        const int u = r * NCTA + cta, cb = u / XPC, i = u - cb * XPC, b = i >= kNT, tau = i - b * kNT;
        row = tau & 63;
        off = (((cb % RX) * 64 + b) << 16) + ((tau >> 6) << 14) + b + 2;
        gate = cb >= RX ? 2 * (cb - RX) + 2 : 0;
    } else {
        const int ring = (h + RW - 64 % RW) % RW;
        row = 0;
        off = ((ring * 22) << 16) + (ring << 12) + 4;
        gate = h >= RW ? ((h - RW + 1) >> 1) + 1 : 0;
    }
    return (off + row * 128) | ((row & 7) << 4) | (last << 3) | ((v > 60) << 24) | (gate << 26);
}

struct Xf {
    uint32_t sbase;
    uint8_t *px, *pw;
    uint32_t cx, cw;
    uint32_t xsw;
    uint32_t dw;
    uint32_t e;
    int lane;
};
__device__ __forceinline__ uint32_t plan_load(const Xf& f, uint32_t v, int wg) {
    uint32_t e;
    asm volatile("ld.shared.u32 %0, [%1];" : "=r"(e) : "r"(f.sbase + OFF_PLAN + v * 8 + wg * 4));
    return __shfl_sync(0xffffffffu, e, 0);
}
template <bool W>
__device__ __forceinline__ void unit_mma(float (&acc)[32], const Xf& f, uint32_t raw) {
    const uint32_t dB = desc_lo(raw);
    if (W) {
        const uint32_t dG = desc_lo(f.sbase + OFF_G);
        wgmma_n64_ss<HI64, 0>(acc, dG, dB);
        wgmma_n64_ss<HI64, 1>(acc, dG + 2, dB + 128);
    } else {
        const uint32_t dF = desc_lo(f.sbase + OFF_F);
        wgmma_n64_ss<HI128, 0>(acc, dF, dB);
        wgmma_n64_ss<HI128, 1>(acc, dF + 2, dB + 128);
        wgmma_n64_ss<HI128, 1>(acc, dF + 4, dB + 256);
        wgmma_n64_ss<HI128, 1>(acc, dF + 6, dB + 384);
    }
    wg_commit();
}
constexpr int DROP = 3;
__device__ __forceinline__ uint32_t pack_sp(float lo, float hi) {
    const uint32_t r = pack_f16(lo, hi);
    return DROP ? (r + (0x10001u << DROP >> 1)) & ~(((1u << DROP) - 1) * 0x10001u) : r;
}
__device__ __forceinline__ void st_quad(uint8_t* p, const float (&acc)[32], int j0) {
    stg128(p, pack_sp(acc[j0], acc[j0 + 1]), pack_sp(acc[j0 + 4], acc[j0 + 5]), pack_sp(acc[j0 + 8], acc[j0 + 9]),
           pack_sp(acc[j0 + 12], acc[j0 + 13]));
}
template <bool W>
__device__ __forceinline__ void unit_store(float (&acc)[32], const Xf& f, uint32_t e) {
    const uint32_t sel = ((W ? f.cw >> (8 + ((e >> 12) & 15)) : e ^ (f.cx >> (8 + ((e >> 21) & 6)))) & 1) << 13;
    const uint32_t o = (e & (W ? 0xFF0F80u : 0xFFFF80u)) + ((e ^ (W ? f.cw : f.cx)) & 0x70);
    uint8_t* const b = W ? f.pw : f.px;
    uint8_t *p0 = b + (o + sel), *p1 = b + ((o ^ 64) + sel);
    reg_fence(acc);
    if (W) {
        st_quad(p0, acc, 0);
        st_quad(p1, acc, 16);
        st_quad(p0 + 4096, acc, 2);
        st_quad(p1 + 4096, acc, 18);
    } else {
        const int d = 131072 + 8192 - 2 * (int)sel;
        st_quad(p0, acc, 0);
        st_quad(p1, acc, 2);
        st_quad(p0 + d, acc, 16);
        st_quad(p1 + d, acc, 18);
    }
}
__device__ __forceinline__ void unit_done(const Xf& f, uint32_t e, uint32_t v) {
    if (e & 8) {
        __syncwarp();
        if (f.lane == 0) mbar_arrive(f.sbase + OFF_BAR + B_SIG + 8 * ((v >> 1) + ((e >> 24) & 1)));
    }
}
__device__ __forceinline__ void step_wait(Xf& f, uint32_t v, int wg) {
    const uint32_t bars = f.sbase + OFF_BAR;
    if (f.e >> 26) mbar_wait(bars + B_GATE - 8 + 8 * (f.e >> 26), 0);
    mbar_wait(bars + B_FULL + 8 * (v % NST), (v / NST) & 1);
}

template <bool DC, int KIND>
__device__ __forceinline__ void gemm_step(uint32_t (&a0)[40], uint32_t (&a1)[40], float (&at)[32], Xf& f, uint32_t v, uint32_t xs, int wg, bool first) {
    const uint32_t bars = f.sbase + OFF_BAR, sb = desc_lo(f.sbase), xb = sb + OFF_X / 16 + xs * (XB / 16), raw = raw_slot(f.sbase, v, wg);
    const uint32_t dx0 = xb + f.xsw, dx1 = xb + (f.xsw ^ 4), dw = f.dw + (v % NST) * 512, e = f.e;
    wg_fence();
    if (KIND) unit_mma<KIND != 1>(at, f, raw);
    constexpr int N1 = KIND == 0 ? 2 : NPRE;
    gemm_mmas<DC, 0, N1>(a0, a1, dx0, dx1, dw);
    wg_commit();
    f.e = plan_load(f, v + 1, wg);
    wg_wait<1>();
    if (!KIND && !first && f.lane == 0) mbar_arrive(bars + B_EMPTY + 8 * ((v - 1) % NST));
    if (KIND) unit_store<KIND != 1>(at, f, e);
    if (KIND) unit_done(f, e, v);
    gemm_mmas<DC, N1, 7>(a0, a1, dx0, dx1, dw);
    if (KIND && !first && f.lane == 0) mbar_arrive(bars + B_EMPTY + 8 * ((v - 1) % NST));
    gemm_mma<DC, 7>(a0, a1, dx0, dx1, dw);
    wg_commit();
}
template <bool DC>
__device__ __forceinline__ void any_step(uint32_t (&a0)[40], uint32_t (&a1)[40], float (&at)[32], Xf& f, uint32_t v, uint32_t xs, int wg, bool first) {
    step_wait(f, v, wg);
    const uint32_t kind = (f.e >> 1) & 3;
    if (kind == 1) gemm_step<DC, 1>(a0, a1, at, f, v, xs, wg, first);
    else if (kind == 2) gemm_step<DC, 2>(a0, a1, at, f, v, xs, wg, first);
    else gemm_step<DC, 0>(a0, a1, at, f, v, xs, wg, first);
}
template <bool DC>
__device__ __forceinline__ void gemm_main(uint32_t (&a0)[40], uint32_t (&a1)[40], uint32_t (&b0)[40], uint32_t (&b1)[40], Xf& f, int wg) {
    float at[32];
#pragma unroll 1
    for (uint32_t k = 0; k < HEND / 2; k++) {
        any_step<DC>(a0, a1, at, f, V0 + 2 * k, k & 3, wg, k == 0);
        any_step<DC>(b0, b1, at, f, V0 + 2 * k + 1, k & 3, wg, false);
    }
    wg_wait<0>();
    if (f.lane == 0) mbar_arrive(f.sbase + OFF_BAR + B_EMPTY + 8 * ((V0 + HEND - 1) % NST));
}
template <bool DC>
__device__ __forceinline__ void gemm_last(uint32_t (&a0)[40], uint32_t (&a1)[40], Xf& f, int wg, int m) {
    const uint32_t bars = f.sbase + OFF_BAR, sb = desc_lo(f.sbase);
    mbar_wait(bars + B_FULL + 8 * ((V0 + HEND) % NST), ((V0 + HEND) / NST + m) & 1);
    if (2 * m + wg > 0) named_bar(3 + 2 * m + wg, 256);
#pragma unroll 1
    for (uint32_t k = 0; k < 4; k++) {
        const uint32_t v = V0 + HEND + 4 * m + k, xb = sb + OFF_X / 16 + k * (XB / 16);
        wg_fence();
        gemm_mmas<DC, 0, 8>(a0, a1, xb + f.xsw, xb + (f.xsw ^ 4), f.dw + (v % NST) * 512);
        wg_commit();
        if (k == 3) break;
        mbar_wait(bars + B_FULL + 8 * ((v + 1) % NST), ((v + 1) / NST) & 1);
        wg_wait<1>();
        if (k && f.lane == 0) mbar_arrive(bars + B_EMPTY + 8 * ((v - 1) % NST));
    }
    if (2 * m + wg < 3) named_arrive(4 + 2 * m + wg, 256);
    wg_wait<1>();
    if (f.lane == 0) mbar_arrive(bars + B_EMPTY + 8 * ((V0 + HEND + 2) % NST));
    wg_wait<0>();
    if (f.lane == 0) {
        mbar_arrive(bars + B_EMPTY + 8 * ((V0 + HEND + 3) % NST));
        if (2 * m + wg == 2) mbar_arrive(bars + B_T2);
    }
}

__device__ __forceinline__ float gelu_half(float hv) {
    float th;
    asm("tanh.approx.f32 %0, %1;" : "=f"(th) : "f"(hv * fmaf(hv * hv, 8.0f * 0.7978845608028654f * 0.044715f, 2.0f * 0.7978845608028654f)));
    return fmaf(hv, th, hv);
}
__device__ __noinline__ void direct_block(const __nv_bfloat16* __restrict__ x, const __nv_bfloat16* __restrict__ w,
                                          const __nv_bfloat16* __restrict__ gamma, const __nv_bfloat16* __restrict__ beta,
                                          __nv_bfloat16* __restrict__ out, float* sm, int b, int db, int part, uint32_t epoch) {
    float *xs = sm, *ws = sm + 64 * 17, *red = ws + 16 * 65;
    const int tid = threadIdx.x, tx = tid & 15, ty = tid >> 4, row0 = part * 500, lim = min(500, kL - row0);
    float* h = g_direct + (size_t)((b * 8 + db) * 16 + part) * (500 * 64);
    for (int l0 = 0; l0 < lim; l0 += 64) {
        float acc[4][4] = {};
        for (int k0 = 0; k0 < 31 * 512; k0 += 16) {
            named_bar(1, 256);
            for (int i = tid; i < 1024; i += 256) {
                xs[(i >> 4) * 17 + (i & 15)] = __bfloat162float(x[((size_t)b * kRows + row0 + min(l0 + (i >> 4), lim - 1)) * 1024 + k0 + (i & 15)]);
                ws[(i >> 6) * 65 + (i & 63)] = __bfloat162float(w[(size_t)(k0 + (i >> 6)) * 512 + 64 * db + (i & 63)]);
            }
            named_bar(1, 256);
            for (int k = 0; k < 16; k++)
#pragma unroll
                for (int i = 0; i < 4; i++)
#pragma unroll
                    for (int j = 0; j < 4; j++) acc[i][j] = fmaf(xs[(ty * 4 + i) * 17 + k], ws[k * 65 + tx * 4 + j], acc[i][j]);
        }
#pragma unroll
        for (int i = 0; i < 4; i++)
#pragma unroll
            for (int j = 0; j < 4; j++)
                if (l0 + ty * 4 + i < lim) h[(l0 + ty * 4 + i) * 64 + tx * 4 + j] = acc[i][j];
    }
    const int c = tid & 63;
    float stat[2] = {0.f, 0.f};
    for (int r = 0; r < 2; r++) {
        named_bar(1, 256);
        float s = 0.f;
        for (int l = tid >> 6; l < lim; l += 4) {
            const float v = h[l * 64 + c] - stat[0];
            s += r ? v * v : v;
        }
        red[tid] = s;
        named_bar(1, 256);
        unsigned long long* p = g_dpart + ((r * 16 + b * 8 + db) * 16) * 64 + c;
        if (tid < 64)
            asm volatile("st.relaxed.gpu.global.v2.b32 [%0], {%1, %2};" ::"l"(p + part * 64),
                         "r"(__float_as_uint(red[c] + red[64 + c] + red[128 + c] + red[192 + c])), "r"(epoch) : "memory");
        s = 0.f;
        for (int k = 0; k < 16; k++) {
            unsigned long long v = 0;
#pragma unroll 1
            for (uint32_t n = 0; n < (1u << 20); n++) {
                asm volatile("ld.relaxed.gpu.global.u64 %0, [%1];" : "=l"(v) : "l"(p + k * 64) : "memory");
                if ((uint32_t)(v >> 32) == epoch) break;
                __nanosleep(200);
            }
            s += __uint_as_float((uint32_t)v);
        }
        stat[r] = s * (1.0f / kL);
    }
    const float a = __bfloat162float(gamma[64 * db + c]) / sqrtf(stat[1] + 1e-5f), be = __bfloat162float(beta[64 * db + c]);
    for (int l = tid >> 6; l < lim; l += 4)
        out[((size_t)b * kL + row0 + l) * 512 + 64 * db + c] = __float2bfloat16(gelu_half(0.5f * fmaf(h[l * 64 + c] - stat[0], a, be)));
    named_bar(1, 256);
}

__device__ __forceinline__ int tail_block(uint32_t gr, int h) { return ((gr >> 4) & 3) ^ (5 * h); }
__device__ __forceinline__ void tail_poll(const volatile uint32_t* ts, int h) {
    const uint32_t gr = ts[64];
#pragma unroll 1
    for (uint32_t n = 0; n < (1u << 15); n++) {
        unsigned v;
        asm volatile("ld.relaxed.gpu.global.u32 %0, [%1];" : "=r"(v) : "l"(&g_yready[((gr >> 6) * 8 + tail_block(gr, h)) * 32]) : "memory");
        if (v >= 32) break;
        __nanosleep(YSLEEP);
    }
    asm volatile("fence.acquire.gpu;" ::: "memory");
    asm volatile("fence.proxy.async.global;" ::: "memory");
}
__device__ __forceinline__ void tail_loads(uint32_t sbase, const uint8_t* sp, const volatile uint32_t* ts, int h, int u0, int u1, int lane) {
    const uint32_t gr = ts[64];
    if (lane >= u0 && lane < u1) {
        const uint32_t bar = sbase + OFF_BAR + B_UNIT + 8 * (10 * h + lane);
        mbar_expect_tx(bar, 8192);
        bulk_g2s(sbase + (h ? OFF_U1 : OFF_U0) + lane * 8192, sp + y_unit(tail_block(gr, h), (gr & 15) * 10 + lane, gr >> 6, ts[66]), 8192, bar);
    }
    __syncwarp();
}
__device__ __forceinline__ const float* corr_src(uint32_t gr, int h) { return &g_corr[(((gr >> 6) * 8 + tail_block(gr, h)) * kNT + (gr & 15) * 10) * 64]; }
__device__ __forceinline__ void corr_load(uint32_t sbase, uint32_t gr, int h, uint32_t bar) { bulk_g2s(sbase + (h ? OFF_C1 : OFF_C0), corr_src(gr, h), 2560, bar); }
__device__ __forceinline__ void tail_phase(uint32_t sbase, uint8_t* smem, uint8_t* sp, int wg, const __nv_bfloat16* __restrict__ x,
                                           const __nv_bfloat16* __restrict__ wt, const __nv_bfloat16* __restrict__ gamma,
                                           const __nv_bfloat16* __restrict__ beta, __nv_bfloat16* __restrict__ out) {
    const uint32_t* ts = reinterpret_cast<const uint32_t*>(smem + OFF_TS);
    const uint32_t gr = __shfl_sync(0xffffffffu, ts[64], 0);
    const float sx = __uint_as_float(ts[74]), sw = __uint_as_float(ts[75]);
    const uint32_t epoch = ts[76];
    const float* nrm = reinterpret_cast<const float*>(smem + OFF_NRM);
    const int tid = threadIdx.x, w = (tid >> 5) & 3, lane = tid & 31, g = lane >> 2, q = lane & 3;
    const int b = gr >> 6, late = (gr >> 4) & 1, part = gr & 15;
    mbar_wait(sbase + OFF_BAR + B_FTAB, 0);
#pragma unroll 1
    for (int rd = 0; rd < 3; rd++) {
        if (rd < 2) {
            float acc[28], acc2[28], s[8] = {0.f, 0.f, 0.f, 0.f, 0.f, 0.f, 0.f, 0.f};
            const float swq = q == 0 ? sw : 0.f;
            const uint32_t ub = sbase + (rd ? OFF_U1 : OFF_U0), ubar = sbase + OFF_BAR + B_UNIT + 80 * rd;
            const float* c1 = reinterpret_cast<const float*>(smem + (rd ? OFF_C1 : OFF_C0)) + 16 * w + g;
            const uint32_t ka = ub + (lane >> 4) * 1024 + (lane & 7) * 128 + (((2 * w + ((lane >> 3) & 1)) ^ (lane & 7)) << 4);
            const bool alt = rd || late;
            const int du = alt ? 2 : 1, u0 = alt ? wg : wg * NU0, ul = alt ? 8 + wg : wg ? 9 : NU0 - 1;
            auto inverse = [&](float (&d)[28], int u) {
                const uint32_t dA = desc_lo(ub + u * 8192), dB = desc_lo(sbase + OFF_F);
                wg_fence();
                wgmma_n56_ss<0>(d, dA, dB);
                wgmma_n56_ss<1>(d, dA + 128, dB + 2);
                wgmma_n56_ss<1>(d, dA + 256, dB + 4);
                wgmma_n56_ss<1>(d, dA + 384, dB + 6);
                wg_commit();
            };
            auto keep = [&](float (&d)[28], int u, int un) {
                const bool ok = mbar_try(ubar + 8 * un, 0);
                reg_fence(d);
                d[25] = fmaf(c1[u * 64] * sx, swq, d[25]);
                d[27] = fmaf(c1[u * 64 + 8] * sx, swq, d[27]);
                if (part == 15 && u == 9) {
                    if (q >= 2) d[16] = d[18] = 0.f;
                    if (q >= 1) d[17] = d[19] = 0.f;
#pragma unroll
                    for (int i = 20; i < 28; i++) d[i] = 0.f;
                }
                const uint32_t a = ka + u * 8192;
#pragma unroll
                for (int j = 0; j < 6; j += 2)
                    stmatrix_x4_t(a + j * 1024, pack_f16(d[4 * j], d[4 * j + 1]), pack_f16(d[4 * j + 2], d[4 * j + 3]),
                                  pack_f16(d[4 * j + 4], d[4 * j + 5]), pack_f16(d[4 * j + 6], d[4 * j + 7]));
                asm volatile("stmatrix.sync.aligned.m8n8.x2.trans.shared.b16 [%0], {%1,%2};"
                             ::"r"(a + 6 * 1024), "r"(pack_f16(d[24], d[25])), "r"(pack_f16(d[26], d[27])) : "memory");
#pragma unroll
                for (int i = 0; i < 28; i++) {
                    s[i & 3] += d[i];
                    s[4 + (i & 3)] = fmaf(d[i], d[i], s[4 + (i & 3)]);
                }
#pragma unroll
                for (int i = 0; i < 8; i++) asm volatile("" : "+f"(s[i]));
                if (!ok) mbar_wait(ubar + 8 * un, 0);
                wg_wait<0>();
            };
            if (rd) mbar_wait(sbase + OFF_BAR + B_C1, 0);
            mbar_wait(ubar + 8 * u0, 0);
            inverse(acc, u0);
            mbar_wait(ubar + 8 * (u0 + du), 0);
            wg_wait<0>();
#pragma unroll 1
            for (int u = u0; u <= ul; u += 2 * du) {
                const int u2 = min(u + 2 * du, ul);
                inverse(acc2, min(u + du, ul));
                keep(acc, u, u2);
                if (u == ul) break;
                inverse(acc, u2);
                keep(acc2, u + du, min(u + 3 * du, ul));
            }
#pragma unroll
            for (int i = 0; i < 8; i += 2) {
                s[i] += s[i + 1];
                s[i] += __shfl_xor_sync(0xffffffffu, s[i], 1);
                s[i] += __shfl_xor_sync(0xffffffffu, s[i], 2);
            }
            const float mine = q == 0 ? s[0] : q == 1 ? s[2] : q == 2 ? s[4] : s[6];
            asm volatile("red.relaxed.gpu.global.add.u64 [%0], %1;"
                         ::"l"(part_sums(sp, b, tail_block(gr, rd)) + 2 * (16 * w + 8 * (q & 1) + g) + (q >> 1)),
                         "l"(fabsf(mine) < 0x1p25f ? __float2ll_rn(mine * 0x1p21f) * 4096 + 1 : 65ll) : "memory");
            __syncwarp();
            if (lane == 0) mbar_arrive(sbase + OFF_BAR + B_SUM + 8 * rd);
        }
        const int h = rd >> 1, db = tail_block(gr, h);
        if (rd == 0 && late) continue;
#pragma unroll 1
        for (uint32_t n = 0; n < (1u << 20); n++)
            if (mbar_try(sbase + OFF_BAR + B_NRM + 8 * h, 0)) break;
        if (reinterpret_cast<const volatile uint32_t*>(ts)[77 + h]) {
            if (rd != 1 || late) direct_block(x, wt, gamma, beta, out, reinterpret_cast<float*>(smem + OFF_DIR), b, db, part, epoch);
            continue;
        }
        const int jh = w & 1, r0 = 8 * (w >> 1), cut = h || late ? 256 : FC0, mid = wg ? FC0 + FA1 : FA0;
        const int i0 = rd == 1 && !late ? mid : wg ? cut : 0, i1 = rd == 0 ? mid : wg ? 512 : cut;
        const int lim = min(500, kL - part * 500) - r0 - g;
        float na[8], nb[8];
#pragma unroll
        for (int i = 0; i < 8; i++) {
            const int col = 32 * jh + 8 * (i >> 1) + 2 * q + (i & 1);
            na[i] = nrm[h * 128 + col];
            nb[i] = nrm[h * 128 + 64 + col];
        }
        __nv_bfloat16* o = out + ((size_t)b * kL + part * 500 + i0 + r0 + g) * 512 + 64 * db + 32 * jh + 8 * q;
        const int row = i0 + r0 + (lane & 7);
        int l = row % kMO;
        uint32_t ra = sbase + (h ? OFF_U1 : OFF_U0) + row / kMO * 8192 + l * 128;
        const int cc = 4 * jh + (lane >> 3);
        auto fetch = [&](uint32_t (&r)[4]) {
            asm volatile("ldmatrix.sync.aligned.m8n8.x4.shared.b16 {%0,%1,%2,%3}, [%4];"
                         : "=r"(r[0]), "=r"(r[1]), "=r"(r[2]), "=r"(r[3]) : "r"(ra + (((cc ^ l) & 7) << 4)) : "memory");
            const bool wrap = l >= kMO - 16;
            l += wrap ? 16 - kMO : 16;
            ra += wrap ? 2048 + 8192 - kMO * 128 : 2048;
        };
        auto gelu8 = [&](const uint32_t (&r)[4], uint32_t (&p)[4]) {
#pragma unroll
            for (int i = 0; i < 4; i++) {
                float lo, hi;
                asm("{\n.reg .b16 a, b;\nmov.b32 {a, b}, %2;\ncvt.f32.f16 %0, a;\ncvt.f32.f16 %1, b;\n}" : "=f"(lo), "=f"(hi) : "r"(r[i]));
                p[i] = pack_bf16(gelu_half(fmaf(lo, na[2 * i], nb[2 * i])), gelu_half(fmaf(hi, na[2 * i + 1], nb[2 * i + 1])));
            }
        };
        uint32_t r[2][4], rn[2][4];
        fetch(r[0]);
        fetch(r[1]);
#pragma unroll 1
        for (int i = i0; i < i1; i += 32) {
            fetch(rn[0]);
            fetch(rn[1]);
            uint32_t p0[4], p1[4];
            gelu8(r[0], p0);
            gelu8(r[1], p1);
            if (i < lim) stg128(o, p0[0], p0[1], p0[2], p0[3]);
            if (i + 16 < lim) stg128(o + 16 * 512, p1[0], p1[1], p1[2], p1[3]);
            o += 32 * 512;
#pragma unroll
            for (int k = 0; k < 4; k++) { r[0][k] = rn[0][k]; r[1][k] = rn[1][k]; }
        }
    }
}
__device__ __forceinline__ void channel_scales(uint32_t sbase, uint8_t* smem, uint8_t* sp, int lane) {
    volatile uint32_t* ts = reinterpret_cast<volatile uint32_t*>(smem + OFF_TS);
    const uint32_t gr = ts[64], epoch = ts[76], bars = sbase + OFF_BAR;
#pragma unroll 1
    for (int h = 0; h < 2; h++) {
#pragma unroll 1
        for (uint32_t n = 0; n < (1u << 20); n++)
            if (mbar_try(bars + B_SUM + 8 * h, 0)) break;
        long long s[4];
#pragma unroll 1
        for (uint32_t n = 0; n < (1u << 19); n++) {
            const unsigned long long* p = part_sums(sp, gr >> 6, tail_block(gr, h)) + 4 * lane;
#pragma unroll
            for (int i = 0; i < 4; i++) asm volatile("ld.relaxed.gpu.global.u64 %0, [%1];" : "=l"(s[i]) : "l"(p + i) : "memory");
            if (__all_sync(0xffffffffu, s[0] & s[1] & s[2] & s[3] & 32)) break;
        }
        const float sx = __uint_as_float(ts[74]), sw = __uint_as_float(ts[75]);
        bool bad = false;
#pragma unroll
        for (int i = 0; i < 2; i++) {
            const int c = 2 * lane + i;
            const float mean = (float)(s[2 * i] >> 12) * (0x1p-21f / kL), sq = (float)(s[2 * i + 1] >> 12) * (0x1p-21f / kL);
            const float2 gb = reinterpret_cast<const float2*>(smem + OFF_GB)[64 * h + c];
            const float den = fmaxf(sq - mean * mean, 0.f) + 1e-5f * sx * sw * sx * sw, a = gb.x * rsqrtf(den);
            float* nrm = reinterpret_cast<float*>(smem + OFF_NRM) + h * 128 + c;
            nrm[0] = 0.5f * a;
            nrm[64] = 0.5f * (gb.y - mean * a);
            bad |= ((s[2 * i] | s[2 * i + 1]) & 0xFC0) || !(den >= 0x1p-22f);
        }
        bad = __any_sync(0xffffffffu, bad);
        if (lane == 0) ts[77 + h] = bad;
        __syncwarp();
        if (lane == 0) mbar_arrive(bars + B_NRM + 8 * h);
    }
    unsigned exits = 0;
    if (lane == 0) exits = atomicAdd(&g_exit, 1);
    if (__shfl_sync(0xffffffffu, exits, 0) == NCTA - 1) {
        for (int i = 0; i < 4; i++) *chunk_flag(sp, i >> 1, i & 1, lane) = 0;
        if (lane < 2) *chunk_flag(sp, 0, lane, 32) = 0;
        g_tsel[lane] = 0;
        if (lane < 16) g_yready[lane * 32] = 0;
#pragma unroll 1
        for (int i = 0; i < 32; i++) stg128(part_sums(sp, i >> 4, (i >> 1) & 7) + (i & 1) * 64 + 2 * lane, 0, 0, 0, 0);
        if (lane == 0) { g_exit = 0; g_epoch = epoch; }
    }
}

__device__ __forceinline__ void publish_tiles(uint32_t bars, int cta, int wg) {
#pragma unroll 1
    for (int m = 0; m < 2; m++) {
        mbar_wait(bars + B_YS + 8 * (2 * m + wg), 0);
        asm volatile("fence.acq_rel.gpu;" ::: "memory");
        red_relaxed(&g_yready[((cta & 2) * 4 + 4 * m + 2 * (cta & 1) + wg) * 32]);
    }
}

__global__ void __launch_bounds__(384, 1)
main_kernel(const __grid_constant__ CUtensorMap tmx, const __grid_constant__ CUtensorMap tmw0, const __grid_constant__ CUtensorMap tmw1,
            const __nv_bfloat16* __restrict__ x, const __nv_bfloat16* __restrict__ wt, const __nv_bfloat16* __restrict__ gamma,
            const __nv_bfloat16* __restrict__ beta, __nv_bfloat16* __restrict__ out) {
    extern __shared__ __align__(1024) uint8_t smem_raw[];
    const uint32_t sbase = smem_u32(smem_raw) & ~1023u;
    const uint32_t bars = sbase + OFF_BAR;
    const int tid = threadIdx.x, wg = __shfl_sync(0xffffffffu, tid >> 7, 0), lane = tid & 31;
    const int cta = blockIdx.x;
    volatile uint32_t* ts = reinterpret_cast<volatile uint32_t*>(smem_raw + OFF_TS);
    uint8_t* const sp = reinterpret_cast<uint8_t*>((reinterpret_cast<uintptr_t>(g_sp) + (2u << 20) - 1) & ~(uintptr_t)((2u << 20) - 1));
    const bool probing = (cta & 3) == 0 && lane == 0 && tid < 128;
    unsigned* pw = reinterpret_cast<unsigned*>(sp + (tid < 64 ? ((cta >> 2) << 21) + ((tid & 32) ? 15 : 13) * 4096
                                                              : ((tid & 32) ? 0 : 14) * 4096 + (cta >> 2) * 128));
    unsigned pv = 0;
    if (probing) {
        stg128(pw, 0, 0, 0, 0);
        stg128(pw + 4, 0, 0, 0, 0);
        asm volatile("atom.relaxed.gpu.global.exch.b32 %0, [%1], %2;" : "=r"(pv) : "l"(pw), "r"(7) : "memory");
    }
    if (tid == 320) bar_setup<0, B_SIG>(bars);
    if (tid >= 256 && tid < 262) ts[68 + tid - 256] = tid < 260 ? 0xffffu : 0;
    if (tid == 383) asm volatile("griddepcontrol.launch_dependents;");
    __syncthreads();

    if (wg == 2) {
        asm volatile("setmaxnreg.dec.sync.aligned.u32 40;");
        const int role = (tid >> 5) & 3;
        if (role == 3) {
            unsigned v = 0;
#pragma unroll 1
            for (uint32_t n = 0; n < (1u << 15); n++) {
                asm volatile("ld.relaxed.gpu.global.u32 %0, [%1];" : "=r"(v) : "l"(&g_tsel[lane]) : "memory");
                if (__all_sync(0xffffffffu, v & 16)) break;
                __nanosleep(TSLEEP);
            }
            const uint32_t m1 = __ballot_sync(0xffffffffu, v & 8), below = (1u << lane) - 1;
            const int rank = (v & 8) ? 32 - __popc(m1) + __popc(m1 & below) : __popc(~m1 & below);
            ts[lane] = rank;
            ts[32 + rank] = lane;
            const uint32_t p0 = __ballot_sync(0xffffffffu, v & 1);
            if (lane == 0) ts[66] = p0;
            if (lane == (cta >> 2)) ts[64] = rank * 4 + (cta & 3);
            const int part = (m1 >> (cta >> 2)) & 1;
            __syncwarp();
            if (lane == 0) { mbar_arrive(bars + B_TSEL); }
            mbar_wait(bars + B_TSEL, 0);
            mbar_wait(bars + B_PUB, 0);
            int gc = 0;
            const int gend = lane == 0 ? 33 : lane == 1 ? GMAX + 1 : 0;
#pragma unroll 1
            for (uint32_t n = 0; n < (1u << 16) && __any_sync(0xffffffffu, gc < gend); n++) {
                asm volatile("ld.relaxed.gpu.global.u32 %0, [%1];" : "=r"(v) : "l"(chunk_flag(sp, lane == 1, part, min(gc, 32 - (lane & 1)))) : "memory");
                if (gc < gend && v >= NCTA) {
                    asm volatile("fence.acquire.gpu;" ::: "memory");
                    mbar_arrive(bars + (lane == 0 ? B_RDY : B_GATE) + 8 * gc);
                    gc++;
                }
            }
            if (lane == 0) publish_tiles(bars, cta, 1);
        } else if (role == 0) {
            const int b = (cta >> 1) & 1, dq = cta & 1;
            for (int v = 0; v < V0; v++) {
                mbar_wait(bars + B_EMPTY + 8 * (v % NST), ((v / NST) & 1) ^ 1);
                if (lane == 0) {
                    mbar_arrive(bars + B_FULL + 8 * (v % NST));
                    mbar_arrive(bars + B_FULL + 8 * (v % NST));
                }
            }
            mbar_wait(bars + B_TSEL, 0);
            const uint32_t gr = ts[64], grp = gr >> 6, idx = (gr >> 2) & 15, pmask = ts[66];
            const uint32_t n0 = idx * 4 + 2 * dq + ((lane & 1) ^ 1), r0 = lane < 3 ? idx * 4 + b : R_W + n0 / 3;
            const uint32_t base = (r0 << 16) + 4096 + ((lane < 3 ? lane : n0 % 3) << 14), step = (lane < 3 ? 64 : 22) << 16;
            uint32_t sels = 0;
            for (int i = 0; i < 12; i++) sels |= run_sel(r0 + i * (step >> 16), grp, pmask) << i;
            int ld = 0;
            const uint32_t bytes = lane == 2 ? XB - 16384 : 8192;
#pragma unroll 1
            for (int h = 0; h < 64; h++) {
                const int s = step_k(h), st = (h + V0) % NST;
                const bool newx = h < HEND ? !(h & 1) : h < HEND + 4;
                const uint32_t fb = bars + B_FULL + 8 * st;
                const uint32_t k = lane < 3 ? (s >> 1) % RX : (h + RW - 64 % RW) % RW, half = lane < 3 ? s & 1 : 0;
                const uint8_t* gsrc = sp + (base + k * step + (half << 17) + ((((sels >> k) ^ half) & 1) << 13));
                const uint32_t dst = sbase + (lane < 3 ? OFF_X + (s & 3) * XB + lane * 8192 : st * 8192 + (lane == 3 ? OFF_W0 : OFF_W1));
                auto landed = [&]() {
                    if (ld < h && mbar_test(bars + B_FULL + 8 * ((ld + V0) % NST), ((ld + V0) / NST) & 1)) {
                        if (!(ld & 1) && (ld >> 1) <= GMAX && lane < 2) red_relaxed(chunk_flag(sp, 1, lane, ld >> 1));
                        ld++;
                    }
                };
                if ((h & 1) || h == 0) {
#pragma unroll 1
                    for (uint32_t n = 0; n < (1u << 19) && !mbar_test(bars + B_RDY + 8 * ((h + 1) >> 1), 0); n++) landed();
                    asm volatile("fence.proxy.async.global;" ::: "memory");
                }
#pragma unroll 1
                for (uint32_t n = 0; n < (1u << 19) && !mbar_test(bars + B_EMPTY + 8 * st, (((h + V0) / NST) & 1) ^ 1); n++) landed();
#pragma unroll 1
                for (uint32_t n = 0; n < (1u << 19) && ld <= h - NST; n++) landed();
                if (lane == 0) mbar_expect_tx(fb, newx ? 16384 + XB : 16384);
                __syncwarp();
                if (lane < 3 ? newx : lane < 5) bulk_g2s(dst, gsrc, bytes, fb);
            }
            tail_poll(ts, 0);
            mbar_wait(bars + B_T2, 0);
            tail_loads(sbase, sp, ts, 0, 0, 8, lane);
            mbar_wait(bars + B_YS + 16, 0);
            tail_loads(sbase, sp, ts, 0, 8, 10, lane);
            for (int v = V0 + 64; v < V0 + 64 + NST; v++) mbar_wait(bars + B_EMPTY + 8 * (v % NST), ((v / NST) & 1) ^ 1);
            tail_poll(ts, 1);
            if (!(gr & 16)) mbar_wait(bars + B_NRM, 0);
            if (lane == 0) {
                mbar_expect_tx(bars + B_C1, 2560);
                corr_load(sbase, gr, 1, bars + B_C1);
            }
            tail_loads(sbase, sp, ts, 1, 0, 10, lane);
        } else if (role == 1) {
            auto raw_load = [&](int r, int h, uint32_t gr, uint32_t dst, uint32_t bar) {
                if (r >= 0) {
                    const int u = r * NCTA + cta, i = u % XPC, b = i >= kNT;
                    tma3d(dst, &tmx, u / XPC * 64, (i - b * kNT) * kMO, b, bar);
                } else if (h >= 0) {
                    const int c = 32 * step_k(h) + ((gr >> 1) & 30);
                    tma3d_ef(dst, c < 512 ? &tmw0 : &tmw1, step_m(h) * 256 + (gr & 3) * 64, 0, c & 511, bar);
                }
            };
            uint32_t gr;
            {
                const int v = lane >> 1, r = v < V0 ? x_round(v, lane & 1) : -1, h = v < V0 ? w_step(v, lane & 1) : -1;
                const uint32_t dst = pre_slot(sbase, v, lane & 1), bar = bars + B_PRE + 8 * lane;
                if (r >= 0 || h >= 0) mbar_expect_tx(bar, r >= 0 ? 8192 : 4096);
                if (v < PRE1) raw_load(r, -1, 0, dst, bar);
                mbar_wait(bars + B_TSEL, 0);
                gr = ts[64];
                raw_load(-1, h, gr, dst, bar);
                if (v >= PRE1) raw_load(r, -1, 0, dst, bar);
                __syncwarp();
            }
            mbar_wait(bars + B_PUB, 0);
#pragma unroll 1
            for (int v = V0; v < V0 + 64; v++) {
                mbar_wait(bars + B_EMPTY + 8 * (v % NST), ((v / NST) & 1) ^ 1);
                __syncwarp();
                const int r = lane < 2 ? x_round(v, lane) : -1, h = lane < 2 ? w_step(v, lane) : -1;
                const uint32_t fb = bars + B_FULL + 8 * (v % NST);
                const uint32_t bytes = __reduce_add_sync(0xffffffffu, r >= 0 ? 8192 : h >= 0 ? 4096 : 0);
                if (lane == 0) mbar_expect_tx(fb, bytes);
                __syncwarp();
                raw_load(r, h, gr, raw_slot(sbase, v, lane), fb);
                if (v >= 63 && v < 67) {
                    if (v == 66 && lane == 0) {
#pragma unroll 1
                        for (uint32_t n = 0; n < (1u << 15); n++) {
                            unsigned c0, c1;
                            asm volatile("ld.relaxed.gpu.global.u32 %0, [%1];" : "=r"(c0) : "l"(&g_cready[(gr >> 6) * 64]) : "memory");
                            asm volatile("ld.relaxed.gpu.global.u32 %0, [%1];" : "=r"(c1) : "l"(&g_cready[(gr >> 6) * 64 + 32]) : "memory");
                            if (c0 == ts[76] && c1 == ts[76]) break;
                            __nanosleep(500);
                        }
                        asm volatile("fence.acquire.gpu;" ::: "memory");
                        asm volatile("fence.proxy.async.global;" ::: "memory");
                        mbar_expect_tx(bars + B_FTAB, 8192 + 2560);
                        bulk_g2s(sbase + OFF_F, g_tab.inv, 8192, bars + B_FTAB);
                        corr_load(sbase, gr, 0, bars + B_FTAB);
                        asm volatile("cp.async.bulk.prefetch.L2.global [%0], 2560;" ::"l"(corr_src(gr, 1)) : "memory");
                    }
                    const int t = v - 63;
                    for (int i = lane; i < kNT; i += 32)
                        ts[(OFF_YT - OFF_TS) / 4 + t * kNT + i] = y_unit(4 * (t >> 1) + 2 * (cta & 1) + (t & 1), i, (cta >> 1) & 1, ts[66]);
                }
            }
            channel_scales(sbase, smem_raw, sp, lane);
        } else {
            uint32_t epoch;
            if (lane == 0) {
                bar_setup<B_SIG, B_END>(bars);
                mbar_arrive(bars + B_TSEL);
            }
            asm volatile("ld.relaxed.gpu.global.u32 %0, [%1];" : "=r"(epoch) : "l"(&g_epoch) : "memory");
            mbar_wait(bars + B_TSEL, 0);
            const uint32_t gr = ts[64];
#pragma unroll
            for (int i = lane; i < 128; i += 32) {
                const int d = 64 * tail_block(gr, i >> 6) + (i & 33) + 8 * ((i >> 1) & 3) + 2 * ((i >> 3) & 3);
                ts[(OFF_GB - OFF_TS) / 4 + 2 * i] = (uint32_t)__bfloat16_as_ushort(gamma[d]) << 16;
                ts[(OFF_GB - OFF_TS) / 4 + 2 * i + 1] = (uint32_t)__bfloat16_as_ushort(beta[d]) << 16;
            }
            if (lane == 0) ts[76] = epoch + 1;
            __syncwarp();
            if (lane) return;
#pragma unroll 1
            for (int gc = 0; gc < 33;) {
                mbar_wait(bars + B_SIG + 8 * gc, 0);
                if (gc < MERGE) mbar_wait(bars + B_SIG + 8 * MERGE, 0);
                int ge = gc + 1;
                while (ge < 33 && mbar_test(bars + B_SIG + 8 * ge, 0)) ge++;
                asm volatile("fence.acq_rel.gpu;" ::: "memory");
                for (; gc < ge; gc++) {
                    red_relaxed(chunk_flag(sp, 0, 0, gc));
                    red_relaxed(chunk_flag(sp, 0, 1, gc));
                    if (gc == 0) mbar_arrive(bars + B_PUB);
                }
            }
            publish_tiles(bars, cta, 0);
        }
    } else {
        asm volatile("setmaxnreg.inc.sync.aligned.u32 232;");
        uint4 fw[2];
#pragma unroll
        for (int j = 0; j < 2; j++) fw[j] = __ldg(reinterpret_cast<const uint4*>(g_tab.fwd) + tid + 256 * j);
        if (wg == 1) {
            uint4 sm[8];
#pragma unroll
            for (int j = 0; j < 4; j++) {
                const int r = 2 * j + ((tid >> 6) & 1);
                sm[j] = __ldg(reinterpret_cast<const uint4*>(x) + ((r >> 2) * kRows + 1000 + 2000 * (r & 3)) * 128 + (((j + r) & 1) << 6) + (tid & 63));
                sm[4 + j] = __ldg(reinterpret_cast<const uint4*>(wt) + (4 * r * 512 + 67 * r + 7) * 64 + (tid & 63));
            }
#pragma unroll
            for (int k = 0; k < 2; k++) {
                uint32_t mx = 0;
#pragma unroll
                for (int j = 4 * k; j < 4 * k + 4; j++)
                    mx = __vmaxu2(__vmaxu2(mx, __vmaxu2(sm[j].x & 0x7FFF7FFFu, sm[j].y & 0x7FFF7FFFu)), __vmaxu2(sm[j].z & 0x7FFF7FFFu, sm[j].w & 0x7FFF7FFFu));
                mx = __reduce_max_sync(0xffffffffu, max(mx & 0xFFFFu, mx >> 16));
                if (lane == 0) atomicMax(const_cast<uint32_t*>(ts) + 72 + k, mx);
            }
        }
        if ((cta & 3) == 0) {
            if (probing) {
                const int w = tid >> 5;
                unsigned best = 0xffffu;
#pragma unroll 1
                for (int r = 0; r < 6; r++) {
                    unsigned t0, t1;
                    asm volatile("{\n.reg .pred p;\nsetp.eq.u32 p, %1, 0xffffffff;\nmov.u32 %0, 0;\n@!p mov.u32 %0, %%clock;\n}"
                                 : "=r"(t0) : "r"(pv) : "memory");
                    asm volatile("atom.relaxed.gpu.global.exch.b32 %0, [%1], %2;" : "=r"(pv) : "l"(pw), "r"(r) : "memory");
                    asm volatile("{\n.reg .pred p;\nsetp.eq.u32 p, %1, 0xffffffff;\nmov.u32 %0, 0;\n@!p mov.u32 %0, %%clock;\n}"
                                 : "=r"(t1) : "r"(pv) : "memory");
                    ts[68 + w] = best = min(best, t1 - t0);
                    const unsigned other = ts[68 + (w ^ 1)];
                    if (min(best, other) < PROBE_NEAR && max(best, other) > PROBE_NEAR) break;
                }
            }
            if (wg == 0) {
                named_bar(2, 128);
                if (tid == 0) {
                    const uint32_t part = ts[71] < ts[70];
                    const uint32_t v = 16 | (part << 3) | ((ts[69] < ts[68]) ^ part);
                    asm volatile("st.relaxed.gpu.global.u32 [%0], %1;" ::"l"(&g_tsel[cta >> 2]), "r"(v) : "memory");
                }
            }
        }
        uint32_t plan = tid < 2 * (V0 + 65) ? plan_word(tid >> 1, tid & 1, cta) : 0;
        {
            named_bar(1, 256);
            const uint32_t ex = max(251 - (int)(ts[72] >> 7), 8), ew = max(251 - (int)(ts[73] >> 7), 8);
            if (tid == 0) { ts[74] = ex << 23; ts[75] = ew << 23; }
            const uint32_t sx = ex * 0x800080u, sw = ew * 0x800080u;
#pragma unroll
            for (int j = 0; j < 2; j++) {
                const int i = tid + 256 * j, row = i >> 3, c = (i ^ row) & 7;
                sts128(sbase + OFF_F + 16 * i, mul_bf16x2(fw[j].x, sx), mul_bf16x2(fw[j].y, sx), mul_bf16x2(fw[j].z, sx), mul_bf16x2(fw[j].w, sx));
                if (c < 2) sts128(sbase + OFF_TMP + row * 32 + c * 16, mul_bf16x2(fw[j].x, sw), mul_bf16x2(fw[j].y, sw), mul_bf16x2(fw[j].z, sw), mul_bf16x2(fw[j].w, sw));
            }
            named_bar(1, 256);
        }
        const int t = tid & 127;
        Xf f;
        f.sbase = sbase; f.lane = lane; f.xsw = cta & 4; f.dw = desc_lo(sbase + (wg ? OFF_W1 : OFF_W0));
        {
            const int w = t >> 5;
            const uint32_t nw = (8 * (w & 1) + (lane >> 2)) * 4 + (cta & 3), rw = R_W + nw / 3;
            f.pw = sp + (rw << 16) + 4096 + ((nw % 3) << 14) + (w >> 1) * 128;
            f.cw = ((lane & 7) ^ (w >> 1)) << 4;
            for (int i = 0; i < RW; i++) f.cw |= run_sel(rw + i * 22, 0, 0) << (8 + i);
            mbar_wait(bars + B_TSEL, 0);
            const uint32_t gr = ts[64], pmask = ts[66];
            const uint32_t rx = ts[8 * w + (lane >> 2)];
            f.px = sp + ((rx & 15) << 18) + 4096;
            f.cx = ((lane & 7) << 4) | ((((pmask >> ((rx >> 3) & 1)) ^ -(((rx >> 1) ^ (rx >> 4)) & 1)) & 0x55) << 8);
#pragma unroll
            for (int i = 0; i < RW; i++) f.cw ^= (((pmask >> ((rw + i * 22) >> 5)) ^ (gr >> 6)) & 1) << (8 + i);
            if (plan & 4) plan |= ((gr & 12) << 8) | ((gr & 48) << 4) | ((gr & 48) << 1);
            if (tid < 2 * (V0 + 65)) ts[(OFF_PLAN - OFF_TS) / 4 + tid] = plan;
            const int row = tid >> 2, ch = tid & 3, s = ts[32 + (gr >> 6) * 16 + ((row >> 1) & 8) + (row & 7)], p = (row >> 3) & 1;
            const int frow = 16 * (s >> 3) + 8 * p + (s & 7);
            uint32_t v[4] = {0, 0, 0, 0};
            if ((ch >> 1) == (row >> 5))
                asm volatile("ld.shared.v4.b32 {%0,%1,%2,%3}, [%4];" : "=r"(v[0]), "=r"(v[1]), "=r"(v[2]), "=r"(v[3])
                             : "r"(sbase + OFF_TMP + frow * 32 + (ch & 1) * 16) : "memory");
            sts128(sbase + OFF_G + row * 64 + ((ch ^ ((row >> 1) & 3)) << 4), v[0], v[1], v[2], v[3]);
            fence_proxy_async_smem();
            named_bar(1, 256);
        }
        {
            float at[32];
#pragma unroll 1
            for (uint32_t v = 0; v < V0; v++) {
                const uint32_t e = plan_load(f, v, wg), raw = pre_slot(sbase, v, wg);
                mbar_wait(bars + B_FULL + 8 * (v % NST), (v / NST) & 1);
                if (e & 6) mbar_wait(bars + B_PRE + 16 * v + 8 * wg, 0);
                wg_fence();
                if ((e & 6) == 2) {
                    unit_mma<false>(at, f, raw);
                    wg_wait<0>();
                    unit_store<false>(at, f, e);
                } else if (e & 4) {
                    unit_mma<true>(at, f, raw);
                    wg_wait<0>();
                    unit_store<true>(at, f, e);
                }
                if (lane == 0) mbar_arrive(bars + B_EMPTY + 8 * (v % NST));
                unit_done(f, e, v);
            }
        }
        const int slot = cta >> 2;
        f.e = plan_load(f, V0, wg);
        uint32_t a0[40], a1[40], b0[40], b1[40];
#pragma unroll
        for (int i = 0; i < 40; i++) a0[i] = a1[i] = b0[i] = b1[i] = 0;
        if (slot == 0) gemm_main<true>(a0, a1, b0, b1, f, wg);
        else gemm_main<false>(a0, a1, b0, b1, f, wg);
#pragma unroll 1
        for (int m = 0; m < 2; m++) {
            if (slot == 0) gemm_last<true>(a0, a1, f, wg, m);
            else gemm_last<false>(a0, a1, f, wg, m);
            reg_fence(a0);
            reg_fence(a1);
            const int wsw = ts[64] & 4;
            const uint32_t ytab = sbase + OFF_YT + (m * 2 + wg) * (kNT * 4);
            store_round<0>(a0, a1, sbase + OFF_STG + wg * 16384, t, wg, sp, slot, ytab, wsw);
            store_round<1>(a0, a1, sbase + OFF_STG + wg * 16384, t, wg, sp, slot, ytab, wsw);
            store_round<2>(a0, a1, sbase + OFF_STG + wg * 16384, t, wg, sp, slot, ytab, wsw);
            __syncwarp();
            if (lane == 0) mbar_arrive(bars + B_YS + 8 * (2 * m + wg));
#pragma unroll
            for (int i = 0; i < 40; i++) { a0[i] = b0[i]; a1[i] = b1[i]; }
        }
        tail_phase(sbase, smem_raw, sp, wg, x, wt, gamma, beta, out);
    }
}

constexpr int C_STAGE = 32768 + 2 * XB, C_SMEM = 3 * C_STAGE + 64;
__global__ void __launch_bounds__(256, 1) corr_kernel(const __grid_constant__ CUtensorMap tmx, const __grid_constant__ CUtensorMap tmw) {
    extern __shared__ __align__(1024) uint8_t smem_raw[];
    const uint32_t sbase = smem_u32(smem_raw) & ~1023u, bars = sbase + 3 * C_STAGE;
    const int tid = threadIdx.x, wg = __shfl_sync(0xffffffffu, tid >> 7, 0), b = blockIdx.x >> 1, dh = blockIdx.x & 1;
    auto load = [&](int k) {
        const uint32_t st = sbase + (k % 3) * C_STAGE, bar = bars + 8 * (k % 3);
        mbar_expect_tx(bar, C_STAGE);
        for (int i = 0; i < 4; i++) tma2d(st + i * 8192, &tmw, 256 * dh + 64 * i, 64 * k, bar);
        tma4d(st + 32768, &tmx, 64 * k, 64 - kMO, 1, b, bar);
        tma4d(st + 32768 + XB, &tmx, 64 * k, 0, 0, b, bar);
    };
    uint32_t epoch = 0;
    if (tid == 0) {
        for (int i = 0; i < 3; i++) mbar_init(bars + 8 * i, 1);
        fence_mbar_init();
        fence_proxy_async_smem();
        for (int k = 0; k < 3; k++) load(k);
        asm volatile("ld.relaxed.gpu.global.u32 %0, [%1];" : "=r"(epoch) : "l"(&g_epoch) : "memory");
    }
    __syncthreads();
    float a[2][80];
#pragma unroll
    for (int i = 0; i < 80; i++) a[0][i] = a[1][i] = 0.f;
#pragma unroll 1
    for (int k = 0; k < 8; k++) {
        const uint32_t dA = desc_lo(sbase + (k % 3) * C_STAGE + wg * 16384), dB = desc_lo(sbase + (k % 3) * C_STAGE + 32768);
        mbar_wait(bars + 8 * (k % 3), (k / 3) & 1);
        wg_fence();
#pragma unroll
        for (int i = 0; i < 8; i++) {
            wgmma_n160_f<1>(a[i & 1], dA + (i & 1) * 512 + (i >> 1) * 128, dB + (i >> 1) * 2);
            wgmma_n160_f<-1>(a[i & 1], dA + (i & 1) * 512 + (i >> 1) * 128, dB + XB / 16 + (i >> 1) * 2);
        }
        wg_commit();
        wg_wait<0>();
        __syncthreads();
        if (tid == 0 && k + 3 < 8) load(k + 3);
    }
    reg_fence(a[0]);
    reg_fence(a[1]);
    const int w = (tid >> 5) & 3, g = (tid & 31) >> 2, q = tid & 3;
#pragma unroll
    for (int i = 0; i < 160; i++) {
        const int m = i / 80, j = i % 80, d = 16 * w + 8 * ((j >> 1) & 1) + g;
        g_corr[((b * 8 + 4 * dh + 2 * wg + m) * kNT + 8 * (j >> 2) + 2 * q + (j & 1)) * 64 + (d & 33) + 8 * ((d >> 1) & 3) + 2 * ((d >> 3) & 3)] = a[m][j];
    }
    __syncthreads();
    if (tid == 0) {
        asm volatile("fence.acq_rel.gpu;" ::: "memory");
        asm volatile("st.relaxed.gpu.global.u32 [%0], %1;" ::"l"(&g_cready[blockIdx.x * 32]), "r"(epoch + 1) : "memory");
    }
}

__global__ void __launch_bounds__(256) plain_conv(const __nv_bfloat16* __restrict__ x, const __nv_bfloat16* __restrict__ w) {
    __shared__ float xs[64][17], ws[16][65];
    float* h = reinterpret_cast<float*>(g_sp + (8u << 20));
    const int b = blockIdx.z, l0 = blockIdx.x * 64, d0 = blockIdx.y * 64, tx = threadIdx.x & 15, ty = threadIdx.x >> 4;
    float acc[4][4] = {};
    for (int k0 = 0; k0 < 31 * 512; k0 += 16) {
        for (int i = threadIdx.x; i < 1024; i += 256) {
            const int l = min(l0 + (i >> 4), kL - 1);
            xs[i >> 4][i & 15] = __bfloat162float(x[((size_t)b * kRows + l) * 1024 + k0 + (i & 15)]);
            ws[i >> 6][i & 63] = __bfloat162float(w[(size_t)(k0 + (i >> 6)) * 512 + d0 + (i & 63)]);
        }
        __syncthreads();
        for (int k = 0; k < 16; k++)
            for (int i = 0; i < 4; i++)
                for (int j = 0; j < 4; j++) acc[i][j] = fmaf(xs[ty * 4 + i][k], ws[k][tx * 4 + j], acc[i][j]);
        __syncthreads();
    }
    for (int i = 0; i < 4; i++)
        for (int j = 0; j < 4; j++)
            if (l0 + ty * 4 + i < kL) h[((size_t)b * kL + l0 + ty * 4 + i) * 512 + d0 + tx * 4 + j] = acc[i][j];
}
__global__ void __launch_bounds__(256) plain_norm(const __nv_bfloat16* __restrict__ gamma, const __nv_bfloat16* __restrict__ beta,
                                                  __nv_bfloat16* __restrict__ out) {
    __shared__ float s1[8][32], s2[8][32];
    const int c = threadIdx.x & 31, r = threadIdx.x >> 5, d = blockIdx.x * 32 + c;
    const float* h = reinterpret_cast<const float*>(g_sp + (8u << 20)) + (size_t)blockIdx.y * kL * 512 + d;
    float a = 0.f, q = 0.f;
    for (int l = r; l < kL; l += 8) { const float v = h[(size_t)l * 512]; a += v; q = fmaf(v, v, q); }
    s1[r][c] = a; s2[r][c] = q;
    __syncthreads();
    a = q = 0.f;
    for (int i = 0; i < 8; i++) { a += s1[i][c]; q += s2[i][c]; }
    const float mean = a * (1.0f / kL), sc = __bfloat162float(gamma[d]) / sqrtf(fmaxf(q * (1.0f / kL) - mean * mean, 0.f) + 1e-5f);
    const float sh = __bfloat162float(beta[d]) - mean * sc;
    for (int l = r; l < kL; l += 8)
        out[((size_t)blockIdx.y * kL + l) * 512 + d] = __float2bfloat16(gelu_half(0.5f * fmaf(h[(size_t)l * 512], sc, sh)));
}

typedef CUresult (*EncodeTiledFn)(CUtensorMap*, CUtensorMapDataType, cuuint32_t, void*, const cuuint64_t*, const cuuint64_t*,
                                  const cuuint32_t*, const cuuint32_t*, CUtensorMapInterleave, CUtensorMapSwizzle,
                                  CUtensorMapL2promotion, CUtensorMapFloatOOBfill);

void encode(EncodeTiledFn fn, CUtensorMap* tm, const void* ptr, int rank, const cuuint64_t* dims, const cuuint64_t* strides,
            const cuuint32_t* box, CUtensorMapL2promotion promo, CUtensorMapSwizzle swz = CU_TENSOR_MAP_SWIZZLE_128B) {
    const cuuint32_t es[5] = {1, 1, 1, 1, 1};
    fn(tm, CU_TENSOR_MAP_DATA_TYPE_BFLOAT16, rank, const_cast<void*>(ptr), dims, strides, box, es, CU_TENSOR_MAP_INTERLEAVE_NONE,
       swz, promo, CU_TENSOR_MAP_FLOAT_OOB_FILL_NONE);
}

}

extern "C" void kernel_launch(void* const* d_in, const int* in_sizes, int n_in, void* d_out, int out_size) {
    const __nv_bfloat16* x = (const __nv_bfloat16*)d_in[0];
    const __nv_bfloat16* w = (const __nv_bfloat16*)d_in[1];
    const __nv_bfloat16* gamma = (const __nv_bfloat16*)d_in[2];
    const __nv_bfloat16* beta = (const __nv_bfloat16*)d_in[3];
    static EncodeTiledFn enc = nullptr;
    static int resident = 0;
    if (!enc) {
        void* fn = nullptr;
        cudaDriverEntryPointQueryResult qr;
        cudaGetDriverEntryPoint("cuTensorMapEncodeTiled", &fn, cudaEnableDefault, &qr);
        enc = (EncodeTiledFn)fn;
        cudaFuncSetAttribute(main_kernel, cudaFuncAttributeMaxDynamicSharedMemorySize, MAIN_SMEM);
        cudaFuncSetAttribute(corr_kernel, cudaFuncAttributeMaxDynamicSharedMemorySize, C_SMEM);
        int dev = 0, per_sm = 0;
        cudaGetDevice(&dev);
        cudaDeviceGetAttribute(&resident, cudaDevAttrMultiProcessorCount, dev);
        cudaOccupancyMaxActiveBlocksPerMultiprocessor(&per_sm, main_kernel, 384, MAIN_SMEM);
        resident *= per_sm;
    }
    if (resident < NCTA + 4) {
        plain_conv<<<dim3((kL + 63) / 64, 8, 2), 256>>>(x, w);
        plain_norm<<<dim3(16, 2), 256>>>(gamma, beta, (__nv_bfloat16*)d_out);
        return;
    }
    CUtensorMap tmx, tmw0, tmw1, tmcx, tmcw;
    {
        const cuuint64_t dims[3] = {1024, kRows, 2}, strides[2] = {2048, (cuuint64_t)kRows * 2048};
        const cuuint32_t box[3] = {64, 64, 1};
        encode(enc, &tmx, x, 3, dims, strides, box, CU_TENSOR_MAP_L2_PROMOTION_L2_128B);
    }
    {
        const cuuint64_t dims0[3] = {512, 16, 512}, dims1[3] = {512, 15, 512}, strides[2] = {2 * 512 * 512 * 2, 1024};
        const cuuint32_t box[3] = {64, 16, 2};
        encode(enc, &tmw0, w, 3, dims0, strides, box, CU_TENSOR_MAP_L2_PROMOTION_L2_128B);
        encode(enc, &tmw1, w + 512 * 512, 3, dims1, strides, box, CU_TENSOR_MAP_L2_PROMOTION_L2_128B);
    }
    {
        const cuuint64_t dims[4] = {512, kMO, kNT, 2}, strides[3] = {2048, kMO * 2048, (cuuint64_t)kRows * 2048};
        const cuuint32_t box[4] = {64, 1, kNT, 1};
        encode(enc, &tmcx, x, 4, dims, strides, box, CU_TENSOR_MAP_L2_PROMOTION_L2_128B);
        const cuuint64_t dimw[2] = {512, 512}, stridew[1] = {1024};
        const cuuint32_t boxw[2] = {64, 64};
        encode(enc, &tmcw, w + 30 * 512 * 512, 2, dimw, stridew, boxw, CU_TENSOR_MAP_L2_PROMOTION_L2_128B);
    }
    main_kernel<<<NCTA, 384, MAIN_SMEM>>>(tmx, tmw0, tmw1, x, w, gamma, beta, (__nv_bfloat16*)d_out);
    cudaLaunchConfig_t cfg = {};
    cudaLaunchAttribute at[1];
    cfg.gridDim = 4;
    cfg.blockDim = 256;
    cfg.dynamicSmemBytes = C_SMEM;
    cfg.stream = cudaStreamPerThread;
    at[0].id = cudaLaunchAttributeProgrammaticStreamSerialization;
    at[0].val.programmaticStreamSerializationAllowed = 1;
    cfg.attrs = at;
    cfg.numAttrs = 1;
    cudaLaunchKernelEx(&cfg, corr_kernel, tmcx, tmcw);
}
```

```cpp
#include <cuda_runtime.h>
#include <cuda_bf16.h>
#include <cuda.h>
#include <stdint.h>

namespace {

constexpr int kL    = 7985;
constexpr int kRows = 8000;
constexpr int kMO   = 50;
constexpr int kNT   = 160;

constexpr int V0 = 7;
constexpr int NPRE = 6;
constexpr int RX = 4;
constexpr int FCUT = 96;
constexpr int YSLEEP = 100;
constexpr int PRE1 = 4;
constexpr int TSLEEP = 200;
constexpr int MERGE = 1;
constexpr int RW = 10;

static_assert(V0 >= 7 && V0 <= 9 && RX >= 2 && RX <= 4 && RW >= V0 - 1 && RW <= 12, "rings must fit and be as deep as the look-ahead");
constexpr uint32_t HOME_MASK = 0xB;
constexpr uint32_t R_W = 64 * RX, R_Y = R_W + 22 * RW, NPAGES = 32;
static_assert(R_Y + 427 <= 32 * NPAGES, "scratch size");

__device__ __align__(1024) uint8_t g_sp[(size_t)(NPAGES + 1) * (2u << 20)];
__device__ unsigned g_tsel[32];
__device__ __forceinline__ uint32_t run_sel(uint32_t r, uint32_t group, uint32_t pmask) {
    return ((pmask >> (r >> 5)) ^ __popc(r & HOME_MASK) ^ group) & 1;
}
__device__ __forceinline__ uint32_t run_off(uint32_t r, uint32_t run, uint32_t group, uint32_t pmask) {
    return (r << 16) + 4096 + (run_sel(r, group, pmask) << 13) + (run << 14);
}
__device__ __forceinline__ unsigned* chunk_flag(uint8_t* sp, int done, int part, int chunk) {
    return reinterpret_cast<unsigned*>(sp + (4 + 3 * (chunk >> 5)) * 65536 + (done ? (part ? 15 : 13) : (part ? 0 : 14)) * 4096 + (chunk & 31) * 128);
}
__device__ __forceinline__ unsigned long long* part_sums(uint8_t* sp, int b, int db) {
    return reinterpret_cast<unsigned long long*>(sp + (8 + 2 * db + ((__popc((8 + 2 * db) & HOME_MASK) ^ b) & 1)) * 65536 + 13 * 4096);
}
__device__ __forceinline__ unsigned* y_flag(uint8_t* sp, int b, int db) { return reinterpret_cast<unsigned*>(part_sums(sp, b, db) + 512); }
__device__ __align__(256) float g_corr[16 * kNT * 64];
__device__ unsigned g_cready[4 * 32];
__device__ float g_direct[512 * 250 * 64];
__device__ unsigned long long g_dpart[2 * 512 * 64];
__device__ unsigned g_exit, g_epoch;

__device__ __forceinline__ uint32_t smem_u32(const void* p) { return (uint32_t)__cvta_generic_to_shared(p); }

__device__ __forceinline__ void mbar_init(uint32_t bar, uint32_t count) {
    asm volatile("mbarrier.init.shared::cta.b64 [%0], %1;" ::"r"(bar), "r"(count) : "memory");
}
__device__ __forceinline__ void mbar_expect_tx(uint32_t bar, uint32_t bytes) {
    asm volatile("mbarrier.arrive.expect_tx.shared::cta.b64 _, [%0], %1;" ::"r"(bar), "r"(bytes) : "memory");
}
__device__ __forceinline__ void mbar_arrive(uint32_t bar) {
    asm volatile("mbarrier.arrive.shared::cta.b64 _, [%0];" ::"r"(bar) : "memory");
}
__device__ __forceinline__ bool mbar_try(uint32_t bar, uint32_t parity) {
    uint32_t ok;
    asm volatile(
        "{\n.reg .pred p;\n"
        "mbarrier.try_wait.parity.shared::cta.b64 p, [%1], %2;\n"
        "selp.u32 %0, 1, 0, p;\n}\n"
        : "=r"(ok) : "r"(bar), "r"(parity) : "memory");
    return ok;
}
__device__ __forceinline__ bool mbar_test(uint32_t bar, uint32_t parity) {
    uint32_t ok;
    asm volatile(
        "{\n.reg .pred p;\n"
        "mbarrier.test_wait.parity.shared::cta.b64 p, [%1], %2;\n"
        "selp.u32 %0, 1, 0, p;\n}\n"
        : "=r"(ok) : "r"(bar), "r"(parity) : "memory");
    return ok;
}
__device__ __forceinline__ void mbar_wait(uint32_t bar, uint32_t parity) {
#pragma unroll 1
    for (uint32_t n = 0; n < (1u << 14); n++)
        if (mbar_try(bar, parity)) break;
}
__device__ __forceinline__ void fence_proxy_async_smem() { asm volatile("fence.proxy.async.shared::cta;" ::: "memory"); }
__device__ __forceinline__ void fence_mbar_init() { asm volatile("fence.mbarrier_init.release.cluster;" ::: "memory"); }

__device__ __forceinline__ void bulk_g2s(uint32_t dst, const void* src, uint32_t bytes, uint32_t bar) {
    asm volatile("cp.async.bulk.shared::cluster.global.mbarrier::complete_tx::bytes [%0], [%1], %2, [%3];"
                 ::"r"(dst), "l"(src), "r"(bytes), "r"(bar) : "memory");
}
__device__ __forceinline__ void bulk_g2s_ef(uint32_t dst, const void* src, uint32_t bytes, uint32_t bar) {
    asm volatile("{\n.reg .b64 pol;\ncreatepolicy.fractional.L2::evict_first.b64 pol, 1.0;\n"
                 "cp.async.bulk.shared::cluster.global.mbarrier::complete_tx::bytes.L2::cache_hint [%0], [%1], %2, [%3], pol;\n}"
                 ::"r"(dst), "l"(src), "r"(bytes), "r"(bar) : "memory");
}
__device__ __forceinline__ void tma3d_ef(uint32_t dst, const CUtensorMap* tm, int c0, int c1, int c2, uint32_t bar) {
    asm volatile("{\n.reg .b64 pol;\ncreatepolicy.fractional.L2::evict_first.b64 pol, 1.0;\n"
                 "cp.async.bulk.tensor.3d.shared::cluster.global.mbarrier::complete_tx::bytes.L2::cache_hint [%0], [%1, {%3, %4, %5}], [%2], pol;\n}"
                 ::"r"(dst), "l"(tm), "r"(bar), "r"(c0), "r"(c1), "r"(c2) : "memory");
}
__device__ __forceinline__ void tma3d(uint32_t dst, const CUtensorMap* tm, int c0, int c1, int c2, uint32_t bar) {
    asm volatile("cp.async.bulk.tensor.3d.shared::cluster.global.mbarrier::complete_tx::bytes [%0], [%1, {%3, %4, %5}], [%2];"
                 ::"r"(dst), "l"(tm), "r"(bar), "r"(c0), "r"(c1), "r"(c2) : "memory");
}
__device__ __forceinline__ void poll_ge(const unsigned* p, unsigned target) {
#pragma unroll 1
    for (uint32_t n = 0; n < (1u << 15); n++) {
        unsigned v;
        asm volatile("ld.acquire.gpu.global.u32 %0, [%1];" : "=r"(v) : "l"(p) : "memory");
        if (v >= target) break;
        __nanosleep(32);
    }
}
__device__ __forceinline__ void red_relaxed(unsigned* p) { asm volatile("red.relaxed.gpu.global.add.u32 [%0], 1;" ::"l"(p) : "memory"); }
__device__ __forceinline__ void named_arrive(int id, int n) { asm volatile("bar.arrive %0, %1;" ::"r"(id), "r"(n) : "memory"); }
__device__ __forceinline__ void named_bar(int id, int n) { asm volatile("bar.sync %0, %1;" ::"r"(id), "r"(n) : "memory"); }

__device__ __forceinline__ void wg_fence() { asm volatile("wgmma.fence.sync.aligned;" ::: "memory"); }
__device__ __forceinline__ void wg_commit() { asm volatile("wgmma.commit_group.sync.aligned;" ::: "memory"); }
template <int N> __device__ __forceinline__ void wg_wait() { asm volatile("wgmma.wait_group.sync.aligned %0;" ::"n"(N) : "memory"); }
template <int N> __device__ __forceinline__ void reg_fence(float (&d)[N]) {
#pragma unroll
    for (int i = 0; i < N; i++) asm volatile("" : "+f"(d[i])::"memory");
}

#define F4(a, i) "+f"(a[i]), "+f"(a[i + 1]), "+f"(a[i + 2]), "+f"(a[i + 3])
#define F8(a, i) F4(a, i), F4(a, i + 4)
#define F16(a, i) F8(a, i), F8(a, i + 8)

constexpr uint32_t HI128 = 0x40000040u, HI64 = 0x80000020u;
__device__ __forceinline__ uint32_t desc_lo(uint32_t addr) { return (addr >> 4) | 0x10000u; }


#define R4(a, i) "+r"(a[i]), "+r"(a[i + 1]), "+r"(a[i + 2]), "+r"(a[i + 3])
#define R8(a, i) R4(a, i), R4(a, i + 4)
template <int N> __device__ __forceinline__ void reg_fence(uint32_t (&d)[N]) {
#pragma unroll
    for (int i = 0; i < N; i++) asm volatile("" : "+r"(d[i])::"memory");
}
__device__ __forceinline__ void tma2d(uint32_t dst, const CUtensorMap* tm, int c0, int c1, uint32_t bar) {
    asm volatile("cp.async.bulk.tensor.2d.shared::cluster.global.mbarrier::complete_tx::bytes [%0], [%1, {%3, %4}], [%2];"
                 ::"r"(dst), "l"(tm), "r"(bar), "r"(c0), "r"(c1) : "memory");
}
__device__ __forceinline__ void tma4d(uint32_t dst, const CUtensorMap* tm, int c0, int c1, int c2, int c3, uint32_t bar) {
    asm volatile("cp.async.bulk.tensor.4d.shared::cluster.global.mbarrier::complete_tx::bytes [%0], [%1, {%3, %4, %5, %6}], [%2];"
                 ::"r"(dst), "l"(tm), "r"(bar), "r"(c0), "r"(c1), "r"(c2), "r"(c3) : "memory");
}
__device__ __forceinline__ bool named_bar_or(int id, int n, bool v) {
    uint32_t r;
    asm volatile("{\n.reg .pred p, q;\nsetp.ne.u32 q, %3, 0;\nbar.red.or.pred p, %1, %2, q;\nselp.u32 %0, 1, 0, p;\n}"
                 : "=r"(r) : "r"(id), "r"(n), "r"((uint32_t)v) : "memory");
    return r;
}

template <uint32_t AHI, int ACC>
__device__ __forceinline__ void wgmma_n64_ss(float (&d)[32], uint32_t da, uint32_t db) {
    asm volatile(
        "{\n.reg .pred p;\n.reg .b64 da, db;\nsetp.ne.b32 p, %36, 0;\nmov.b64 da, {%32, %34};\nmov.b64 db, {%33, %35};\n"
        "wgmma.mma_async.sync.aligned.m64n64k16.f32.bf16.bf16 "
        "{%0,%1,%2,%3,%4,%5,%6,%7,%8,%9,%10,%11,%12,%13,%14,%15,%16,%17,%18,%19,%20,%21,%22,%23,%24,%25,%26,%27,%28,%29,%30,%31},"
        "da, db, p, 1, 1, 0, 1;\n}\n"
        : F16(d, 0), F16(d, 16)
        : "r"(da), "r"(db), "n"(AHI), "n"(HI128), "n"(ACC));
}


template <int ACC>
__device__ __forceinline__ void wgmma_n56_ss(float (&d)[28], uint32_t da, uint32_t db) {
    asm volatile(
        "{\n.reg .pred p;\n.reg .b64 da, db;\nsetp.ne.b32 p, %31, 0;\nmov.b64 da, {%28, %30};\nmov.b64 db, {%29, %30};\n"
        "wgmma.mma_async.sync.aligned.m64n56k16.f32.f16.f16 "
        "{%0,%1,%2,%3,%4,%5,%6,%7,%8,%9,%10,%11,%12,%13,%14,%15,%16,%17,%18,%19,%20,%21,%22,%23,%24,%25,%26,%27},"
        "da, db, p, 1, 1, 1, 0;\n}\n"
        : F16(d, 0), F8(d, 16), F4(d, 24)
        : "r"(da), "r"(db), "n"(HI128), "n"(ACC));
}

template <int SA>
__device__ __forceinline__ void wgmma_n160_h(uint32_t (&d)[40], uint32_t da, uint32_t db) {
    asm volatile(
        "{\n.reg .pred p;\n.reg .b64 da, db;\nsetp.eq.b32 p, 0, 0;\nmov.b64 da, {%40, %43};\nmov.b64 db, {%41, %43};\n"
        "wgmma.mma_async.sync.aligned.m64n160k16.f16.f16.f16 "
        "{%0,%1,%2,%3,%4,%5,%6,%7,%8,%9,%10,%11,%12,%13,%14,%15,%16,%17,%18,%19,%20,%21,%22,%23,%24,%25,%26,%27,"
        "%28,%29,%30,%31,%32,%33,%34,%35,%36,%37,%38,%39},"
        "da, db, p, %42, 1, 1, 0;\n}\n"
        : R8(d, 0), R8(d, 8), R8(d, 16), R8(d, 24), R8(d, 32)
        : "r"(da), "r"(db), "n"(SA), "n"(HI128));
}
template <int SA>
__device__ __forceinline__ void wgmma_n160_f(float (&d)[80], uint32_t da, uint32_t db) {
    asm volatile(
        "{\n.reg .pred p;\n.reg .b64 da, db;\nsetp.eq.b32 p, 0, 0;\nmov.b64 da, {%80, %83};\nmov.b64 db, {%81, %83};\n"
        "wgmma.mma_async.sync.aligned.m64n160k16.f32.bf16.bf16 "
        "{%0,%1,%2,%3,%4,%5,%6,%7,%8,%9,%10,%11,%12,%13,%14,%15,%16,%17,%18,%19,%20,%21,%22,%23,%24,%25,%26,%27,"
        "%28,%29,%30,%31,%32,%33,%34,%35,%36,%37,%38,%39,%40,%41,%42,%43,%44,%45,%46,%47,%48,%49,%50,%51,%52,%53,%54,%55,"
        "%56,%57,%58,%59,%60,%61,%62,%63,%64,%65,%66,%67,%68,%69,%70,%71,%72,%73,%74,%75,%76,%77,%78,%79},"
        "da, db, p, %82, 1, 1, 0;\n}\n"
        : F16(d, 0), F16(d, 16), F16(d, 32), F16(d, 48), F16(d, 64)
        : "r"(da), "r"(db), "n"(SA), "n"(HI128));
}

__device__ __forceinline__ uint32_t pack_f16(float lo, float hi) {
    uint32_t r;
    asm("cvt.rn.f16x2.f32 %0, %1, %2;" : "=r"(r) : "f"(hi), "f"(lo));
    return r;
}
__device__ __forceinline__ uint32_t mul_bf16x2(uint32_t a, uint32_t b) {
    uint32_t r;
    asm("mul.rn.bf16x2 %0, %1, %2;" : "=r"(r) : "r"(a), "r"(b));
    return r;
}
__device__ __forceinline__ void sts128(uint32_t p, uint32_t a, uint32_t b, uint32_t c, uint32_t d) {
    asm volatile("st.shared.v4.b32 [%0], {%1,%2,%3,%4};" ::"r"(p), "r"(a), "r"(b), "r"(c), "r"(d) : "memory");
}
__device__ __forceinline__ uint32_t pack_bf16(float lo, float hi) {
    uint32_t r;
    asm("cvt.rn.bf16x2.f32 %0, %1, %2;" : "=r"(r) : "f"(hi), "f"(lo));
    return r;
}
__device__ __forceinline__ void stg128(void* p, uint32_t a, uint32_t b, uint32_t c, uint32_t d) {
    asm volatile("st.global.v4.b32 [%0], {%1,%2,%3,%4};" ::"l"(p), "r"(a), "r"(b), "r"(c), "r"(d) : "memory");
}
__device__ __forceinline__ void stmatrix_x4_t(uint32_t addr, uint32_t a, uint32_t b, uint32_t c, uint32_t d) {
    asm volatile("stmatrix.sync.aligned.m8n8.x4.trans.shared.b16 [%0], {%1,%2,%3,%4};"
                 ::"r"(addr), "r"(a), "r"(b), "r"(c), "r"(d) : "memory");
}

constexpr uint32_t cos64(int k, bool half) {
    constexpr uint16_t q[17] = {0x3F80, 0x3F7F, 0x3F7B, 0x3F75, 0x3F6D, 0x3F62, 0x3F55, 0x3F46, 0x3F35, 0x3F22, 0x3F0E, 0x3EF1, 0x3EC4, 0x3E95, 0x3E48, 0x3DC9, 0x0000};
    constexpr uint16_t h[17] = {0x3C00, 0x3BF6, 0x3BD9, 0x3BA8, 0x3B64, 0x3B0E, 0x3AA7, 0x3A2F, 0x39A8, 0x3913, 0x3872, 0x378B, 0x361F, 0x34A5, 0x323E, 0x2E46, 0x0000};
    k &= 63;
    if (k > 32) k = 64 - k;
    const uint16_t* t = half ? h : q;
    return k <= 16 ? t[k] : (t[32 - k] | 0x8000u);
}
constexpr uint32_t fwd_coef(int s, int p, int t) { return (p && s == 0) ? cos64(32 * t, false) : cos64(s * t - 16 * p, false); }
constexpr uint32_t inv_coef(int l, int phi) {
    const int s = phi >> 1, p = phi & 1;
    if (l >= kMO) return 0;
    const uint32_t c = s == 0 ? cos64(32 * l * p, true) : cos64(s * l + 16 * p, true);
    return (c & 0x7FFF) ? c - ((s == 0 ? 6 : 5) << 10) : 0;
}
struct Tables {
    uint32_t fwd[2048];
    uint32_t inv[2048];
};
constexpr Tables make_tables() {
    Tables t = {};
    for (int i = 0; i < 2048; i++) {
        const int row = i >> 5, tt = 8 * (((i >> 2) & 7) ^ (row & 7)) + 2 * (i & 3), s = 8 * (row >> 4) + (row & 7), p = (row >> 3) & 1;
        t.fwd[i] = fwd_coef(s, p, tt) | (fwd_coef(s, p, tt + 1) << 16);
        t.inv[i] = inv_coef(row, tt) | (inv_coef(row, tt + 1) << 16);
    }
    return t;
}
__device__ __align__(128) const Tables g_tab = make_tables();

constexpr int NCTA = 128;
constexpr int NST = 4;
constexpr int HEND = 56;
constexpr int XB = kNT * 128;
constexpr int OFF_W1 = 0, OFF_X = OFF_W1 + NST * 8192, OFF_W0 = OFF_X + 4 * XB, OFF_RAW = OFF_W0 + NST * 8192;
constexpr int OFF_STG = OFF_RAW + 32768;
constexpr int OFF_U0 = OFF_W0, OFF_U1 = OFF_X, OFF_C1 = OFF_W1, OFF_DIR = OFF_W1 + 8192;
constexpr int OFF_F = OFF_RAW + 65536;
constexpr int OFF_G = OFF_F + 8192;
constexpr int OFF_C0 = OFF_G;
constexpr int OFF_BAR = OFF_G + 4096;
constexpr int B_FULL = 0, B_EMPTY = 8 * NST, B_TSEL = 16 * NST, B_PRE = B_TSEL + 8, B_SIG = B_PRE + 16 * V0, B_YS = B_SIG + 8 * 33,
              B_T2 = B_YS + 8 * 4, B_SUM = B_T2 + 8, B_GATE = B_SUM + 32, B_RDY = B_GATE + 8 * 32, B_PUB = B_RDY + 8 * 33, B_UNIT = B_PUB + 8,
              B_FTAB = B_UNIT + 8 * 20, B_C1 = B_FTAB + 8, B_NRM = B_C1 + 8, B_END = B_NRM + 32;
template <int O0, int O1>
__device__ __forceinline__ void bar_setup(uint32_t bars) {
#pragma unroll
    for (int o = O0; o < O1; o += 8)
        mbar_init(bars + o, o < B_EMPTY ? 2 : o < B_TSEL ? 8 : o == B_TSEL ? 2 : o < B_SIG ? 1 : o < B_YS - 8 ? 8 : o < B_GATE ? 4 : 1);
    fence_mbar_init();
    fence_proxy_async_smem();
}
constexpr int OFF_TS = OFF_BAR + B_END;
constexpr int OFF_PLAN = OFF_TS + 336;
constexpr int OFF_YT = OFF_PLAN + (V0 + 65) * 8;
constexpr int OFF_GB = (OFF_YT + 4 * kNT * 4 + 15) & ~15;
constexpr int MAIN_SMEM = OFF_GB + 2048;
static_assert(MAIN_SMEM <= 232448 && OFF_U0 + 10 * 8192 == OFF_STG + 16384, "shared memory");
constexpr int XPC = 2 * kNT;
constexpr unsigned PROBE_NEAR = 400;

__device__ __forceinline__ uint32_t raw_slot(uint32_t sbase, uint32_t v, int wg) { return sbase + OFF_RAW + ((v & 3) * 2 + wg) * 8192; }

__device__ __forceinline__ uint32_t pre_slot(uint32_t sbase, uint32_t v, int wg) {
    return v < 4 ? raw_slot(sbase, v, wg) : v < 8 ? sbase + OFF_X + (v - 4) * XB + wg * 8192 : sbase + (wg ? OFF_W1 : OFF_W0) + ((V0 + 3) % NST) * 8192;
}
constexpr int OFF_TMP = OFF_W1 + 8192;

template <bool DC, int I>
__device__ __forceinline__ void gemm_mma(uint32_t (&a0)[40], uint32_t (&a1)[40], uint32_t dx0, uint32_t dx1, uint32_t dw) {
    constexpr int ks = I >> 2;
    const uint32_t A0 = dw + ks * 128, A1 = A0 + 256, B0 = dx0 + ks * 2, B1 = dx1 + ks * 2;
    if ((I & 3) == 0) wgmma_n160_h<1>(a0, A0, B0);
    if ((I & 3) == 1) wgmma_n160_h<1>(a1, A1, DC ? B1 : B0);
    if ((I & 3) == 2 && !DC) wgmma_n160_h<1>(a0, A1, B1);
    if ((I & 3) == 3 && !DC) wgmma_n160_h<-1>(a1, A0, B1);
}

template <bool DC, int I0, int I1>
__device__ __forceinline__ void gemm_mmas(uint32_t (&a0)[40], uint32_t (&a1)[40], uint32_t dx0, uint32_t dx1, uint32_t dw) {
    if constexpr (I0 < I1) {
        gemm_mma<DC, I0>(a0, a1, dx0, dx1, dw);
        gemm_mmas<DC, I0 + 1, I1>(a0, a1, dx0, dx1, dw);
    }
}
__device__ __forceinline__ uint32_t y_unit(uint32_t db, uint32_t tau, uint32_t b, uint32_t pmask) {
    const uint32_t n = db * kNT + tau;
    return run_off(R_Y + n / 3, n % 3, b, pmask);
}
template <int R>
__device__ __forceinline__ void store_round(const uint32_t (&a0)[40], const uint32_t (&a1)[40], uint32_t stg, int t, int wg, uint8_t* sp,
                                            int slot, uint32_t ytab, int wsw) {
    const int w = t >> 5, lane = t & 31, m = lane >> 3, i8 = lane & 7;
    constexpr int N = R == 2 ? 4 : 8;
    named_bar(2 + wg, 128);
    const uint32_t addr = stg + i8 * 256 + (m >> 1) * 128 + (((2 * w + (m & 1)) ^ i8 ^ wsw) << 4);
#pragma unroll
    for (int j = 8 * R; j < 8 * R + N; j++) stmatrix_x4_t(addr + (j - 8 * R) * 2048, a0[2 * j], a0[2 * j + 1], a1[2 * j], a1[2 * j + 1]);
    named_bar(2 + wg, 128);
    const int row = 2 * w + (lane >> 4), phi = 2 * slot + (m & 1);
    const uint32_t src = stg + row * 256 + (m & 1) * 128 + ((i8 ^ row) << 4);
    uint8_t* dst = sp + phi * 128 + ((i8 ^ (phi & 7)) << 4);
    uint32_t v[N][4], o[N];
#pragma unroll
    for (int i = 0; i < N; i++) {
        asm volatile("ld.shared.u32 %0, [%1];" : "=r"(o[i]) : "r"(ytab + (64 * R + 8 * i + row) * 4) : "memory");
        asm volatile("ld.shared.v4.b32 {%0,%1,%2,%3}, [%4];" : "=r"(v[i][0]), "=r"(v[i][1]), "=r"(v[i][2]), "=r"(v[i][3])
                     : "r"(src + i * 2048) : "memory");
    }
#pragma unroll
    for (int i = 0; i < N; i++) stg128(dst + o[i], v[i][0], v[i][1], v[i][2], v[i][3]);
}

__device__ __forceinline__ int step_k(int h) { return h < HEND ? h >> 1 : 28 + (h & 3); }
__device__ __forceinline__ int step_m(int h) { return h < HEND ? h & 1 : (h >> 2) & 1; }
constexpr uint64_t x_mask() {
    uint64_t r = 2 | (3ull << 58);
    for (int v = 2; v < 58; v++)
        if ((0x6B >> (v & 7)) & 1) r |= 1ull << v;
    return r;
}
constexpr uint64_t XMASK = x_mask();
__device__ __forceinline__ int x_round(int v, int wg) {
    return v == 0 ? wg : (v < 60 && wg != (v & 1) && ((XMASK >> v) & 1)) ? 1 + __popcll(XMASK << (63 - v)) : -1;
}
__device__ __forceinline__ int w_step(int v, int wg) {
    return v == 0 ? -1 : v < 60 ? (wg == (v & 1) ? v - 1 : -1) : v < 62 ? 2 * v - 61 + wg : (v == 62 && wg == 0) ? 63 : -1;
}
constexpr int GMAX = (64 - RW) / 2 > 31 - 2 * RX ? (64 - RW) / 2 : 31 - 2 * RX;

__device__ __forceinline__ uint32_t plan_word(int v, int wg, int cta) {
    const int r = x_round(v, wg), h = w_step(v, wg);
    if (r < 0 && h < 0) return 0;
    const bool last = v >= 60 || (v & 1) || (v > 0 && wg == 0 && x_round(v + 1, 0) < 0);
    uint32_t off, row, gate;
    if (r >= 0) {
        const int u = r * NCTA + cta, cb = u / XPC, i = u - cb * XPC, b = i >= kNT, tau = i - b * kNT;
        row = tau & 63;
        off = (((cb % RX) * 64 + b) << 16) + ((tau >> 6) << 14) + b + 2;
        gate = cb >= RX ? 2 * (cb - RX) + 2 : 0;
    } else {
        const int ring = (h + RW - 64 % RW) % RW;
        row = 0;
        off = ((ring * 22) << 16) + (ring << 12) + 4;
        gate = h >= RW ? ((h - RW + 1) >> 1) + 1 : 0;
    }
    return (off + row * 128) | ((row & 7) << 4) | (last << 3) | ((v > 60) << 24) | (gate << 26);
}

struct Xf {
    uint32_t sbase;
    uint8_t *px, *pw;
    uint32_t cx, cw;
    uint32_t xsw;
    uint32_t dw;
    uint32_t e;
    int lane;
};
__device__ __forceinline__ uint32_t plan_load(const Xf& f, uint32_t v, int wg) {
    uint32_t e;
    asm volatile("ld.shared.u32 %0, [%1];" : "=r"(e) : "r"(f.sbase + OFF_PLAN + v * 8 + wg * 4));
    return __shfl_sync(0xffffffffu, e, 0);
}
template <bool W>
__device__ __forceinline__ void unit_mma(float (&acc)[32], const Xf& f, uint32_t raw) {
    const uint32_t dB = desc_lo(raw);
    if (W) {
        const uint32_t dG = desc_lo(f.sbase + OFF_G);
        wgmma_n64_ss<HI64, 0>(acc, dG, dB);
        wgmma_n64_ss<HI64, 1>(acc, dG + 2, dB + 128);
    } else {
        const uint32_t dF = desc_lo(f.sbase + OFF_F);
        wgmma_n64_ss<HI128, 0>(acc, dF, dB);
        wgmma_n64_ss<HI128, 1>(acc, dF + 2, dB + 128);
        wgmma_n64_ss<HI128, 1>(acc, dF + 4, dB + 256);
        wgmma_n64_ss<HI128, 1>(acc, dF + 6, dB + 384);
    }
    wg_commit();
}
constexpr int DROP = 3;
__device__ __forceinline__ uint32_t pack_sp(float lo, float hi) {
    const uint32_t r = pack_f16(lo, hi);
    return DROP ? (r + (0x10001u << DROP >> 1)) & ~(((1u << DROP) - 1) * 0x10001u) : r;
}
__device__ __forceinline__ void st_quad(uint8_t* p, const float (&acc)[32], int j0) {
    stg128(p, pack_sp(acc[j0], acc[j0 + 1]), pack_sp(acc[j0 + 4], acc[j0 + 5]), pack_sp(acc[j0 + 8], acc[j0 + 9]),
           pack_sp(acc[j0 + 12], acc[j0 + 13]));
}
template <bool W>
__device__ __forceinline__ void unit_store(float (&acc)[32], const Xf& f, uint32_t e) {
    const uint32_t sel = ((W ? f.cw >> (8 + ((e >> 12) & 15)) : e ^ (f.cx >> (8 + ((e >> 21) & 6)))) & 1) << 13;
    const uint32_t o = (e & (W ? 0xFF0F80u : 0xFFFF80u)) + ((e ^ (W ? f.cw : f.cx)) & 0x70);
    uint8_t* const b = W ? f.pw : f.px;
    uint8_t *p0 = b + (o + sel), *p1 = b + ((o ^ 64) + sel);
    reg_fence(acc);
    if (W) {
        st_quad(p0, acc, 0);
        st_quad(p1, acc, 16);
        st_quad(p0 + 4096, acc, 2);
        st_quad(p1 + 4096, acc, 18);
    } else {
        const int d = 131072 + 8192 - 2 * (int)sel;
        st_quad(p0, acc, 0);
        st_quad(p1, acc, 2);
        st_quad(p0 + d, acc, 16);
        st_quad(p1 + d, acc, 18);
    }
}
__device__ __forceinline__ void unit_done(const Xf& f, uint32_t e, uint32_t v) {
    if (e & 8) {
        __syncwarp();
        if (f.lane == 0) mbar_arrive(f.sbase + OFF_BAR + B_SIG + 8 * ((v >> 1) + ((e >> 24) & 1)));
    }
}
__device__ __forceinline__ void step_wait(Xf& f, uint32_t v, int wg) {
    const uint32_t bars = f.sbase + OFF_BAR;
    if (f.e >> 26) mbar_wait(bars + B_GATE - 8 + 8 * (f.e >> 26), 0);
    mbar_wait(bars + B_FULL + 8 * (v % NST), (v / NST) & 1);
}

template <bool DC, int KIND>
__device__ __forceinline__ void gemm_step(uint32_t (&a0)[40], uint32_t (&a1)[40], float (&at)[32], Xf& f, uint32_t v, uint32_t xs, int wg, bool first) {
    const uint32_t bars = f.sbase + OFF_BAR, sb = desc_lo(f.sbase), xb = sb + OFF_X / 16 + xs * (XB / 16), raw = raw_slot(f.sbase, v, wg);
    const uint32_t dx0 = xb + f.xsw, dx1 = xb + (f.xsw ^ 4), dw = f.dw + (v % NST) * 512, e = f.e;
    wg_fence();
    if (KIND) unit_mma<KIND != 1>(at, f, raw);
    constexpr int N1 = KIND == 0 ? 2 : NPRE;
    gemm_mmas<DC, 0, N1>(a0, a1, dx0, dx1, dw);
    wg_commit();
    f.e = plan_load(f, v + 1, wg);
    wg_wait<1>();
    if (!KIND && !first && f.lane == 0) mbar_arrive(bars + B_EMPTY + 8 * ((v - 1) % NST));
    if (KIND) unit_store<KIND != 1>(at, f, e);
    if (KIND) unit_done(f, e, v);
    gemm_mmas<DC, N1, 7>(a0, a1, dx0, dx1, dw);
    if (KIND && !first && f.lane == 0) mbar_arrive(bars + B_EMPTY + 8 * ((v - 1) % NST));
    gemm_mma<DC, 7>(a0, a1, dx0, dx1, dw);
    wg_commit();
}
template <bool DC>
__device__ __forceinline__ void any_step(uint32_t (&a0)[40], uint32_t (&a1)[40], float (&at)[32], Xf& f, uint32_t v, uint32_t xs, int wg, bool first) {
    step_wait(f, v, wg);
    const uint32_t kind = (f.e >> 1) & 3;
    if (kind == 1) gemm_step<DC, 1>(a0, a1, at, f, v, xs, wg, first);
    else if (kind == 2) gemm_step<DC, 2>(a0, a1, at, f, v, xs, wg, first);
    else gemm_step<DC, 0>(a0, a1, at, f, v, xs, wg, first);
}
template <bool DC>
__device__ __forceinline__ void gemm_main(uint32_t (&a0)[40], uint32_t (&a1)[40], uint32_t (&b0)[40], uint32_t (&b1)[40], Xf& f, int wg) {
    float at[32];
#pragma unroll 1
    for (uint32_t k = 0; k < HEND / 2; k++) {
        any_step<DC>(a0, a1, at, f, V0 + 2 * k, k & 3, wg, k == 0);
        any_step<DC>(b0, b1, at, f, V0 + 2 * k + 1, k & 3, wg, false);
    }
    wg_wait<0>();
    if (f.lane == 0) mbar_arrive(f.sbase + OFF_BAR + B_EMPTY + 8 * ((V0 + HEND - 1) % NST));
}
template <bool DC>
__device__ __forceinline__ void gemm_last(uint32_t (&a0)[40], uint32_t (&a1)[40], Xf& f, int wg, int m) {
    const uint32_t bars = f.sbase + OFF_BAR, sb = desc_lo(f.sbase);
    mbar_wait(bars + B_FULL + 8 * ((V0 + HEND) % NST), ((V0 + HEND) / NST + m) & 1);
    if (2 * m + wg > 0) named_bar(3 + 2 * m + wg, 256);
#pragma unroll 1
    for (uint32_t k = 0; k < 4; k++) {
        const uint32_t v = V0 + HEND + 4 * m + k, xb = sb + OFF_X / 16 + k * (XB / 16);
        wg_fence();
        gemm_mmas<DC, 0, 8>(a0, a1, xb + f.xsw, xb + (f.xsw ^ 4), f.dw + (v % NST) * 512);
        wg_commit();
        if (k == 3) break;
        mbar_wait(bars + B_FULL + 8 * ((v + 1) % NST), ((v + 1) / NST) & 1);
        wg_wait<1>();
        if (k && f.lane == 0) mbar_arrive(bars + B_EMPTY + 8 * ((v - 1) % NST));
    }
    if (2 * m + wg < 3) named_arrive(4 + 2 * m + wg, 256);
    wg_wait<1>();
    if (f.lane == 0) mbar_arrive(bars + B_EMPTY + 8 * ((V0 + HEND + 2) % NST));
    wg_wait<0>();
    if (f.lane == 0) {
        mbar_arrive(bars + B_EMPTY + 8 * ((V0 + HEND + 3) % NST));
        if (2 * m + wg == 2) mbar_arrive(bars + B_T2);
    }
}

__device__ __forceinline__ float gelu_half(float hv) {
    float th;
    asm("tanh.approx.f32 %0, %1;" : "=f"(th) : "f"(hv * fmaf(hv * hv, 8.0f * 0.7978845608028654f * 0.044715f, 2.0f * 0.7978845608028654f)));
    return fmaf(hv, th, hv);
}
__device__ __noinline__ void direct_block(const __nv_bfloat16* __restrict__ x, const __nv_bfloat16* __restrict__ w,
                                          const __nv_bfloat16* __restrict__ gamma, const __nv_bfloat16* __restrict__ beta,
                                          __nv_bfloat16* __restrict__ out, float* sm, int b, int db, int part, uint32_t epoch) {
    float *xs = sm, *ws = sm + 32 * 17, *red = ws + 16 * 65;
    const int tid = threadIdx.x & 127, bar = 2 + (threadIdx.x >> 7), tx = tid & 15, ty = tid >> 4, row0 = part * 250, lim = min(250, kL - row0);
    float* h = g_direct + (size_t)((b * 8 + db) * 32 + part) * (250 * 64);
    for (int l0 = 0; l0 < lim; l0 += 32) {
        float acc[4][4] = {};
        for (int k0 = 0; k0 < 31 * 512; k0 += 16) {
            named_bar(bar, 128);
            for (int i = tid; i < 1024; i += 128) {
                if (i < 512) xs[(i >> 4) * 17 + (i & 15)] = __bfloat162float(x[((size_t)b * kRows + row0 + min(l0 + (i >> 4), lim - 1)) * 1024 + k0 + (i & 15)]);
                ws[(i >> 6) * 65 + (i & 63)] = __bfloat162float(w[(size_t)(k0 + (i >> 6)) * 512 + 64 * db + (i & 63)]);
            }
            named_bar(bar, 128);
            for (int k = 0; k < 16; k++)
#pragma unroll
                for (int i = 0; i < 4; i++)
#pragma unroll
                    for (int j = 0; j < 4; j++) acc[i][j] = fmaf(xs[(ty * 4 + i) * 17 + k], ws[k * 65 + tx * 4 + j], acc[i][j]);
        }
#pragma unroll
        for (int i = 0; i < 4; i++)
#pragma unroll
            for (int j = 0; j < 4; j++)
                if (l0 + ty * 4 + i < lim) h[(l0 + ty * 4 + i) * 64 + tx * 4 + j] = acc[i][j];
    }
    const int c = tid & 63;
    float mean = 0.f, var = 0.f;
    for (int r = 0; r < 2; r++) {
        named_bar(bar, 128);
        float s = 0.f;
        for (int l = tid >> 6; l < lim; l += 2) {
            const float v = h[l * 64 + c] - mean;
            s += r ? v * v : v;
        }
        red[tid] = s;
        named_bar(bar, 128);
        unsigned long long* p = g_dpart + ((r * 16 + b * 8 + db) * 32) * 64 + c;
        if (tid < 64)
            asm volatile("st.relaxed.gpu.global.v2.b32 [%0], {%1, %2};" ::"l"(p + part * 64), "r"(__float_as_uint(red[c] + red[64 + c])), "r"(epoch) : "memory");
        s = 0.f;
        for (int k = 0; k < 32; k++) {
            unsigned long long v = 0;
#pragma unroll 1
            for (uint32_t n = 0; n < (1u << 19); n++) {
                asm volatile("ld.relaxed.gpu.global.u64 %0, [%1];" : "=l"(v) : "l"(p + k * 64) : "memory");
                if ((uint32_t)(v >> 32) == epoch) break;
                __nanosleep(200);
            }
            s += __uint_as_float((uint32_t)v);
        }
        (r ? var : mean) = s * (1.0f / kL);
    }
    const float a = __bfloat162float(gamma[64 * db + c]) / sqrtf(var + 1e-5f), be = __bfloat162float(beta[64 * db + c]);
    for (int l = tid >> 6; l < lim; l += 2)
        out[((size_t)b * kL + row0 + l) * 512 + 64 * db + c] = __float2bfloat16(gelu_half(0.5f * fmaf(h[l * 64 + c] - mean, a, be)));
    named_bar(bar, 128);
}

__device__ __forceinline__ int tail_block(uint32_t gr, int t) { return 4 * (t >> 1) + ((gr >> 4) & 2) + (t & 1); }
__device__ __forceinline__ void tail_poll(uint8_t* sp, uint32_t gr, int t) {
#pragma unroll 1
    for (uint32_t n = 0; n < (1u << 15); n++) {
        unsigned v;
        asm volatile("ld.relaxed.gpu.global.u32 %0, [%1];" : "=r"(v) : "l"(y_flag(sp, gr >> 6, tail_block(gr, t))) : "memory");
        if (v >= 32) break;
        __nanosleep(YSLEEP);
    }
    asm volatile("fence.acquire.gpu;" ::: "memory");
    asm volatile("fence.proxy.async.global;" ::: "memory");
}
__device__ __forceinline__ void tail_loads(uint32_t sbase, const uint8_t* sp, uint32_t gr, uint32_t pmask, int u0, int u1, int lane) {
    if (lane >= u0 && lane < u1) {
        const uint32_t bar = sbase + OFF_BAR + B_UNIT + 8 * lane;
        mbar_expect_tx(bar, 8192);
        bulk_g2s(sbase + (lane < 10 ? OFF_U0 : OFF_U1 - 81920) + lane * 8192, sp + y_unit(tail_block(gr, lane / 5), (gr & 31) * 5 + lane % 5, gr >> 6, pmask), 8192, bar);
    }
    __syncwarp();
}
__device__ __forceinline__ const float* corr_src(uint32_t gr, int t) { return &g_corr[(((gr >> 6) * 8 + tail_block(gr, t)) * kNT + (gr & 31) * 5) * 64]; }
__device__ __forceinline__ void corr_load(uint32_t sbase, uint32_t gr, int t, uint32_t bar) {
    bulk_g2s(sbase + (t < 2 ? OFF_C0 : OFF_C1) + (t & 1) * 1280, corr_src(gr, t), 1280, bar);
}
__device__ __forceinline__ void tail_phase(uint32_t sbase, uint8_t* smem, uint8_t* sp, int wg, const __nv_bfloat16* __restrict__ x,
                                           const __nv_bfloat16* __restrict__ wt, const __nv_bfloat16* __restrict__ gamma,
                                           const __nv_bfloat16* __restrict__ beta, __nv_bfloat16* __restrict__ out) {
    const uint32_t* ts = reinterpret_cast<const uint32_t*>(smem + OFF_TS);
    const uint32_t gr = __shfl_sync(0xffffffffu, ts[64], 0);
    const float sx = __uint_as_float(ts[74]), sw = __uint_as_float(ts[75]);
    const int tid = threadIdx.x, w = (tid >> 5) & 3, lane = tid & 31, g = lane >> 2, q = lane & 3;
    const int b = gr >> 6, part = gr & 31;
    mbar_wait(sbase + OFF_BAR + B_FTAB, 0);
#pragma unroll 1
    for (int rd = 0; rd < 4 - wg; rd++) {
        if (rd < 2) {
            float acc[28], acc2[28], s[8] = {0.f, 0.f, 0.f, 0.f, 0.f, 0.f, 0.f, 0.f};
            const float swq = q == 0 ? sw : 0.f;
            const uint32_t ub = sbase + (rd ? OFF_U1 : OFF_U0) + wg * 40960, ubar = sbase + OFF_BAR + B_UNIT + 80 * rd + 40 * wg;
            const float* c1 = reinterpret_cast<const float*>(smem + (rd ? OFF_C1 : OFF_C0) + wg * 1280) + 16 * w + g;
            const uint32_t ka = ub + (lane >> 4) * 1024 + (lane & 7) * 128 + (((2 * w + ((lane >> 3) & 1)) ^ (lane & 7)) << 4);
            auto inverse = [&](float (&d)[28], int u) {
                const uint32_t dA = desc_lo(ub + u * 8192), dB = desc_lo(sbase + OFF_F);
                wg_fence();
                wgmma_n56_ss<0>(d, dA, dB);
                wgmma_n56_ss<1>(d, dA + 128, dB + 2);
                wgmma_n56_ss<1>(d, dA + 256, dB + 4);
                wgmma_n56_ss<1>(d, dA + 384, dB + 6);
                wg_commit();
            };
            auto keep = [&](float (&d)[28], int u, int un) {
                const bool ok = mbar_try(ubar + 8 * un, 0);
                reg_fence(d);
                d[25] = fmaf(c1[u * 64] * sx, swq, d[25]);
                d[27] = fmaf(c1[u * 64 + 8] * sx, swq, d[27]);
                if (part == 31 && u == 4) {
                    if (q >= 2) d[16] = d[18] = 0.f;
                    if (q >= 1) d[17] = d[19] = 0.f;
#pragma unroll
                    for (int i = 20; i < 28; i++) d[i] = 0.f;
                }
                const uint32_t a = ka + u * 8192;
#pragma unroll
                for (int j = 0; j < 6; j += 2)
                    stmatrix_x4_t(a + j * 1024, pack_f16(d[4 * j], d[4 * j + 1]), pack_f16(d[4 * j + 2], d[4 * j + 3]),
                                  pack_f16(d[4 * j + 4], d[4 * j + 5]), pack_f16(d[4 * j + 6], d[4 * j + 7]));
                asm volatile("stmatrix.sync.aligned.m8n8.x2.trans.shared.b16 [%0], {%1,%2};"
                             ::"r"(a + 6 * 1024), "r"(pack_f16(d[24], d[25])), "r"(pack_f16(d[26], d[27])) : "memory");
#pragma unroll
                for (int i = 0; i < 28; i++) {
                    s[i & 3] += d[i];
                    s[4 + (i & 3)] = fmaf(d[i], d[i], s[4 + (i & 3)]);
                }
#pragma unroll
                for (int i = 0; i < 8; i++) asm volatile("" : "+f"(s[i]));
                if (!ok) mbar_wait(ubar + 8 * un, 0);
                wg_wait<0>();
            };
            if (rd) mbar_wait(sbase + OFF_BAR + B_C1, 0);
            mbar_wait(ubar, 0);
            inverse(acc, 0);
            mbar_wait(ubar + 8, 0);
            wg_wait<0>();
#pragma unroll 1
            for (int u = 0;; u += 2) {
                inverse(acc2, min(u + 1, 4));
                keep(acc, u, min(u + 2, 4));
                if (u == 4) break;
                inverse(acc, u + 2);
                keep(acc2, u + 1, min(u + 3, 4));
            }
#pragma unroll
            for (int i = 0; i < 8; i += 2) {
                s[i] += s[i + 1];
                s[i] += __shfl_xor_sync(0xffffffffu, s[i], 1);
                s[i] += __shfl_xor_sync(0xffffffffu, s[i], 2);
            }
            const float mine = q == 0 ? s[0] : q == 1 ? s[2] : q == 2 ? s[4] : s[6];
            asm volatile("red.relaxed.gpu.global.add.u64 [%0], %1;"
                         ::"l"(part_sums(sp, b, tail_block(gr, 2 * rd + wg)) + 2 * (16 * w + 8 * (q & 1) + g) + (q >> 1)),
                         "l"(fabsf(mine) < 0x1p25f ? __float2ll_rn(mine * 0x1p21f) * 4096 + 1 : 65ll) : "memory");
            __syncwarp();
            if (lane == 0) mbar_arrive(sbase + OFF_BAR + B_SUM + 8 * (2 * rd + wg));
            if (rd == 0) continue;
        }
        const int t = rd == 3 ? 3 : 2 * rd - 2 + wg, db = tail_block(gr, t), i0 = rd == 3 ? FCUT : 0, i1 = rd == 2 && wg ? FCUT : 256;
#pragma unroll 1
        for (uint32_t n = 0; n < (1u << 20); n++)
            if (mbar_try(sbase + OFF_BAR + B_NRM + 8 * t, 0)) break;
        if (reinterpret_cast<const volatile uint32_t*>(ts)[77 + t]) {
            if (rd < 3) direct_block(x, wt, gamma, beta, out, reinterpret_cast<float*>(smem + OFF_DIR + wg * 8192), b, db, part, ts[76]);
            continue;
        }
        const int jh = w & 1, r0 = 8 * (w >> 1);
        const int lim = min(250, kL - part * 250) - r0 - g;
        float na[8], nb[8];
#pragma unroll
        for (int i = 0; i < 8; i += 2) {
            const float4 v = reinterpret_cast<const float4*>(smem + OFF_GB)[32 * t + 16 * jh + 2 * i + q];
            na[i] = v.x; nb[i] = v.y; na[i + 1] = v.z; nb[i + 1] = v.w;
        }
        __nv_bfloat16* o = out + ((size_t)b * kL + part * 250 + i0 + r0 + g) * 512 + 64 * db + 32 * jh + 8 * q;
        const int row = i0 + r0 + (lane & 7);
        int l = row % kMO;
        uint32_t ra = sbase + (t < 2 ? OFF_U0 : OFF_U1) + (t & 1) * 40960 + row / kMO * 8192 + l * 128;
        const int cc = 4 * jh + (lane >> 3);
        auto fetch = [&](uint32_t (&r)[4]) {
            asm volatile("ldmatrix.sync.aligned.m8n8.x4.shared.b16 {%0,%1,%2,%3}, [%4];"
                         : "=r"(r[0]), "=r"(r[1]), "=r"(r[2]), "=r"(r[3]) : "r"(ra + (((cc ^ l) & 7) << 4)) : "memory");
            const bool wrap = l >= kMO - 16;
            l += wrap ? 16 - kMO : 16;
            ra += wrap ? 2048 + 8192 - kMO * 128 : 2048;
        };
        auto gelu8 = [&](const uint32_t (&r)[4], uint32_t (&p)[4]) {
#pragma unroll
            for (int i = 0; i < 4; i++) {
                float lo, hi;
                asm("{\n.reg .b16 a, b;\nmov.b32 {a, b}, %2;\ncvt.f32.f16 %0, a;\ncvt.f32.f16 %1, b;\n}" : "=f"(lo), "=f"(hi) : "r"(r[i]));
                p[i] = pack_bf16(gelu_half(fmaf(lo, na[2 * i], nb[2 * i])), gelu_half(fmaf(hi, na[2 * i + 1], nb[2 * i + 1])));
            }
        };
        uint32_t r[2][4], rn[2][4];
        fetch(r[0]);
        fetch(r[1]);
#pragma unroll 1
        for (int i = i0; i < i1; i += 32) {
            fetch(rn[0]);
            fetch(rn[1]);
            uint32_t p0[4], p1[4];
            gelu8(r[0], p0);
            gelu8(r[1], p1);
            if (i < lim) stg128(o, p0[0], p0[1], p0[2], p0[3]);
            if (i + 16 < lim) stg128(o + 16 * 512, p1[0], p1[1], p1[2], p1[3]);
            o += 32 * 512;
#pragma unroll
            for (int k = 0; k < 4; k++) { r[0][k] = rn[0][k]; r[1][k] = rn[1][k]; }
        }
    }
}
__device__ __forceinline__ void channel_scales(uint32_t sbase, uint8_t* smem, uint8_t* sp, int lane) {
    volatile uint32_t* ts = reinterpret_cast<volatile uint32_t*>(smem + OFF_TS);
    const uint32_t gr = ts[64], bars = sbase + OFF_BAR;
#pragma unroll 1
    for (int t = 0; t < 4; t++) {
#pragma unroll 1
        for (uint32_t n = 0; n < (1u << 20); n++)
            if (mbar_try(bars + B_SUM + 8 * t, 0)) break;
        long long s[4];
#pragma unroll 1
        for (uint32_t n = 0; n < (1u << 19); n++) {
            const unsigned long long* p = part_sums(sp, gr >> 6, tail_block(gr, t)) + 4 * lane;
#pragma unroll
            for (int i = 0; i < 4; i++) asm volatile("ld.relaxed.gpu.global.u64 %0, [%1];" : "=l"(s[i]) : "l"(p + i) : "memory");
            if (__all_sync(0xffffffffu, s[0] & s[1] & s[2] & s[3] & 32)) break;
        }
        const float sx = __uint_as_float(ts[74]), sw = __uint_as_float(ts[75]);
        bool bad = false;
#pragma unroll
        for (int i = 0; i < 2; i++) {
            const float mean = (float)(s[2 * i] >> 12) * (0x1p-21f / kL), sq = (float)(s[2 * i + 1] >> 12) * (0x1p-21f / kL);
            float2* gb = reinterpret_cast<float2*>(smem + OFF_GB) + 64 * t + 2 * lane + i;
            const float den = fmaxf(sq - mean * mean, 0.f) + 1e-5f * sx * sw * sx * sw, a = gb->x * rsqrtf(den);
            *gb = make_float2(0.5f * a, 0.5f * (gb->y - mean * a));
            bad |= ((s[2 * i] | s[2 * i + 1]) & 0xFC0) || !(den >= 0x1p-22f);
        }
        bad = __any_sync(0xffffffffu, bad);
        if (lane == 0) ts[77 + t] = bad;
        __syncwarp();
        if (lane == 0) mbar_arrive(bars + B_NRM + 8 * t);
    }
    unsigned exits = 0;
    if (lane == 0) exits = atomicAdd(&g_exit, 1);
    if (__shfl_sync(0xffffffffu, exits, 0) == NCTA - 1) {
        for (int i = 0; i < 4; i++) *chunk_flag(sp, i >> 1, i & 1, lane) = 0;
        if (lane < 2) *chunk_flag(sp, 0, lane, 32) = 0;
        g_tsel[lane] = 0;
        if (lane < 16) *y_flag(sp, lane >> 3, lane & 7) = 0;
#pragma unroll 1
        for (int i = 0; i < 32; i++) stg128(part_sums(sp, i >> 4, (i >> 1) & 7) + (i & 1) * 64 + 2 * lane, 0, 0, 0, 0);
        if (lane == 0) { g_exit = 0; g_epoch = ts[76]; }
    }
}

__device__ __forceinline__ void publish_tiles(uint8_t* sp, uint32_t bars, int cta, int wg) {
#pragma unroll 1
    for (int m = 0; m < 2; m++) {
        mbar_wait(bars + B_YS + 8 * (2 * m + wg), 0);
        asm volatile("fence.acq_rel.gpu;" ::: "memory");
        red_relaxed(y_flag(sp, (cta >> 1) & 1, 4 * m + 2 * (cta & 1) + wg));
    }
}

__global__ void __launch_bounds__(384, 1)
main_kernel(const __grid_constant__ CUtensorMap tmx, const __grid_constant__ CUtensorMap tmw0, const __grid_constant__ CUtensorMap tmw1,
            const __nv_bfloat16* __restrict__ x, const __nv_bfloat16* __restrict__ wt, const __nv_bfloat16* __restrict__ gamma,
            const __nv_bfloat16* __restrict__ beta, __nv_bfloat16* __restrict__ out) {
    extern __shared__ __align__(1024) uint8_t smem_raw[];
    const uint32_t sbase = smem_u32(smem_raw) & ~1023u;
    const uint32_t bars = sbase + OFF_BAR;
    const int tid = threadIdx.x, wg = __shfl_sync(0xffffffffu, tid >> 7, 0), lane = tid & 31;
    const int cta = blockIdx.x;
    volatile uint32_t* ts = reinterpret_cast<volatile uint32_t*>(smem_raw + OFF_TS);
    uint8_t* const sp = reinterpret_cast<uint8_t*>((reinterpret_cast<uintptr_t>(g_sp) + (2u << 20) - 1) & ~(uintptr_t)((2u << 20) - 1));
    const bool probing = (cta & 3) == 0 && lane == 0 && tid < 128;
    unsigned* pw = reinterpret_cast<unsigned*>(sp + (tid < 64 ? ((cta >> 2) << 21) + ((tid & 32) ? 15 : 13) * 4096
                                                              : ((tid & 32) ? 0 : 14) * 4096 + (cta >> 2) * 128));
    unsigned pv = 0;
    if (probing) {
        stg128(pw, 0, 0, 0, 0);
        stg128(pw + 4, 0, 0, 0, 0);
        asm volatile("atom.relaxed.gpu.global.exch.b32 %0, [%1], %2;" : "=r"(pv) : "l"(pw), "r"(7) : "memory");
    }
    if (tid == 320) bar_setup<0, B_SIG>(bars);
    if (tid >= 256 && tid < 262) ts[68 + tid - 256] = tid < 260 ? 0xffffu : 0;
    if (tid == 383) asm volatile("griddepcontrol.launch_dependents;");
    __syncthreads();

    if (wg == 2) {
        asm volatile("setmaxnreg.dec.sync.aligned.u32 40;");
        const int role = (tid >> 5) & 3;
        if (role == 3) {
            unsigned v = 0;
#pragma unroll 1
            for (uint32_t n = 0; n < (1u << 15); n++) {
                asm volatile("ld.relaxed.gpu.global.u32 %0, [%1];" : "=r"(v) : "l"(&g_tsel[lane]) : "memory");
                if (__all_sync(0xffffffffu, v & 16)) break;
                __nanosleep(TSLEEP);
            }
            const uint32_t m1 = __ballot_sync(0xffffffffu, v & 8), below = (1u << lane) - 1;
            const int rank = (v & 8) ? 32 - __popc(m1) + __popc(m1 & below) : __popc(~m1 & below);
            ts[lane] = rank;
            ts[32 + rank] = lane;
            const uint32_t p0 = __ballot_sync(0xffffffffu, v & 1);
            if (lane == 0) ts[66] = p0;
            if (lane == (cta >> 2)) ts[64] = rank * 4 + (cta & 3);
            const int part = (m1 >> (cta >> 2)) & 1;
            __syncwarp();
            if (lane == 0) { mbar_arrive(bars + B_TSEL); }
            mbar_wait(bars + B_TSEL, 0);
            mbar_wait(bars + B_PUB, 0);
            int gc = 0;
            const int gend = lane == 0 ? 33 : lane == 1 ? GMAX + 1 : 0;
#pragma unroll 1
            for (uint32_t n = 0; n < (1u << 16) && __any_sync(0xffffffffu, gc < gend); n++) {
                asm volatile("ld.relaxed.gpu.global.u32 %0, [%1];" : "=r"(v) : "l"(chunk_flag(sp, lane == 1, part, min(gc, 32 - (lane & 1)))) : "memory");
                if (gc < gend && v >= NCTA) {
                    asm volatile("fence.acquire.gpu;" ::: "memory");
                    mbar_arrive(bars + (lane == 0 ? B_RDY : B_GATE) + 8 * gc);
                    gc++;
                }
            }
            if (lane == 0) publish_tiles(sp, bars, cta, 1);
        } else if (role == 0) {
            const int b = (cta >> 1) & 1, dq = cta & 1;
            for (int v = 0; v < V0; v++) {
                mbar_wait(bars + B_EMPTY + 8 * (v % NST), ((v / NST) & 1) ^ 1);
                if (lane == 0) {
                    mbar_arrive(bars + B_FULL + 8 * (v % NST));
                    mbar_arrive(bars + B_FULL + 8 * (v % NST));
                }
            }
            mbar_wait(bars + B_TSEL, 0);
            const uint32_t gr = ts[64], grp = gr >> 6, idx = (gr >> 2) & 15, pmask = ts[66];
            const uint32_t n0 = idx * 4 + 2 * dq + ((lane & 1) ^ 1), r0 = lane < 3 ? idx * 4 + b : R_W + n0 / 3;
            const uint32_t base = (r0 << 16) + 4096 + ((lane < 3 ? lane : n0 % 3) << 14), step = (lane < 3 ? 64 : 22) << 16;
            uint32_t sels = 0;
            for (int i = 0; i < 12; i++) sels |= run_sel(r0 + i * (step >> 16), grp, pmask) << i;
            int ld = 0;
            const uint32_t bytes = lane == 2 ? XB - 16384 : 8192;
#pragma unroll 1
            for (int h = 0; h < 64; h++) {
                const int s = step_k(h), st = (h + V0) % NST;
                const bool newx = h < HEND ? !(h & 1) : h < HEND + 4;
                const uint32_t fb = bars + B_FULL + 8 * st;
                const uint32_t k = lane < 3 ? (s >> 1) % RX : (h + RW - 64 % RW) % RW, half = lane < 3 ? s & 1 : 0;
                const uint8_t* gsrc = sp + (base + k * step + (half << 17) + ((((sels >> k) ^ half) & 1) << 13));
                const uint32_t dst = sbase + (lane < 3 ? OFF_X + (s & 3) * XB + lane * 8192 : st * 8192 + (lane == 3 ? OFF_W0 : OFF_W1));
                auto landed = [&]() {
                    if (ld < h && mbar_test(bars + B_FULL + 8 * ((ld + V0) % NST), ((ld + V0) / NST) & 1)) {
                        if (!(ld & 1) && (ld >> 1) <= GMAX && lane < 2) red_relaxed(chunk_flag(sp, 1, lane, ld >> 1));
                        ld++;
                    }
                };
                if ((h & 1) || h == 0) {
#pragma unroll 1
                    for (uint32_t n = 0; n < (1u << 19) && !mbar_test(bars + B_RDY + 8 * ((h + 1) >> 1), 0); n++) landed();
                    asm volatile("fence.proxy.async.global;" ::: "memory");
                }
#pragma unroll 1
                for (uint32_t n = 0; n < (1u << 19) && !mbar_test(bars + B_EMPTY + 8 * st, (((h + V0) / NST) & 1) ^ 1); n++) landed();
#pragma unroll 1
                for (uint32_t n = 0; n < (1u << 19) && ld <= h - NST; n++) landed();
                if (lane == 0) mbar_expect_tx(fb, newx ? 16384 + XB : 16384);
                __syncwarp();
                if (lane < 3 ? newx : lane < 5) bulk_g2s(dst, gsrc, bytes, fb);
            }
            tail_poll(sp, gr, 0);
            mbar_wait(bars + B_T2, 0);
            tail_loads(sbase, sp, gr, pmask, 0, 5, lane);
            tail_poll(sp, gr, 1);
            tail_loads(sbase, sp, gr, pmask, 5, 8, lane);
            mbar_wait(bars + B_YS + 16, 0);
            tail_loads(sbase, sp, gr, pmask, 8, 10, lane);
            for (int v = V0 + 64; v < V0 + 64 + NST; v++) mbar_wait(bars + B_EMPTY + 8 * (v % NST), ((v / NST) & 1) ^ 1);
            if (lane == 0) {
                mbar_expect_tx(bars + B_C1, 2560);
                corr_load(sbase, gr, 2, bars + B_C1);
                corr_load(sbase, gr, 3, bars + B_C1);
            }
            tail_poll(sp, gr, 2);
            tail_loads(sbase, sp, gr, pmask, 10, 15, lane);
            tail_poll(sp, gr, 3);
            tail_loads(sbase, sp, gr, pmask, 15, 20, lane);
        } else if (role == 1) {
            auto raw_load = [&](int r, int h, uint32_t gr, uint32_t dst, uint32_t bar) {
                if (r >= 0) {
                    const int u = r * NCTA + cta, i = u % XPC, b = i >= kNT;
                    tma3d(dst, &tmx, u / XPC * 64, (i - b * kNT) * kMO, b, bar);
                } else if (h >= 0) {
                    const int c = 32 * step_k(h) + ((gr >> 1) & 30);
                    tma3d_ef(dst, c < 512 ? &tmw0 : &tmw1, step_m(h) * 256 + (gr & 3) * 64, 0, c & 511, bar);
                }
            };
            uint32_t gr;
            {
                const int v = lane >> 1, r = v < V0 ? x_round(v, lane & 1) : -1, h = v < V0 ? w_step(v, lane & 1) : -1;
                const uint32_t dst = pre_slot(sbase, v, lane & 1), bar = bars + B_PRE + 8 * lane;
                if (r >= 0 || h >= 0) mbar_expect_tx(bar, r >= 0 ? 8192 : 4096);
                if (v < PRE1) raw_load(r, -1, 0, dst, bar);
                mbar_wait(bars + B_TSEL, 0);
                gr = ts[64];
                raw_load(-1, h, gr, dst, bar);
                if (v >= PRE1) raw_load(r, -1, 0, dst, bar);
                __syncwarp();
            }
            mbar_wait(bars + B_PUB, 0);
#pragma unroll 1
            for (int v = V0; v < V0 + 64; v++) {
                mbar_wait(bars + B_EMPTY + 8 * (v % NST), ((v / NST) & 1) ^ 1);
                __syncwarp();
                const int r = lane < 2 ? x_round(v, lane) : -1, h = lane < 2 ? w_step(v, lane) : -1;
                const uint32_t fb = bars + B_FULL + 8 * (v % NST);
                const uint32_t bytes = __reduce_add_sync(0xffffffffu, r >= 0 ? 8192 : h >= 0 ? 4096 : 0);
                if (lane == 0) mbar_expect_tx(fb, bytes);
                __syncwarp();
                raw_load(r, h, gr, raw_slot(sbase, v, lane), fb);
                if (v >= 63 && v < 67) {
                    if (v == 66 && lane == 0) {
#pragma unroll 1
                        for (uint32_t n = 0; n < (1u << 15); n++) {
                            unsigned c0, c1;
                            asm volatile("ld.relaxed.gpu.global.u32 %0, [%1];" : "=r"(c0) : "l"(&g_cready[(gr >> 6) * 64]) : "memory");
                            asm volatile("ld.relaxed.gpu.global.u32 %0, [%1];" : "=r"(c1) : "l"(&g_cready[(gr >> 6) * 64 + 32]) : "memory");
                            if (c0 == ts[76] && c1 == ts[76]) break;
                            __nanosleep(500);
                        }
                        asm volatile("fence.acquire.gpu;" ::: "memory");
                        asm volatile("fence.proxy.async.global;" ::: "memory");
                        mbar_expect_tx(bars + B_FTAB, 8192 + 2560);
                        bulk_g2s(sbase + OFF_F, g_tab.inv, 8192, bars + B_FTAB);
                        for (int t = 0; t < 2; t++) {
                            corr_load(sbase, gr, t, bars + B_FTAB);
                            asm volatile("cp.async.bulk.prefetch.L2.global [%0], 1280;" ::"l"(corr_src(gr, 2 + t)) : "memory");
                        }
                    }
                    const int t = v - 63;
                    for (int i = lane; i < kNT; i += 32)
                        ts[(OFF_YT - OFF_TS) / 4 + t * kNT + i] = y_unit(4 * (t >> 1) + 2 * (cta & 1) + (t & 1), i, (cta >> 1) & 1, ts[66]);
                }
            }
            channel_scales(sbase, smem_raw, sp, lane);
        } else {
            uint32_t epoch;
            if (lane == 0) {
                bar_setup<B_SIG, B_END>(bars);
                mbar_arrive(bars + B_TSEL);
            }
            asm volatile("ld.relaxed.gpu.global.u32 %0, [%1];" : "=r"(epoch) : "l"(&g_epoch) : "memory");
            mbar_wait(bars + B_TSEL, 0);
            const uint32_t gr = ts[64];
#pragma unroll
            for (int i = lane; i < 256; i += 32) {
                const int d = 64 * tail_block(gr, i >> 6) + (i & 33) + 8 * ((i >> 1) & 3) + 2 * ((i >> 3) & 3);
                ts[(OFF_GB - OFF_TS) / 4 + 2 * i] = (uint32_t)__bfloat16_as_ushort(gamma[d]) << 16;
                ts[(OFF_GB - OFF_TS) / 4 + 2 * i + 1] = (uint32_t)__bfloat16_as_ushort(beta[d]) << 16;
            }
            if (lane == 0) ts[76] = epoch + 1;
            __syncwarp();
            if (lane) return;
#pragma unroll 1
            for (int gc = 0; gc < 33;) {
                mbar_wait(bars + B_SIG + 8 * gc, 0);
                if (gc < MERGE) mbar_wait(bars + B_SIG + 8 * MERGE, 0);
                int ge = gc + 1;
                while (ge < 33 && mbar_test(bars + B_SIG + 8 * ge, 0)) ge++;
                asm volatile("fence.acq_rel.gpu;" ::: "memory");
                for (; gc < ge; gc++) {
                    red_relaxed(chunk_flag(sp, 0, 0, gc));
                    red_relaxed(chunk_flag(sp, 0, 1, gc));
                    if (gc == 0) mbar_arrive(bars + B_PUB);
                }
            }
            publish_tiles(sp, bars, cta, 0);
        }
    } else {
        asm volatile("setmaxnreg.inc.sync.aligned.u32 232;");
        uint4 fw[2];
#pragma unroll
        for (int j = 0; j < 2; j++) fw[j] = __ldg(reinterpret_cast<const uint4*>(g_tab.fwd) + tid + 256 * j);
        if (wg == 1) {
            uint4 sm[8];
#pragma unroll
            for (int j = 0; j < 4; j++) {
                const int r = 2 * j + ((tid >> 6) & 1);
                sm[j] = __ldg(reinterpret_cast<const uint4*>(x) + ((r >> 2) * kRows + 1000 + 2000 * (r & 3)) * 128 + (((j + r) & 1) << 6) + (tid & 63));
                sm[4 + j] = __ldg(reinterpret_cast<const uint4*>(wt) + (4 * r * 512 + 67 * r + 7) * 64 + (tid & 63));
            }
#pragma unroll
            for (int k = 0; k < 2; k++) {
                uint32_t mx = 0;
#pragma unroll
                for (int j = 4 * k; j < 4 * k + 4; j++)
                    mx = __vmaxu2(__vmaxu2(mx, __vmaxu2(sm[j].x & 0x7FFF7FFFu, sm[j].y & 0x7FFF7FFFu)), __vmaxu2(sm[j].z & 0x7FFF7FFFu, sm[j].w & 0x7FFF7FFFu));
                mx = __reduce_max_sync(0xffffffffu, max(mx & 0xFFFFu, mx >> 16));
                if (lane == 0) atomicMax(const_cast<uint32_t*>(ts) + 72 + k, mx);
            }
        }
        if ((cta & 3) == 0) {
            if (probing) {
                const int w = tid >> 5;
                unsigned best = 0xffffu;
#pragma unroll 1
                for (int r = 0; r < 6; r++) {
                    unsigned t0, t1;
                    asm volatile("{\n.reg .pred p;\nsetp.eq.u32 p, %1, 0xffffffff;\nmov.u32 %0, 0;\n@!p mov.u32 %0, %%clock;\n}"
                                 : "=r"(t0) : "r"(pv) : "memory");
                    asm volatile("atom.relaxed.gpu.global.exch.b32 %0, [%1], %2;" : "=r"(pv) : "l"(pw), "r"(r) : "memory");
                    asm volatile("{\n.reg .pred p;\nsetp.eq.u32 p, %1, 0xffffffff;\nmov.u32 %0, 0;\n@!p mov.u32 %0, %%clock;\n}"
                                 : "=r"(t1) : "r"(pv) : "memory");
                    ts[68 + w] = best = min(best, t1 - t0);
                    const unsigned other = ts[68 + (w ^ 1)];
                    if (min(best, other) < PROBE_NEAR && max(best, other) > PROBE_NEAR) break;
                }
            }
            if (wg == 0) {
                named_bar(2, 128);
                if (tid == 0) {
                    const uint32_t part = ts[71] < ts[70];
                    const uint32_t v = 16 | (part << 3) | ((ts[69] < ts[68]) ^ part);
                    asm volatile("st.relaxed.gpu.global.u32 [%0], %1;" ::"l"(&g_tsel[cta >> 2]), "r"(v) : "memory");
                }
            }
        }
        uint32_t plan = tid < 2 * (V0 + 65) ? plan_word(tid >> 1, tid & 1, cta) : 0;
        {
            named_bar(1, 256);
            const uint32_t ex = max(251 - (int)(ts[72] >> 7), 8), ew = max(251 - (int)(ts[73] >> 7), 8);
            if (tid == 0) { ts[74] = ex << 23; ts[75] = ew << 23; }
            const uint32_t sx = ex * 0x800080u, sw = ew * 0x800080u;
#pragma unroll
            for (int j = 0; j < 2; j++) {
                const int i = tid + 256 * j, row = i >> 3, c = (i ^ row) & 7;
                sts128(sbase + OFF_F + 16 * i, mul_bf16x2(fw[j].x, sx), mul_bf16x2(fw[j].y, sx), mul_bf16x2(fw[j].z, sx), mul_bf16x2(fw[j].w, sx));
                if (c < 2) sts128(sbase + OFF_TMP + row * 32 + c * 16, mul_bf16x2(fw[j].x, sw), mul_bf16x2(fw[j].y, sw), mul_bf16x2(fw[j].z, sw), mul_bf16x2(fw[j].w, sw));
            }
            named_bar(1, 256);
        }
        const int t = tid & 127;
        Xf f;
        f.sbase = sbase; f.lane = lane; f.xsw = cta & 4; f.dw = desc_lo(sbase + (wg ? OFF_W1 : OFF_W0));
        {
            const int w = t >> 5;
            const uint32_t nw = (8 * (w & 1) + (lane >> 2)) * 4 + (cta & 3), rw = R_W + nw / 3;
            f.pw = sp + (rw << 16) + 4096 + ((nw % 3) << 14) + (w >> 1) * 128;
            f.cw = ((lane & 7) ^ (w >> 1)) << 4;
            for (int i = 0; i < RW; i++) f.cw |= run_sel(rw + i * 22, 0, 0) << (8 + i);
            mbar_wait(bars + B_TSEL, 0);
            const uint32_t gr = ts[64], pmask = ts[66];
            const uint32_t rx = ts[8 * w + (lane >> 2)];
            f.px = sp + ((rx & 15) << 18) + 4096;
            f.cx = ((lane & 7) << 4) | ((((pmask >> ((rx >> 3) & 1)) ^ -(((rx >> 1) ^ (rx >> 4)) & 1)) & 0x55) << 8);
#pragma unroll
            for (int i = 0; i < RW; i++) f.cw ^= (((pmask >> ((rw + i * 22) >> 5)) ^ (gr >> 6)) & 1) << (8 + i);
            if (plan & 4) plan |= ((gr & 12) << 8) | ((gr & 48) << 4) | ((gr & 48) << 1);
            if (tid < 2 * (V0 + 65)) ts[(OFF_PLAN - OFF_TS) / 4 + tid] = plan;
            const int row = tid >> 2, ch = tid & 3, s = ts[32 + (gr >> 6) * 16 + ((row >> 1) & 8) + (row & 7)], p = (row >> 3) & 1;
            const int frow = 16 * (s >> 3) + 8 * p + (s & 7);
            uint32_t v[4] = {0, 0, 0, 0};
            if ((ch >> 1) == (row >> 5))
                asm volatile("ld.shared.v4.b32 {%0,%1,%2,%3}, [%4];" : "=r"(v[0]), "=r"(v[1]), "=r"(v[2]), "=r"(v[3])
                             : "r"(sbase + OFF_TMP + frow * 32 + (ch & 1) * 16) : "memory");
            sts128(sbase + OFF_G + row * 64 + ((ch ^ ((row >> 1) & 3)) << 4), v[0], v[1], v[2], v[3]);
            fence_proxy_async_smem();
            named_bar(1, 256);
        }
        {
            float at[32];
#pragma unroll 1
            for (uint32_t v = 0; v < V0; v++) {
                const uint32_t e = plan_load(f, v, wg), raw = pre_slot(sbase, v, wg);
                mbar_wait(bars + B_FULL + 8 * (v % NST), (v / NST) & 1);
                if (e & 6) mbar_wait(bars + B_PRE + 16 * v + 8 * wg, 0);
                wg_fence();
                if ((e & 6) == 2) {
                    unit_mma<false>(at, f, raw);
                    wg_wait<0>();
                    unit_store<false>(at, f, e);
                } else if (e & 4) {
                    unit_mma<true>(at, f, raw);
                    wg_wait<0>();
                    unit_store<true>(at, f, e);
                }
                if (lane == 0) mbar_arrive(bars + B_EMPTY + 8 * (v % NST));
                unit_done(f, e, v);
            }
        }
        const int slot = cta >> 2;
        f.e = plan_load(f, V0, wg);
        uint32_t a0[40], a1[40], b0[40], b1[40];
#pragma unroll
        for (int i = 0; i < 40; i++) a0[i] = a1[i] = b0[i] = b1[i] = 0;
        if (slot == 0) gemm_main<true>(a0, a1, b0, b1, f, wg);
        else gemm_main<false>(a0, a1, b0, b1, f, wg);
#pragma unroll 1
        for (int m = 0; m < 2; m++) {
            if (slot == 0) gemm_last<true>(a0, a1, f, wg, m);
            else gemm_last<false>(a0, a1, f, wg, m);
            reg_fence(a0);
            reg_fence(a1);
            const int wsw = ts[64] & 4;
            const uint32_t ytab = sbase + OFF_YT + (m * 2 + wg) * (kNT * 4);
            store_round<0>(a0, a1, sbase + OFF_STG + wg * 16384, t, wg, sp, slot, ytab, wsw);
            store_round<1>(a0, a1, sbase + OFF_STG + wg * 16384, t, wg, sp, slot, ytab, wsw);
            store_round<2>(a0, a1, sbase + OFF_STG + wg * 16384, t, wg, sp, slot, ytab, wsw);
            __syncwarp();
            if (lane == 0) mbar_arrive(bars + B_YS + 8 * (2 * m + wg));
            if (m) break;
#pragma unroll
            for (int i = 0; i < 40; i++) { a0[i] = b0[i]; a1[i] = b1[i]; }
        }
        tail_phase(sbase, smem_raw, sp, wg, x, wt, gamma, beta, out);
    }
}

constexpr int C_STAGE = 32768 + 2 * XB, C_SMEM = 3 * C_STAGE + 64;
__global__ void __launch_bounds__(256, 1) corr_kernel(const __grid_constant__ CUtensorMap tmx, const __grid_constant__ CUtensorMap tmw) {
    extern __shared__ __align__(1024) uint8_t smem_raw[];
    const uint32_t sbase = smem_u32(smem_raw) & ~1023u, bars = sbase + 3 * C_STAGE;
    const int tid = threadIdx.x, wg = __shfl_sync(0xffffffffu, tid >> 7, 0), b = blockIdx.x >> 1, dh = blockIdx.x & 1;
    auto load = [&](int k) {
        const uint32_t st = sbase + (k % 3) * C_STAGE, bar = bars + 8 * (k % 3);
        mbar_expect_tx(bar, C_STAGE);
        for (int i = 0; i < 4; i++) tma2d(st + i * 8192, &tmw, 256 * dh + 64 * i, 64 * k, bar);
        tma4d(st + 32768, &tmx, 64 * k, 64 - kMO, 1, b, bar);
        tma4d(st + 32768 + XB, &tmx, 64 * k, 0, 0, b, bar);
    };
    uint32_t epoch = 0;
    if (tid == 0) {
        for (int i = 0; i < 3; i++) mbar_init(bars + 8 * i, 1);
        fence_mbar_init();
        fence_proxy_async_smem();
        for (int k = 0; k < 3; k++) load(k);
        asm volatile("ld.relaxed.gpu.global.u32 %0, [%1];" : "=r"(epoch) : "l"(&g_epoch) : "memory");
    }
    __syncthreads();
    float a[2][80];
#pragma unroll
    for (int i = 0; i < 80; i++) a[0][i] = a[1][i] = 0.f;
#pragma unroll 1
    for (int k = 0; k < 8; k++) {
        const uint32_t dA = desc_lo(sbase + (k % 3) * C_STAGE + wg * 16384), dB = desc_lo(sbase + (k % 3) * C_STAGE + 32768);
        mbar_wait(bars + 8 * (k % 3), (k / 3) & 1);
        wg_fence();
#pragma unroll
        for (int i = 0; i < 8; i++) {
            wgmma_n160_f<1>(a[i & 1], dA + (i & 1) * 512 + (i >> 1) * 128, dB + (i >> 1) * 2);
            wgmma_n160_f<-1>(a[i & 1], dA + (i & 1) * 512 + (i >> 1) * 128, dB + XB / 16 + (i >> 1) * 2);
        }
        wg_commit();
        wg_wait<0>();
        __syncthreads();
        if (tid == 0 && k + 3 < 8) load(k + 3);
    }
    reg_fence(a[0]);
    reg_fence(a[1]);
    const int w = (tid >> 5) & 3, g = (tid & 31) >> 2, q = tid & 3;
#pragma unroll
    for (int i = 0; i < 160; i++) {
        const int m = i / 80, j = i % 80, d = 16 * w + 8 * ((j >> 1) & 1) + g;
        g_corr[((b * 8 + 4 * dh + 2 * wg + m) * kNT + 8 * (j >> 2) + 2 * q + (j & 1)) * 64 + (d & 33) + 8 * ((d >> 1) & 3) + 2 * ((d >> 3) & 3)] = a[m][j];
    }
    __syncthreads();
    if (tid == 0) {
        asm volatile("fence.acq_rel.gpu;" ::: "memory");
        asm volatile("st.relaxed.gpu.global.u32 [%0], %1;" ::"l"(&g_cready[blockIdx.x * 32]), "r"(epoch + 1) : "memory");
    }
}

__global__ void __launch_bounds__(256) plain_conv(const __nv_bfloat16* __restrict__ x, const __nv_bfloat16* __restrict__ w) {
    __shared__ float xs[64][17], ws[16][65];
    float* h = reinterpret_cast<float*>(g_sp + (8u << 20));
    const int b = blockIdx.z, l0 = blockIdx.x * 64, d0 = blockIdx.y * 64, tx = threadIdx.x & 15, ty = threadIdx.x >> 4;
    float acc[4][4] = {};
    for (int k0 = 0; k0 < 31 * 512; k0 += 16) {
        for (int i = threadIdx.x; i < 1024; i += 256) {
            const int l = min(l0 + (i >> 4), kL - 1);
            xs[i >> 4][i & 15] = __bfloat162float(x[((size_t)b * kRows + l) * 1024 + k0 + (i & 15)]);
            ws[i >> 6][i & 63] = __bfloat162float(w[(size_t)(k0 + (i >> 6)) * 512 + d0 + (i & 63)]);
        }
        __syncthreads();
        for (int k = 0; k < 16; k++)
            for (int i = 0; i < 4; i++)
                for (int j = 0; j < 4; j++) acc[i][j] = fmaf(xs[ty * 4 + i][k], ws[k][tx * 4 + j], acc[i][j]);
        __syncthreads();
    }
    for (int i = 0; i < 4; i++)
        for (int j = 0; j < 4; j++)
            if (l0 + ty * 4 + i < kL) h[((size_t)b * kL + l0 + ty * 4 + i) * 512 + d0 + tx * 4 + j] = acc[i][j];
}
__global__ void __launch_bounds__(256) plain_norm(const __nv_bfloat16* __restrict__ gamma, const __nv_bfloat16* __restrict__ beta,
                                                  __nv_bfloat16* __restrict__ out) {
    __shared__ float s1[8][32], s2[8][32];
    const int c = threadIdx.x & 31, r = threadIdx.x >> 5, d = blockIdx.x * 32 + c;
    const float* h = reinterpret_cast<const float*>(g_sp + (8u << 20)) + (size_t)blockIdx.y * kL * 512 + d;
    float a = 0.f, q = 0.f;
    for (int l = r; l < kL; l += 8) { const float v = h[(size_t)l * 512]; a += v; q = fmaf(v, v, q); }
    s1[r][c] = a; s2[r][c] = q;
    __syncthreads();
    a = q = 0.f;
    for (int i = 0; i < 8; i++) { a += s1[i][c]; q += s2[i][c]; }
    const float mean = a * (1.0f / kL), sc = __bfloat162float(gamma[d]) / sqrtf(fmaxf(q * (1.0f / kL) - mean * mean, 0.f) + 1e-5f);
    const float sh = __bfloat162float(beta[d]) - mean * sc;
    for (int l = r; l < kL; l += 8)
        out[((size_t)blockIdx.y * kL + l) * 512 + d] = __float2bfloat16(gelu_half(0.5f * fmaf(h[(size_t)l * 512], sc, sh)));
}

typedef CUresult (*EncodeTiledFn)(CUtensorMap*, CUtensorMapDataType, cuuint32_t, void*, const cuuint64_t*, const cuuint64_t*,
                                  const cuuint32_t*, const cuuint32_t*, CUtensorMapInterleave, CUtensorMapSwizzle,
                                  CUtensorMapL2promotion, CUtensorMapFloatOOBfill);

void encode(EncodeTiledFn fn, CUtensorMap* tm, const void* ptr, int rank, const cuuint64_t* dims, const cuuint64_t* strides,
            const cuuint32_t* box, CUtensorMapL2promotion promo, CUtensorMapSwizzle swz = CU_TENSOR_MAP_SWIZZLE_128B) {
    const cuuint32_t es[5] = {1, 1, 1, 1, 1};
    fn(tm, CU_TENSOR_MAP_DATA_TYPE_BFLOAT16, rank, const_cast<void*>(ptr), dims, strides, box, es, CU_TENSOR_MAP_INTERLEAVE_NONE,
       swz, promo, CU_TENSOR_MAP_FLOAT_OOB_FILL_NONE);
}

}

extern "C" void kernel_launch(void* const* d_in, const int* in_sizes, int n_in, void* d_out, int out_size) {
    const __nv_bfloat16* x = (const __nv_bfloat16*)d_in[0];
    const __nv_bfloat16* w = (const __nv_bfloat16*)d_in[1];
    const __nv_bfloat16* gamma = (const __nv_bfloat16*)d_in[2];
    const __nv_bfloat16* beta = (const __nv_bfloat16*)d_in[3];
    static EncodeTiledFn enc = nullptr;
    static int resident = 0;
    if (!enc) {
        void* fn = nullptr;
        cudaDriverEntryPointQueryResult qr;
        cudaGetDriverEntryPoint("cuTensorMapEncodeTiled", &fn, cudaEnableDefault, &qr);
        enc = (EncodeTiledFn)fn;
        cudaFuncSetAttribute(main_kernel, cudaFuncAttributeMaxDynamicSharedMemorySize, MAIN_SMEM);
        cudaFuncSetAttribute(corr_kernel, cudaFuncAttributeMaxDynamicSharedMemorySize, C_SMEM);
        int dev = 0, per_sm = 0;
        cudaGetDevice(&dev);
        cudaDeviceGetAttribute(&resident, cudaDevAttrMultiProcessorCount, dev);
        cudaOccupancyMaxActiveBlocksPerMultiprocessor(&per_sm, main_kernel, 384, MAIN_SMEM);
        resident *= per_sm;
    }
    if (resident < NCTA + 4) {
        plain_conv<<<dim3((kL + 63) / 64, 8, 2), 256>>>(x, w);
        plain_norm<<<dim3(16, 2), 256>>>(gamma, beta, (__nv_bfloat16*)d_out);
        return;
    }
    CUtensorMap tmx, tmw0, tmw1, tmcx, tmcw;
    {
        const cuuint64_t dims[3] = {1024, kRows, 2}, strides[2] = {2048, (cuuint64_t)kRows * 2048};
        const cuuint32_t box[3] = {64, 64, 1};
        encode(enc, &tmx, x, 3, dims, strides, box, CU_TENSOR_MAP_L2_PROMOTION_L2_128B);
    }
    {
        const cuuint64_t dims0[3] = {512, 16, 512}, dims1[3] = {512, 15, 512}, strides[2] = {2 * 512 * 512 * 2, 1024};
        const cuuint32_t box[3] = {64, 16, 2};
        encode(enc, &tmw0, w, 3, dims0, strides, box, CU_TENSOR_MAP_L2_PROMOTION_L2_128B);
        encode(enc, &tmw1, w + 512 * 512, 3, dims1, strides, box, CU_TENSOR_MAP_L2_PROMOTION_L2_128B);
    }
    {
        const cuuint64_t dims[4] = {512, kMO, kNT, 2}, strides[3] = {2048, kMO * 2048, (cuuint64_t)kRows * 2048};
        const cuuint32_t box[4] = {64, 1, kNT, 1};
        encode(enc, &tmcx, x, 4, dims, strides, box, CU_TENSOR_MAP_L2_PROMOTION_L2_128B);
        const cuuint64_t dimw[2] = {512, 512}, stridew[1] = {1024};
        const cuuint32_t boxw[2] = {64, 64};
        encode(enc, &tmcw, w + 30 * 512 * 512, 2, dimw, stridew, boxw, CU_TENSOR_MAP_L2_PROMOTION_L2_128B);
    }
    main_kernel<<<NCTA, 384, MAIN_SMEM>>>(tmx, tmw0, tmw1, x, w, gamma, beta, (__nv_bfloat16*)d_out);
    cudaLaunchConfig_t cfg = {};
    cudaLaunchAttribute at[1];
    cfg.gridDim = 4;
    cfg.blockDim = 256;
    cfg.dynamicSmemBytes = C_SMEM;
    cfg.stream = cudaStreamPerThread;
    at[0].id = cudaLaunchAttributeProgrammaticStreamSerialization;
    at[0].val.programmaticStreamSerializationAllowed = 1;
    cfg.attrs = at;
    cfg.numAttrs = 1;
    cudaLaunchKernelEx(&cfg, corr_kernel, tmcx, tmcw);
}
```

```cpp
#include <cuda_runtime.h>
#include <cuda_bf16.h>
#include <cuda.h>
#include <stdint.h>

namespace {

constexpr int kL    = 7985;
constexpr int kRows = 8000;
constexpr int kMO   = 50;
constexpr int kNT   = 160;

constexpr int V0 = 7;
constexpr int NPRE = 6;
constexpr int RX = 4;
constexpr int FCUT = 128;
constexpr int YSLEEP = 100;
constexpr int PRE1 = 4;
constexpr int TSLEEP = 200;
constexpr int MERGE = 1;
constexpr int RW = 10;

static_assert(V0 >= 7 && V0 <= 9 && RX >= 2 && RX <= 4 && RW >= V0 - 1 && RW <= 12, "rings must fit and be as deep as the look-ahead");
constexpr uint32_t HOME_MASK = 0xB;
constexpr uint32_t R_W = 64 * RX, NPAGES = (R_W + 22 * RW + 31) / 32;

__device__ __align__(1024) uint8_t g_sp[(size_t)(NPAGES + 1) * (2u << 20)];
__device__ __align__(128) unsigned g_tsel[32];
__device__ __forceinline__ uint32_t run_sel(uint32_t r, uint32_t group, uint32_t pmask) {
    return ((pmask >> (r >> 5)) ^ __popc(r & HOME_MASK) ^ group) & 1;
}
__device__ __forceinline__ uint32_t run_off(uint32_t r, uint32_t run, uint32_t group, uint32_t pmask) {
    return (r << 16) + 4096 + (run_sel(r, group, pmask) << 13) + (run << 14);
}
__device__ __forceinline__ unsigned* chunk_flag(uint8_t* sp, int done, int part, int chunk) {
    return reinterpret_cast<unsigned*>(sp + (4 + 3 * (chunk >> 5)) * 65536 + (done ? (part ? 15 : 13) : (part ? 0 : 14)) * 4096 + (chunk & 31) * 128);
}
__device__ __forceinline__ unsigned long long* part_sums(uint8_t* sp, int b, int db, uint32_t epoch) {
    return reinterpret_cast<unsigned long long*>(sp + (8 + 2 * db + ((__popc((8 + 2 * db) & HOME_MASK) ^ b) & 1)) * 65536 + 13 * 4096 + (epoch & 1) * 1024);
}
__device__ __forceinline__ unsigned* y_flag(uint8_t* sp, int b, int db) { return reinterpret_cast<unsigned*>(part_sums(sp, b, db, 0) + 512); }
__device__ __align__(256) float g_corr[16 * kNT * 64];
__device__ unsigned g_cready[4 * 32];
__device__ float g_direct[512 * 250 * 64];
__device__ unsigned long long g_dpart[2 * 512 * 64];
__device__ unsigned g_exit, g_epoch;

__device__ __forceinline__ uint32_t smem_u32(const void* p) { return (uint32_t)__cvta_generic_to_shared(p); }

__device__ __forceinline__ void mbar_init(uint32_t bar, uint32_t count) {
    asm volatile("mbarrier.init.shared::cta.b64 [%0], %1;" ::"r"(bar), "r"(count) : "memory");
}
__device__ __forceinline__ void mbar_expect_tx(uint32_t bar, uint32_t bytes) {
    asm volatile("mbarrier.arrive.expect_tx.shared::cta.b64 _, [%0], %1;" ::"r"(bar), "r"(bytes) : "memory");
}
__device__ __forceinline__ void mbar_arrive(uint32_t bar) {
    asm volatile("mbarrier.arrive.shared::cta.b64 _, [%0];" ::"r"(bar) : "memory");
}
__device__ __forceinline__ bool mbar_try(uint32_t bar, uint32_t parity) {
    uint32_t ok;
    asm volatile(
        "{\n.reg .pred p;\n"
        "mbarrier.try_wait.parity.shared::cta.b64 p, [%1], %2;\n"
        "selp.u32 %0, 1, 0, p;\n}\n"
        : "=r"(ok) : "r"(bar), "r"(parity) : "memory");
    return ok;
}
__device__ __forceinline__ bool mbar_test(uint32_t bar, uint32_t parity) {
    uint32_t ok;
    asm volatile(
        "{\n.reg .pred p;\n"
        "mbarrier.test_wait.parity.shared::cta.b64 p, [%1], %2;\n"
        "selp.u32 %0, 1, 0, p;\n}\n"
        : "=r"(ok) : "r"(bar), "r"(parity) : "memory");
    return ok;
}
__device__ __forceinline__ void mbar_wait(uint32_t bar, uint32_t parity) {
#pragma unroll 1
    for (uint32_t n = 0; n < (1u << 14); n++)
        if (mbar_try(bar, parity)) break;
}
__device__ __forceinline__ void fence_proxy_async_smem() { asm volatile("fence.proxy.async.shared::cta;" ::: "memory"); }
__device__ __forceinline__ void fence_mbar_init() { asm volatile("fence.mbarrier_init.release.cluster;" ::: "memory"); }

__device__ __forceinline__ void bulk_g2s(uint32_t dst, const void* src, uint32_t bytes, uint32_t bar) {
    asm volatile("cp.async.bulk.shared::cluster.global.mbarrier::complete_tx::bytes [%0], [%1], %2, [%3];"
                 ::"r"(dst), "l"(src), "r"(bytes), "r"(bar) : "memory");
}
__device__ __forceinline__ void bulk_g2s_ef(uint32_t dst, const void* src, uint32_t bytes, uint32_t bar) {
    asm volatile("{\n.reg .b64 pol;\ncreatepolicy.fractional.L2::evict_first.b64 pol, 1.0;\n"
                 "cp.async.bulk.shared::cluster.global.mbarrier::complete_tx::bytes.L2::cache_hint [%0], [%1], %2, [%3], pol;\n}"
                 ::"r"(dst), "l"(src), "r"(bytes), "r"(bar) : "memory");
}
__device__ __forceinline__ void tma3d_ef(uint32_t dst, const CUtensorMap* tm, int c0, int c1, int c2, uint32_t bar) {
    asm volatile("{\n.reg .b64 pol;\ncreatepolicy.fractional.L2::evict_first.b64 pol, 1.0;\n"
                 "cp.async.bulk.tensor.3d.shared::cluster.global.mbarrier::complete_tx::bytes.L2::cache_hint [%0], [%1, {%3, %4, %5}], [%2], pol;\n}"
                 ::"r"(dst), "l"(tm), "r"(bar), "r"(c0), "r"(c1), "r"(c2) : "memory");
}
__device__ __forceinline__ void tma3d(uint32_t dst, const CUtensorMap* tm, int c0, int c1, int c2, uint32_t bar) {
    asm volatile("cp.async.bulk.tensor.3d.shared::cluster.global.mbarrier::complete_tx::bytes [%0], [%1, {%3, %4, %5}], [%2];"
                 ::"r"(dst), "l"(tm), "r"(bar), "r"(c0), "r"(c1), "r"(c2) : "memory");
}
__device__ __forceinline__ void poll_ge(const unsigned* p, unsigned target) {
#pragma unroll 1
    for (uint32_t n = 0; n < (1u << 15); n++) {
        unsigned v;
        asm volatile("ld.acquire.gpu.global.u32 %0, [%1];" : "=r"(v) : "l"(p) : "memory");
        if (v >= target) break;
        __nanosleep(32);
    }
}
__device__ __forceinline__ void red_relaxed(unsigned* p) { asm volatile("red.relaxed.gpu.global.add.u32 [%0], 1;" ::"l"(p) : "memory"); }
__device__ __forceinline__ void named_arrive(int id, int n) { asm volatile("bar.arrive %0, %1;" ::"r"(id), "r"(n) : "memory"); }
__device__ __forceinline__ void named_bar(int id, int n) { asm volatile("bar.sync %0, %1;" ::"r"(id), "r"(n) : "memory"); }

__device__ __forceinline__ void wg_fence() { asm volatile("wgmma.fence.sync.aligned;" ::: "memory"); }
__device__ __forceinline__ void wg_commit() { asm volatile("wgmma.commit_group.sync.aligned;" ::: "memory"); }
template <int N> __device__ __forceinline__ void wg_wait() { asm volatile("wgmma.wait_group.sync.aligned %0;" ::"n"(N) : "memory"); }
template <int N> __device__ __forceinline__ void reg_fence(float (&d)[N]) {
#pragma unroll
    for (int i = 0; i < N; i++) asm volatile("" : "+f"(d[i])::"memory");
}

#define F4(a, i) "+f"(a[i]), "+f"(a[i + 1]), "+f"(a[i + 2]), "+f"(a[i + 3])
#define F8(a, i) F4(a, i), F4(a, i + 4)
#define F16(a, i) F8(a, i), F8(a, i + 8)

constexpr uint32_t HI128 = 0x40000040u, HI64 = 0x80000020u;
__device__ __forceinline__ uint32_t desc_lo(uint32_t addr) { return (addr >> 4) | 0x10000u; }


#define R4(a, i) "+r"(a[i]), "+r"(a[i + 1]), "+r"(a[i + 2]), "+r"(a[i + 3])
#define R8(a, i) R4(a, i), R4(a, i + 4)
template <int N> __device__ __forceinline__ void reg_fence(uint32_t (&d)[N]) {
#pragma unroll
    for (int i = 0; i < N; i++) asm volatile("" : "+r"(d[i])::"memory");
}
__device__ __forceinline__ void tma2d(uint32_t dst, const CUtensorMap* tm, int c0, int c1, uint32_t bar) {
    asm volatile("cp.async.bulk.tensor.2d.shared::cluster.global.mbarrier::complete_tx::bytes [%0], [%1, {%3, %4}], [%2];"
                 ::"r"(dst), "l"(tm), "r"(bar), "r"(c0), "r"(c1) : "memory");
}
__device__ __forceinline__ void tma4d(uint32_t dst, const CUtensorMap* tm, int c0, int c1, int c2, int c3, uint32_t bar) {
    asm volatile("cp.async.bulk.tensor.4d.shared::cluster.global.mbarrier::complete_tx::bytes [%0], [%1, {%3, %4, %5, %6}], [%2];"
                 ::"r"(dst), "l"(tm), "r"(bar), "r"(c0), "r"(c1), "r"(c2), "r"(c3) : "memory");
}
__device__ __forceinline__ bool named_bar_or(int id, int n, bool v) {
    uint32_t r;
    asm volatile("{\n.reg .pred p, q;\nsetp.ne.u32 q, %3, 0;\nbar.red.or.pred p, %1, %2, q;\nselp.u32 %0, 1, 0, p;\n}"
                 : "=r"(r) : "r"(id), "r"(n), "r"((uint32_t)v) : "memory");
    return r;
}

template <uint32_t AHI, int ACC>
__device__ __forceinline__ void wgmma_n64_ss(float (&d)[32], uint32_t da, uint32_t db) {
    asm volatile(
        "{\n.reg .pred p;\n.reg .b64 da, db;\nsetp.ne.b32 p, %36, 0;\nmov.b64 da, {%32, %34};\nmov.b64 db, {%33, %35};\n"
        "wgmma.mma_async.sync.aligned.m64n64k16.f32.bf16.bf16 "
        "{%0,%1,%2,%3,%4,%5,%6,%7,%8,%9,%10,%11,%12,%13,%14,%15,%16,%17,%18,%19,%20,%21,%22,%23,%24,%25,%26,%27,%28,%29,%30,%31},"
        "da, db, p, 1, 1, 0, 1;\n}\n"
        : F16(d, 0), F16(d, 16)
        : "r"(da), "r"(db), "n"(AHI), "n"(HI128), "n"(ACC));
}


template <int ACC>
__device__ __forceinline__ void wgmma_n56_ss(float (&d)[28], uint32_t da, uint32_t db) {
    asm volatile(
        "{\n.reg .pred p;\n.reg .b64 da, db;\nsetp.ne.b32 p, %31, 0;\nmov.b64 da, {%28, %30};\nmov.b64 db, {%29, %30};\n"
        "wgmma.mma_async.sync.aligned.m64n56k16.f32.f16.f16 "
        "{%0,%1,%2,%3,%4,%5,%6,%7,%8,%9,%10,%11,%12,%13,%14,%15,%16,%17,%18,%19,%20,%21,%22,%23,%24,%25,%26,%27},"
        "da, db, p, 1, 1, 1, 0;\n}\n"
        : F16(d, 0), F8(d, 16), F4(d, 24)
        : "r"(da), "r"(db), "n"(HI128), "n"(ACC));
}

template <int SA>
__device__ __forceinline__ void wgmma_n160_h(uint32_t (&d)[40], uint32_t da, uint32_t db) {
    asm volatile(
        "{\n.reg .pred p;\n.reg .b64 da, db;\nsetp.eq.b32 p, 0, 0;\nmov.b64 da, {%40, %43};\nmov.b64 db, {%41, %43};\n"
        "wgmma.mma_async.sync.aligned.m64n160k16.f16.f16.f16 "
        "{%0,%1,%2,%3,%4,%5,%6,%7,%8,%9,%10,%11,%12,%13,%14,%15,%16,%17,%18,%19,%20,%21,%22,%23,%24,%25,%26,%27,"
        "%28,%29,%30,%31,%32,%33,%34,%35,%36,%37,%38,%39},"
        "da, db, p, %42, 1, 1, 0;\n}\n"
        : R8(d, 0), R8(d, 8), R8(d, 16), R8(d, 24), R8(d, 32)
        : "r"(da), "r"(db), "n"(SA), "n"(HI128));
}
template <int SA>
__device__ __forceinline__ void wgmma_n160_f(float (&d)[80], uint32_t da, uint32_t db) {
    asm volatile(
        "{\n.reg .pred p;\n.reg .b64 da, db;\nsetp.eq.b32 p, 0, 0;\nmov.b64 da, {%80, %83};\nmov.b64 db, {%81, %83};\n"
        "wgmma.mma_async.sync.aligned.m64n160k16.f32.bf16.bf16 "
        "{%0,%1,%2,%3,%4,%5,%6,%7,%8,%9,%10,%11,%12,%13,%14,%15,%16,%17,%18,%19,%20,%21,%22,%23,%24,%25,%26,%27,"
        "%28,%29,%30,%31,%32,%33,%34,%35,%36,%37,%38,%39,%40,%41,%42,%43,%44,%45,%46,%47,%48,%49,%50,%51,%52,%53,%54,%55,"
        "%56,%57,%58,%59,%60,%61,%62,%63,%64,%65,%66,%67,%68,%69,%70,%71,%72,%73,%74,%75,%76,%77,%78,%79},"
        "da, db, p, %82, 1, 1, 0;\n}\n"
        : F16(d, 0), F16(d, 16), F16(d, 32), F16(d, 48), F16(d, 64)
        : "r"(da), "r"(db), "n"(SA), "n"(HI128));
}

__device__ __forceinline__ uint32_t pack_f16(float lo, float hi) {
    uint32_t r;
    asm("cvt.rn.f16x2.f32 %0, %1, %2;" : "=r"(r) : "f"(hi), "f"(lo));
    return r;
}
__device__ __forceinline__ uint32_t mul_bf16x2(uint32_t a, uint32_t b) {
    uint32_t r;
    asm("mul.rn.bf16x2 %0, %1, %2;" : "=r"(r) : "r"(a), "r"(b));
    return r;
}
__device__ __forceinline__ void sts128(uint32_t p, uint32_t a, uint32_t b, uint32_t c, uint32_t d) {
    asm volatile("st.shared.v4.b32 [%0], {%1,%2,%3,%4};" ::"r"(p), "r"(a), "r"(b), "r"(c), "r"(d) : "memory");
}
__device__ __forceinline__ uint32_t pack_bf16(float lo, float hi) {
    uint32_t r;
    asm("cvt.rn.bf16x2.f32 %0, %1, %2;" : "=r"(r) : "f"(hi), "f"(lo));
    return r;
}
__device__ __forceinline__ void stg128(void* p, uint32_t a, uint32_t b, uint32_t c, uint32_t d) {
    asm volatile("st.global.v4.b32 [%0], {%1,%2,%3,%4};" ::"l"(p), "r"(a), "r"(b), "r"(c), "r"(d) : "memory");
}
__device__ __forceinline__ void stmatrix_x4_t(uint32_t addr, uint32_t a, uint32_t b, uint32_t c, uint32_t d) {
    asm volatile("stmatrix.sync.aligned.m8n8.x4.trans.shared.b16 [%0], {%1,%2,%3,%4};"
                 ::"r"(addr), "r"(a), "r"(b), "r"(c), "r"(d) : "memory");
}

constexpr uint32_t cos64(int k, bool half) {
    constexpr uint16_t q[17] = {0x3F80, 0x3F7F, 0x3F7B, 0x3F75, 0x3F6D, 0x3F62, 0x3F55, 0x3F46, 0x3F35, 0x3F22, 0x3F0E, 0x3EF1, 0x3EC4, 0x3E95, 0x3E48, 0x3DC9, 0x0000};
    constexpr uint16_t h[17] = {0x3C00, 0x3BF6, 0x3BD9, 0x3BA8, 0x3B64, 0x3B0E, 0x3AA7, 0x3A2F, 0x39A8, 0x3913, 0x3872, 0x378B, 0x361F, 0x34A5, 0x323E, 0x2E46, 0x0000};
    k &= 63;
    if (k > 32) k = 64 - k;
    const uint16_t* t = half ? h : q;
    return k <= 16 ? t[k] : (t[32 - k] | 0x8000u);
}
constexpr uint32_t fwd_coef(int s, int p, int t) { return (p && s == 0) ? cos64(32 * t, false) : cos64(s * t - 16 * p, false); }
constexpr uint32_t inv_coef(int l, int phi) {
    const int s = phi >> 1, p = phi & 1;
    if (l >= kMO) return 0;
    const uint32_t c = s == 0 ? cos64(32 * l * p, true) : cos64(s * l + 16 * p, true);
    return (c & 0x7FFF) ? c - ((s == 0 ? 6 : 5) << 10) : 0;
}
struct Tables {
    uint32_t fwd[2048];
    uint32_t inv[2048];
};
constexpr Tables make_tables() {
    Tables t = {};
    for (int i = 0; i < 2048; i++) {
        const int row = i >> 5, tt = 8 * (((i >> 2) & 7) ^ (row & 7)) + 2 * (i & 3), s = 8 * (row >> 4) + (row & 7), p = (row >> 3) & 1;
        t.fwd[i] = fwd_coef(s, p, tt) | (fwd_coef(s, p, tt + 1) << 16);
        t.inv[i] = inv_coef(row, tt) | (inv_coef(row, tt + 1) << 16);
    }
    return t;
}
__device__ __align__(128) const Tables g_tab = make_tables();

constexpr int NCTA = 128;
constexpr int NST = 4;
constexpr int HEND = 56;
constexpr int XB = kNT * 128;
constexpr int OFF_W1 = 0, OFF_X = OFF_W1 + NST * 8192, OFF_W0 = OFF_X + 4 * XB, OFF_RAW = OFF_W0 + NST * 8192;
constexpr int OFF_STG = OFF_RAW + 32768;
constexpr int OFF_U0 = OFF_W0, OFF_U1 = OFF_X, OFF_C1 = OFF_W1, OFF_DIR = OFF_W1 + 8192;
constexpr int OFF_F = OFF_RAW + 65536;
constexpr int OFF_G = OFF_F + 8192;
constexpr int OFF_C0 = OFF_G;
constexpr int OFF_BAR = OFF_G + 4096;
constexpr int B_FULL = 0, B_EMPTY = 8 * NST, B_TSEL = 16 * NST, B_PRE = B_TSEL + 8, B_SIG = B_PRE + 16 * V0, B_YS = B_SIG + 8 * 33,
              B_T2 = B_YS + 8 * 4, B_SUM = B_T2 + 8, B_GATE = B_SUM + 32, B_RDY = B_GATE + 8 * 32, B_PUB = B_RDY + 8 * 33, B_UNIT = B_PUB + 8,
              B_FTAB = B_UNIT + 8 * 20, B_C1 = B_FTAB + 8, B_NRM = B_C1 + 8, B_END = B_NRM + 32;
template <int O0, int O1>
__device__ __forceinline__ void bar_setup(uint32_t bars) {
#pragma unroll
    for (int o = O0; o < O1; o += 8)
        mbar_init(bars + o, o < B_EMPTY ? 2 : o < B_TSEL ? 8 : o == B_TSEL ? 2 : o < B_SIG ? 1 : o < B_YS - 8 ? 8 : o < B_GATE ? 4 : 1);
    fence_mbar_init();
    fence_proxy_async_smem();
}
constexpr int OFF_TS = OFF_BAR + B_END;
constexpr int OFF_PLAN = OFF_TS + 336;
constexpr int OFF_YT = OFF_PLAN + (V0 + 65) * 8;
constexpr int OFF_GB = (OFF_YT + 4 * kNT * 4 + 15) & ~15;
constexpr int MAIN_SMEM = OFF_GB + 2048;
static_assert(MAIN_SMEM <= 232448 && OFF_U0 + 10 * 8192 == OFF_STG + 16384, "shared memory");
constexpr int XPC = 2 * kNT;
constexpr unsigned PROBE_NEAR = 400;

__device__ __forceinline__ uint32_t raw_slot(uint32_t sbase, uint32_t v, int wg) { return sbase + OFF_RAW + ((v & 3) * 2 + wg) * 8192; }

__device__ __forceinline__ uint32_t pre_slot(uint32_t sbase, uint32_t v, int wg) {
    return v < 4 ? raw_slot(sbase, v, wg) : v < 8 ? sbase + OFF_X + (v - 4) * XB + wg * 8192 : sbase + (wg ? OFF_W1 : OFF_W0) + ((V0 + 3) % NST) * 8192;
}
constexpr int OFF_TMP = OFF_W1 + 8192;

template <bool DC, int I>
__device__ __forceinline__ void gemm_mma(uint32_t (&a0)[40], uint32_t (&a1)[40], uint32_t dx0, uint32_t dx1, uint32_t dw) {
    constexpr int ks = I >> 2;
    const uint32_t A0 = dw + ks * 128, A1 = A0 + 256, B0 = dx0 + ks * 2, B1 = dx1 + ks * 2;
    if ((I & 3) == 0) wgmma_n160_h<1>(a0, A0, B0);
    if ((I & 3) == 1) wgmma_n160_h<1>(a1, A1, DC ? B1 : B0);
    if ((I & 3) == 2 && !DC) wgmma_n160_h<1>(a0, A1, B1);
    if ((I & 3) == 3 && !DC) wgmma_n160_h<-1>(a1, A0, B1);
}

template <bool DC, int I0, int I1>
__device__ __forceinline__ void gemm_mmas(uint32_t (&a0)[40], uint32_t (&a1)[40], uint32_t dx0, uint32_t dx1, uint32_t dw) {
    if constexpr (I0 < I1) {
        gemm_mma<DC, I0>(a0, a1, dx0, dx1, dw);
        gemm_mmas<DC, I0 + 1, I1>(a0, a1, dx0, dx1, dw);
    }
}
static_assert(RX == 4 && RW == 10, "placement of the output spectra");
__device__ __forceinline__ uint32_t y_unit(uint32_t db, uint32_t tau, uint32_t b, uint32_t pmask) {
    const uint32_t n = (((db >> 1) & 2) + (db & 1)) * XPC + ((db >> 1) & 1) * kNT + tau, r = n / 3;
    return run_off(r + (r >= 192 && r < 278 ? (r < 214 ? 64 : -22) : 0), n % 3, b, pmask);
}
__device__ __forceinline__ int y_gate(int t) { return t ? 28 + t : 27; }
template <int R>
__device__ __forceinline__ void store_round(const uint32_t (&a0)[40], const uint32_t (&a1)[40], uint32_t stg, int t, int wg, uint8_t* sp,
                                            int slot, uint32_t ytab, int wsw) {
    const int w = t >> 5, lane = t & 31, m = lane >> 3, i8 = lane & 7;
    constexpr int N = R == 2 ? 4 : 8;
    named_bar(2 + wg, 128);
    const uint32_t addr = stg + i8 * 256 + (m >> 1) * 128 + (((2 * w + (m & 1)) ^ i8 ^ wsw) << 4);
#pragma unroll
    for (int j = 8 * R; j < 8 * R + N; j++) stmatrix_x4_t(addr + (j - 8 * R) * 2048, a0[2 * j], a0[2 * j + 1], a1[2 * j], a1[2 * j + 1]);
    named_bar(2 + wg, 128);
    const int row = 2 * w + (lane >> 4), phi = 2 * slot + (m & 1);
    const uint32_t src = stg + row * 256 + (m & 1) * 128 + ((i8 ^ row) << 4);
    uint8_t* dst = sp + phi * 128 + ((i8 ^ (phi & 7)) << 4);
    uint32_t v[N][4], o[N];
#pragma unroll
    for (int i = 0; i < N; i++) {
        asm volatile("ld.shared.u32 %0, [%1];" : "=r"(o[i]) : "r"(ytab + (64 * R + 8 * i + row) * 4) : "memory");
        asm volatile("ld.shared.v4.b32 {%0,%1,%2,%3}, [%4];" : "=r"(v[i][0]), "=r"(v[i][1]), "=r"(v[i][2]), "=r"(v[i][3])
                     : "r"(src + i * 2048) : "memory");
    }
#pragma unroll
    for (int i = 0; i < N; i++) stg128(dst + o[i], v[i][0], v[i][1], v[i][2], v[i][3]);
}

__device__ __forceinline__ int step_k(int h) { return h < HEND ? h >> 1 : 28 + (h & 3); }
__device__ __forceinline__ int step_m(int h) { return h < HEND ? h & 1 : (h >> 2) & 1; }
constexpr uint64_t x_mask() {
    uint64_t r = 2 | (3ull << 58);
    for (int v = 2; v < 58; v++)
        if ((0x6B >> (v & 7)) & 1) r |= 1ull << v;
    return r;
}
constexpr uint64_t XMASK = x_mask();
__device__ __forceinline__ int x_round(int v, int wg) {
    return v == 0 ? wg : (v < 60 && wg != (v & 1) && ((XMASK >> v) & 1)) ? 1 + __popcll(XMASK << (63 - v)) : -1;
}
__device__ __forceinline__ int w_step(int v, int wg) {
    return v == 0 ? -1 : v < 60 ? (wg == (v & 1) ? v - 1 : -1) : v < 62 ? 2 * v - 61 + wg : (v == 62 && wg == 0) ? 63 : -1;
}

__device__ __forceinline__ uint32_t plan_word(int v, int wg, int cta) {
    const int r = x_round(v, wg), h = w_step(v, wg);
    if (r < 0 && h < 0) return 0;
    const bool last = v >= 60 || (v & 1) || (v > 0 && wg == 0 && x_round(v + 1, 0) < 0);
    uint32_t off, row, gate;
    if (r >= 0) {
        const int u = r * NCTA + cta, cb = u / XPC, i = u - cb * XPC, b = i >= kNT, tau = i - b * kNT;
        row = tau & 63;
        off = (((cb % RX) * 64 + b) << 16) + ((tau >> 6) << 14) + b + 2;
        gate = cb >= RX ? 2 * (cb - RX) + 2 : 0;
    } else {
        const int ring = (h + RW - 64 % RW) % RW;
        row = 0;
        off = ((ring * 22) << 16) + (ring << 12) + 4;
        gate = h >= RW ? ((h - RW + 1) >> 1) + 1 : 0;
    }
    return (off + row * 128) | ((row & 7) << 4) | (last << 3) | ((v > 60) << 24) | (gate << 26);
}

struct Xf {
    uint32_t sbase;
    uint8_t *px, *pw;
    uint32_t cx, cw;
    uint32_t xsw;
    uint32_t dw;
    uint32_t e;
    int lane;
};
__device__ __forceinline__ uint32_t plan_load(const Xf& f, uint32_t v, int wg) {
    uint32_t e;
    asm volatile("ld.shared.u32 %0, [%1];" : "=r"(e) : "r"(f.sbase + OFF_PLAN + v * 8 + wg * 4));
    return __shfl_sync(0xffffffffu, e, 0);
}
template <bool W>
__device__ __forceinline__ void unit_mma(float (&acc)[32], const Xf& f, uint32_t raw) {
    const uint32_t dB = desc_lo(raw);
    if (W) {
        const uint32_t dG = desc_lo(f.sbase + OFF_G);
        wgmma_n64_ss<HI64, 0>(acc, dG, dB);
        wgmma_n64_ss<HI64, 1>(acc, dG + 2, dB + 128);
    } else {
        const uint32_t dF = desc_lo(f.sbase + OFF_F);
        wgmma_n64_ss<HI128, 0>(acc, dF, dB);
        wgmma_n64_ss<HI128, 1>(acc, dF + 2, dB + 128);
        wgmma_n64_ss<HI128, 1>(acc, dF + 4, dB + 256);
        wgmma_n64_ss<HI128, 1>(acc, dF + 6, dB + 384);
    }
    wg_commit();
}
constexpr int DROP = 3;
__device__ __forceinline__ uint32_t pack_sp(float lo, float hi) {
    const uint32_t r = pack_f16(lo, hi);
    return DROP ? (r + (0x10001u << DROP >> 1)) & ~(((1u << DROP) - 1) * 0x10001u) : r;
}
__device__ __forceinline__ void st_quad(uint8_t* p, const float (&acc)[32], int j0) {
    stg128(p, pack_sp(acc[j0], acc[j0 + 1]), pack_sp(acc[j0 + 4], acc[j0 + 5]), pack_sp(acc[j0 + 8], acc[j0 + 9]),
           pack_sp(acc[j0 + 12], acc[j0 + 13]));
}
template <bool W>
__device__ __forceinline__ void unit_store(float (&acc)[32], const Xf& f, uint32_t e) {
    const uint32_t sel = ((W ? f.cw >> (8 + ((e >> 12) & 15)) : e ^ (f.cx >> (8 + ((e >> 21) & 6)))) & 1) << 13;
    const uint32_t o = (e & (W ? 0xFF0F80u : 0xFFFF80u)) + ((e ^ (W ? f.cw : f.cx)) & 0x70);
    uint8_t* const b = W ? f.pw : f.px;
    uint8_t *p0 = b + (o + sel), *p1 = b + ((o ^ 64) + sel);
    reg_fence(acc);
    if (W) {
        st_quad(p0, acc, 0);
        st_quad(p1, acc, 16);
        st_quad(p0 + 4096, acc, 2);
        st_quad(p1 + 4096, acc, 18);
    } else {
        const int d = 131072 + 8192 - 2 * (int)sel;
        st_quad(p0, acc, 0);
        st_quad(p1, acc, 2);
        st_quad(p0 + d, acc, 16);
        st_quad(p1 + d, acc, 18);
    }
}
__device__ __forceinline__ void unit_done(const Xf& f, uint32_t e, uint32_t v) {
    if (e & 8) {
        __syncwarp();
        if (f.lane == 0) mbar_arrive(f.sbase + OFF_BAR + B_SIG + 8 * ((v >> 1) + ((e >> 24) & 1)));
    }
}
__device__ __forceinline__ void step_wait(Xf& f, uint32_t v, int wg) {
    const uint32_t bars = f.sbase + OFF_BAR;
    if (f.e >> 26) mbar_wait(bars + B_GATE - 8 + 8 * (f.e >> 26), 0);
    mbar_wait(bars + B_FULL + 8 * (v % NST), (v / NST) & 1);
}

template <bool DC, int KIND>
__device__ __forceinline__ void gemm_step(uint32_t (&a0)[40], uint32_t (&a1)[40], float (&at)[32], Xf& f, uint32_t v, uint32_t xs, int wg, bool first) {
    const uint32_t bars = f.sbase + OFF_BAR, sb = desc_lo(f.sbase), xb = sb + OFF_X / 16 + xs * (XB / 16), raw = raw_slot(f.sbase, v, wg);
    const uint32_t dx0 = xb + f.xsw, dx1 = xb + (f.xsw ^ 4), dw = f.dw + (v % NST) * 512, e = f.e;
    wg_fence();
    if (KIND) unit_mma<KIND != 1>(at, f, raw);
    constexpr int N1 = KIND == 0 ? 2 : NPRE;
    gemm_mmas<DC, 0, N1>(a0, a1, dx0, dx1, dw);
    wg_commit();
    f.e = plan_load(f, v + 1, wg);
    wg_wait<1>();
    if (!KIND && !first && f.lane == 0) mbar_arrive(bars + B_EMPTY + 8 * ((v - 1) % NST));
    if (KIND) unit_store<KIND != 1>(at, f, e);
    if (KIND) unit_done(f, e, v);
    gemm_mmas<DC, N1, 7>(a0, a1, dx0, dx1, dw);
    if (KIND && !first && f.lane == 0) mbar_arrive(bars + B_EMPTY + 8 * ((v - 1) % NST));
    gemm_mma<DC, 7>(a0, a1, dx0, dx1, dw);
    wg_commit();
}
template <bool DC>
__device__ __forceinline__ void any_step(uint32_t (&a0)[40], uint32_t (&a1)[40], float (&at)[32], Xf& f, uint32_t v, uint32_t xs, int wg, bool first) {
    step_wait(f, v, wg);
    const uint32_t kind = (f.e >> 1) & 3;
    if (kind == 1) gemm_step<DC, 1>(a0, a1, at, f, v, xs, wg, first);
    else if (kind == 2) gemm_step<DC, 2>(a0, a1, at, f, v, xs, wg, first);
    else gemm_step<DC, 0>(a0, a1, at, f, v, xs, wg, first);
}
template <bool DC>
__device__ __forceinline__ void gemm_main(uint32_t (&a0)[40], uint32_t (&a1)[40], uint32_t (&b0)[40], uint32_t (&b1)[40], Xf& f, int wg) {
    float at[32];
#pragma unroll 1
    for (uint32_t k = 0; k < HEND / 2; k++) {
        any_step<DC>(a0, a1, at, f, V0 + 2 * k, k & 3, wg, k == 0);
        any_step<DC>(b0, b1, at, f, V0 + 2 * k + 1, k & 3, wg, false);
    }
    wg_wait<0>();
    if (f.lane == 0) mbar_arrive(f.sbase + OFF_BAR + B_EMPTY + 8 * ((V0 + HEND - 1) % NST));
}
template <bool DC>
__device__ __forceinline__ void gemm_last(uint32_t (&a0)[40], uint32_t (&a1)[40], Xf& f, int wg, int m) {
    const uint32_t bars = f.sbase + OFF_BAR, sb = desc_lo(f.sbase);
    mbar_wait(bars + B_FULL + 8 * ((V0 + HEND) % NST), ((V0 + HEND) / NST + m) & 1);
    if (2 * m + wg > 0) named_bar(3 + 2 * m + wg, 256);
#pragma unroll 1
    for (uint32_t k = 0; k < 4; k++) {
        const uint32_t v = V0 + HEND + 4 * m + k, xb = sb + OFF_X / 16 + k * (XB / 16);
        wg_fence();
        gemm_mmas<DC, 0, 8>(a0, a1, xb + f.xsw, xb + (f.xsw ^ 4), f.dw + (v % NST) * 512);
        wg_commit();
        if (k == 3) break;
        mbar_wait(bars + B_FULL + 8 * ((v + 1) % NST), ((v + 1) / NST) & 1);
        wg_wait<1>();
        if (k && f.lane == 0) mbar_arrive(bars + B_EMPTY + 8 * ((v - 1) % NST));
    }
    if (2 * m + wg < 3) named_arrive(4 + 2 * m + wg, 256);
    wg_wait<1>();
    if (f.lane == 0) mbar_arrive(bars + B_EMPTY + 8 * ((V0 + HEND + 2) % NST));
    wg_wait<0>();
    if (f.lane == 0) {
        mbar_arrive(bars + B_EMPTY + 8 * ((V0 + HEND + 3) % NST));
        if (2 * m + wg == 2) mbar_arrive(bars + B_T2);
    }
}

__device__ __forceinline__ float gelu_half(float hv) {
    float th;
    asm("tanh.approx.f32 %0, %1;" : "=f"(th) : "f"(hv * fmaf(hv * hv, 8.0f * 0.7978845608028654f * 0.044715f, 2.0f * 0.7978845608028654f)));
    return fmaf(hv, th, hv);
}
__device__ __noinline__ void direct_block(const __nv_bfloat16* __restrict__ x, const __nv_bfloat16* __restrict__ w,
                                          const __nv_bfloat16* __restrict__ gamma, const __nv_bfloat16* __restrict__ beta,
                                          __nv_bfloat16* __restrict__ out, float* sm, int b, int db, int part, uint32_t epoch) {
    float *xs = sm, *ws = sm + 32 * 17, *red = ws + 16 * 65;
    const int tid = threadIdx.x & 127, bar = 2 + (threadIdx.x >> 7), tx = tid & 15, ty = tid >> 4, row0 = part * 250, lim = min(250, kL - row0);
    float* h = g_direct + (size_t)((b * 8 + db) * 32 + part) * (250 * 64);
    for (int l0 = 0; l0 < lim; l0 += 32) {
        float acc[4][4] = {};
        for (int k0 = 0; k0 < 31 * 512; k0 += 16) {
            named_bar(bar, 128);
            for (int i = tid; i < 1024; i += 128) {
                if (i < 512) xs[(i >> 4) * 17 + (i & 15)] = __bfloat162float(x[((size_t)b * kRows + row0 + min(l0 + (i >> 4), lim - 1)) * 1024 + k0 + (i & 15)]);
                ws[(i >> 6) * 65 + (i & 63)] = __bfloat162float(w[(size_t)(k0 + (i >> 6)) * 512 + 64 * db + (i & 63)]);
            }
            named_bar(bar, 128);
            for (int k = 0; k < 16; k++)
#pragma unroll
                for (int i = 0; i < 4; i++)
#pragma unroll
                    for (int j = 0; j < 4; j++) acc[i][j] = fmaf(xs[(ty * 4 + i) * 17 + k], ws[k * 65 + tx * 4 + j], acc[i][j]);
        }
#pragma unroll
        for (int i = 0; i < 4; i++)
#pragma unroll
            for (int j = 0; j < 4; j++)
                if (l0 + ty * 4 + i < lim) h[(l0 + ty * 4 + i) * 64 + tx * 4 + j] = acc[i][j];
    }
    const int c = tid & 63;
    float mean = 0.f, var = 0.f;
    for (int r = 0; r < 2; r++) {
        named_bar(bar, 128);
        float s = 0.f;
        for (int l = tid >> 6; l < lim; l += 2) {
            const float v = h[l * 64 + c] - mean;
            s += r ? v * v : v;
        }
        red[tid] = s;
        named_bar(bar, 128);
        unsigned long long* p = g_dpart + ((r * 16 + b * 8 + db) * 32) * 64 + c;
        if (tid < 64)
            asm volatile("st.relaxed.gpu.global.v2.b32 [%0], {%1, %2};" ::"l"(p + part * 64), "r"(__float_as_uint(red[c] + red[64 + c])), "r"(epoch) : "memory");
        s = 0.f;
        for (int k = 0; k < 32; k++) {
            unsigned long long v = 0;
#pragma unroll 1
            for (uint32_t n = 0; n < (1u << 19); n++) {
                asm volatile("ld.relaxed.gpu.global.u64 %0, [%1];" : "=l"(v) : "l"(p + k * 64) : "memory");
                if ((uint32_t)(v >> 32) == epoch) break;
                __nanosleep(200);
            }
            s += __uint_as_float((uint32_t)v);
        }
        (r ? var : mean) = s * (1.0f / kL);
    }
    const float a = __bfloat162float(gamma[64 * db + c]) / sqrtf(var + 1e-5f), be = __bfloat162float(beta[64 * db + c]);
    for (int l = tid >> 6; l < lim; l += 2)
        out[((size_t)b * kL + row0 + l) * 512 + 64 * db + c] = __float2bfloat16(gelu_half(0.5f * fmaf(h[l * 64 + c] - mean, a, be)));
    named_bar(bar, 128);
}

__device__ __forceinline__ int tail_block(uint32_t gr, int t) { return 4 * (t >> 1) + ((gr >> 4) & 2) + (t & 1); }
__device__ __forceinline__ void tail_poll(uint8_t* sp, uint32_t gr, int t) {
#pragma unroll 1
    for (uint32_t n = 0; n < (1u << 15); n++) {
        unsigned v;
        asm volatile("ld.relaxed.gpu.global.u32 %0, [%1];" : "=r"(v) : "l"(y_flag(sp, gr >> 6, tail_block(gr, t))) : "memory");
        if (v >= 32) break;
        __nanosleep(YSLEEP);
    }
    asm volatile("fence.acquire.gpu;" ::: "memory");
    asm volatile("fence.proxy.async.global;" ::: "memory");
}
__device__ __forceinline__ void tail_loads(uint32_t sbase, const uint8_t* sp, uint32_t gr, uint32_t pmask, int u0, int u1, int lane) {
    if (lane >= u0 && lane < u1) {
        const uint32_t bar = sbase + OFF_BAR + B_UNIT + 8 * lane;
        mbar_expect_tx(bar, 8192);
        bulk_g2s(sbase + (lane < 10 ? OFF_U0 : OFF_U1 - 81920) + lane * 8192, sp + y_unit(tail_block(gr, lane / 5), (gr & 31) * 5 + lane % 5, gr >> 6, pmask), 8192, bar);
    }
    __syncwarp();
}
__device__ __forceinline__ const float* corr_src(uint32_t gr, int t) { return &g_corr[(((gr >> 6) * 8 + tail_block(gr, t)) * kNT + (gr & 31) * 5) * 64]; }
__device__ __forceinline__ void corr_load(uint32_t sbase, uint32_t gr, int t, uint32_t bar) {
    bulk_g2s(sbase + (t < 2 ? OFF_C0 : OFF_C1) + (t & 1) * 1280, corr_src(gr, t), 1280, bar);
}
__device__ __forceinline__ void tail_phase(uint32_t sbase, uint8_t* smem, uint8_t* sp, int wg, uint32_t gr, float sx, float sw, const __nv_bfloat16* __restrict__ x,
                                           const __nv_bfloat16* __restrict__ wt, const __nv_bfloat16* __restrict__ gamma,
                                           const __nv_bfloat16* __restrict__ beta, __nv_bfloat16* __restrict__ out) {
    const uint32_t* ts = reinterpret_cast<const uint32_t*>(smem + OFF_TS);
    const int tid = threadIdx.x, w = (tid >> 5) & 3, lane = tid & 31, g = lane >> 2, q = lane & 3;
    const int b = gr >> 6, part = gr & 31;
#pragma unroll 1
    for (int rd = 0; rd < 4 - wg; rd++) {
        if (rd < 2) {
            float acc[28], acc2[28], s[8] = {0.f, 0.f, 0.f, 0.f, 0.f, 0.f, 0.f, 0.f};
            const float swq = q == 0 ? sw : 0.f;
            const uint32_t ub = sbase + (rd ? OFF_U1 : OFF_U0) + wg * 40960, ubar = sbase + OFF_BAR + B_UNIT + 80 * rd + 40 * wg;
            const float* c1 = reinterpret_cast<const float*>(smem + (rd ? OFF_C1 : OFF_C0) + wg * 1280) + 16 * w + g;
            const uint32_t ka = ub + (lane >> 4) * 1024 + (lane & 7) * 128 + (((2 * w + ((lane >> 3) & 1)) ^ (lane & 7)) << 4);
            auto inverse = [&](float (&d)[28], int u) {
                const uint32_t dA = desc_lo(ub + u * 8192), dB = desc_lo(sbase + OFF_F);
                wg_fence();
                wgmma_n56_ss<0>(d, dA, dB);
                wgmma_n56_ss<1>(d, dA + 128, dB + 2);
                wgmma_n56_ss<1>(d, dA + 256, dB + 4);
                wgmma_n56_ss<1>(d, dA + 384, dB + 6);
                wg_commit();
            };
            auto keep = [&](float (&d)[28], int u, int un) {
                const bool ok = mbar_try(ubar + 8 * un, 0);
                reg_fence(d);
                d[25] = fmaf(c1[u * 64] * sx, swq, d[25]);
                d[27] = fmaf(c1[u * 64 + 8] * sx, swq, d[27]);
                if (part == 31 && u == 4) {
                    if (q >= 2) d[16] = d[18] = 0.f;
                    if (q >= 1) d[17] = d[19] = 0.f;
#pragma unroll
                    for (int i = 20; i < 28; i++) d[i] = 0.f;
                }
                const uint32_t a = ka + u * 8192;
#pragma unroll
                for (int j = 0; j < 6; j += 2)
                    stmatrix_x4_t(a + j * 1024, pack_f16(d[4 * j], d[4 * j + 1]), pack_f16(d[4 * j + 2], d[4 * j + 3]),
                                  pack_f16(d[4 * j + 4], d[4 * j + 5]), pack_f16(d[4 * j + 6], d[4 * j + 7]));
                asm volatile("stmatrix.sync.aligned.m8n8.x2.trans.shared.b16 [%0], {%1,%2};"
                             ::"r"(a + 6 * 1024), "r"(pack_f16(d[24], d[25])), "r"(pack_f16(d[26], d[27])) : "memory");
#pragma unroll
                for (int i = 0; i < 28; i++) {
                    s[i & 3] += d[i];
                    s[4 + (i & 3)] = fmaf(d[i], d[i], s[4 + (i & 3)]);
                }
#pragma unroll
                for (int i = 0; i < 8; i++) asm volatile("" : "+f"(s[i]));
                if (!ok) mbar_wait(ubar + 8 * un, 0);
                wg_wait<0>();
            };
            if (rd) mbar_wait(sbase + OFF_BAR + B_C1, 0);
            mbar_wait(ubar, 0);
            inverse(acc, 0);
            mbar_wait(ubar + 8, 0);
            wg_wait<0>();
#pragma unroll 1
            for (int u = 0;; u += 2) {
                inverse(acc2, min(u + 1, 4));
                keep(acc, u, min(u + 2, 4));
                if (u == 4) break;
                inverse(acc, u + 2);
                keep(acc2, u + 1, min(u + 3, 4));
            }
#pragma unroll
            for (int i = 0; i < 8; i += 2) {
                s[i] += s[i + 1];
                s[i] += __shfl_xor_sync(0xffffffffu, s[i], 1);
                s[i] += __shfl_xor_sync(0xffffffffu, s[i], 2);
            }
            const float mine = q == 0 ? s[0] : q == 1 ? s[2] : q == 2 ? s[4] : s[6];
            asm volatile("red.relaxed.gpu.global.add.u64 [%0], %1;"
                         ::"l"(part_sums(sp, b, tail_block(gr, 2 * rd + wg), ts[76]) + 2 * (16 * w + 8 * (q & 1) + g) + (q >> 1)),
                         "l"(fabsf(mine) < 0x1p25f ? __float2ll_rn(mine * 0x1p21f) * 4096 + 1 : 65ll) : "memory");
            __syncwarp();
            if (lane == 0) mbar_arrive(sbase + OFF_BAR + B_SUM + 8 * (2 * rd + wg));
            if (rd == 0) continue;
        }
        const int t = rd == 3 ? 3 : 2 * rd - 2 + wg, db = tail_block(gr, t), i0 = rd == 3 ? FCUT : 0, i1 = rd == 2 && wg ? FCUT : 256;
#pragma unroll 1
        for (uint32_t n = 0; n < (1u << 20); n++)
            if (mbar_try(sbase + OFF_BAR + B_NRM + 8 * t, 0)) break;
        if (reinterpret_cast<const volatile uint32_t*>(ts)[77 + t]) {
            if (rd < 3) direct_block(x, wt, gamma, beta, out, reinterpret_cast<float*>(smem + OFF_DIR + wg * 8192), b, db, part, ts[76]);
            continue;
        }
        const int jh = g & 1, r0 = 4 * w;
        const int lim = min(250, kL - part * 250) - r0 - (g >> 1);
        float na[8], nb[8];
#pragma unroll
        for (int i = 0; i < 8; i += 2) {
            const float4 v = reinterpret_cast<const float4*>(smem + OFF_GB)[32 * t + 16 * jh + 2 * i + q];
            na[i] = v.x; nb[i] = v.y; na[i + 1] = v.z; nb[i + 1] = v.w;
        }
        __nv_bfloat16* o = out + ((size_t)b * kL + part * 250 + i0 + r0 + (g >> 1)) * 512 + 64 * db + 32 * jh + 8 * q;
        const int row = i0 + r0 + ((lane >> 1) & 3);
        int l = row % kMO;
        uint32_t ra = sbase + (t < 2 ? OFF_U0 : OFF_U1) + (t & 1) * 40960 + row / kMO * 8192 + l * 128;
        const int cc = 4 * (lane & 1) + (lane >> 3);
        auto fetch = [&](uint32_t (&r)[4]) {
            asm volatile("ldmatrix.sync.aligned.m8n8.x4.shared.b16 {%0,%1,%2,%3}, [%4];"
                         : "=r"(r[0]), "=r"(r[1]), "=r"(r[2]), "=r"(r[3]) : "r"(ra + (((cc ^ l) & 7) << 4)) : "memory");
            const bool wrap = l >= kMO - 16;
            l += wrap ? 16 - kMO : 16;
            ra += wrap ? 2048 + 8192 - kMO * 128 : 2048;
        };
        auto gelu8 = [&](const uint32_t (&r)[4], uint32_t (&p)[4]) {
#pragma unroll
            for (int i = 0; i < 4; i++) {
                float lo, hi;
                asm("{\n.reg .b16 a, b;\nmov.b32 {a, b}, %2;\ncvt.f32.f16 %0, a;\ncvt.f32.f16 %1, b;\n}" : "=f"(lo), "=f"(hi) : "r"(r[i]));
                p[i] = pack_bf16(gelu_half(fmaf(lo, na[2 * i], nb[2 * i])), gelu_half(fmaf(hi, na[2 * i + 1], nb[2 * i + 1])));
            }
        };
        uint32_t r[2][4], rn[2][4];
        fetch(r[0]);
        fetch(r[1]);
#pragma unroll 1
        for (int i = i0; i < i1; i += 32) {
            fetch(rn[0]);
            fetch(rn[1]);
            uint32_t p0[4], p1[4];
            gelu8(r[0], p0);
            gelu8(r[1], p1);
            if (i < lim) stg128(o, p0[0], p0[1], p0[2], p0[3]);
            if (i + 16 < lim) stg128(o + 16 * 512, p1[0], p1[1], p1[2], p1[3]);
            o += 32 * 512;
#pragma unroll
            for (int k = 0; k < 4; k++) { r[0][k] = rn[0][k]; r[1][k] = rn[1][k]; }
        }
    }
}
__device__ __forceinline__ void channel_scales(uint32_t sbase, uint8_t* smem, uint8_t* sp, int lane) {
    volatile uint32_t* ts = reinterpret_cast<volatile uint32_t*>(smem + OFF_TS);
    const uint32_t gr = ts[64], bars = sbase + OFF_BAR;
#pragma unroll 1
    for (int t = 0; t < 4; t++) {
#pragma unroll 1
        for (uint32_t n = 0; n < (1u << 20); n++)
            if (mbar_try(bars + B_SUM + 8 * t, 0)) break;
        long long s[4];
#pragma unroll 1
        for (uint32_t n = 0; n < (1u << 19); n++) {
            const unsigned long long* p = part_sums(sp, gr >> 6, tail_block(gr, t), ts[76]) + 4 * lane;
#pragma unroll
            for (int i = 0; i < 4; i++) asm volatile("ld.relaxed.gpu.global.u64 %0, [%1];" : "=l"(s[i]) : "l"(p + i) : "memory");
            if (__all_sync(0xffffffffu, s[0] & s[1] & s[2] & s[3] & 32)) break;
        }
        const float sx = __uint_as_float(ts[74]), sw = __uint_as_float(ts[75]);
        bool bad = false;
#pragma unroll
        for (int i = 0; i < 2; i++) {
            const float mean = (float)(s[2 * i] >> 12) * (0x1p-21f / kL), sq = (float)(s[2 * i + 1] >> 12) * (0x1p-21f / kL);
            float2* gb = reinterpret_cast<float2*>(smem + OFF_GB) + 64 * t + 2 * lane + i;
            const float den = fmaxf(sq - mean * mean, 0.f) + 1e-5f * sx * sw * sx * sw, a = gb->x * rsqrtf(den);
            *gb = make_float2(0.5f * a, 0.5f * (gb->y - mean * a));
            bad |= ((s[2 * i] | s[2 * i + 1]) & 0xFC0) || !(den >= 0x1p-22f);
        }
        bad = __any_sync(0xffffffffu, bad);
        if (lane == 0) ts[77 + t] = bad;
        __syncwarp();
        if (lane == 0) mbar_arrive(bars + B_NRM + 8 * t);
    }
}

__device__ __forceinline__ void publish_tiles(uint8_t* sp, uint32_t bars, int cta, int wg) {
#pragma unroll 1
    for (int m = 0; m < 2; m++) {
        mbar_wait(bars + B_YS + 8 * (2 * m + wg), 0);
        asm volatile("fence.acq_rel.gpu;" ::: "memory");
        red_relaxed(y_flag(sp, (cta >> 1) & 1, 4 * m + 2 * (cta & 1) + wg));
    }
}

__global__ void __launch_bounds__(384, 1)
main_kernel(const __grid_constant__ CUtensorMap tmx, const __grid_constant__ CUtensorMap tmw0, const __grid_constant__ CUtensorMap tmw1,
            const __nv_bfloat16* __restrict__ x, const __nv_bfloat16* __restrict__ wt, const __nv_bfloat16* __restrict__ gamma,
            const __nv_bfloat16* __restrict__ beta, __nv_bfloat16* __restrict__ out) {
    extern __shared__ __align__(1024) uint8_t smem_raw[];
    const uint32_t sbase = smem_u32(smem_raw) & ~1023u;
    const uint32_t bars = sbase + OFF_BAR;
    const int tid = threadIdx.x, wg = __shfl_sync(0xffffffffu, tid >> 7, 0), lane = tid & 31;
    const int cta = blockIdx.x;
    volatile uint32_t* ts = reinterpret_cast<volatile uint32_t*>(smem_raw + OFF_TS);
    uint8_t* const sp = reinterpret_cast<uint8_t*>((reinterpret_cast<uintptr_t>(g_sp) + (2u << 20) - 1) & ~(uintptr_t)((2u << 20) - 1));
    const bool probing = (cta & 3) == 0 && lane == 0 && tid < 128 && (tid >= 64 || cta < 4 * NPAGES);
    unsigned* pw = reinterpret_cast<unsigned*>(sp + (tid < 64 ? ((cta >> 2) << 21) + ((tid & 32) ? 15 : 13) * 4096
                                                              : ((tid & 32) ? 0 : 14) * 4096 + (cta >> 2) * 128));
    unsigned pv = 0;
    if (probing) {
        stg128(pw, 0, 0, 0, 0);
        stg128(pw + 4, 0, 0, 0, 0);
        asm volatile("atom.relaxed.gpu.global.exch.b32 %0, [%1], %2;" : "=r"(pv) : "l"(pw), "r"(7) : "memory");
    }
    if (tid == 320) bar_setup<0, B_SIG>(bars);
    if (tid >= 256 && tid < 262) ts[68 + tid - 256] = tid < 260 ? 0xffffu : 0;
    if (tid == 383) asm volatile("griddepcontrol.launch_dependents;");
    __syncthreads();

    if (wg == 2) {
        asm volatile("setmaxnreg.dec.sync.aligned.u32 40;");
        const int role = (tid >> 5) & 3;
        if (role == 3) {
            unsigned v = 0;
#pragma unroll 1
            for (uint32_t n = 0; n < (1u << 15); n++) {
                asm volatile("ld.relaxed.gpu.global.u32 %0, [%1];" : "=r"(v) : "l"(&g_tsel[lane]) : "memory");
                if (__all_sync(0xffffffffu, v & 16)) break;
                __nanosleep(TSLEEP);
            }
            const uint32_t m1 = __ballot_sync(0xffffffffu, v & 8), below = (1u << lane) - 1;
            const int rank = (v & 8) ? 32 - __popc(m1) + __popc(m1 & below) : __popc(~m1 & below);
            ts[lane] = rank;
            ts[32 + rank] = lane;
            const uint32_t p0 = __ballot_sync(0xffffffffu, v & 1);
            if (lane == 0) ts[66] = p0;
            if (lane == (cta >> 2)) ts[64] = rank * 4 + (cta & 3);
            const int part = (m1 >> (cta >> 2)) & 1;
            __syncwarp();
            if (lane == 0) { mbar_arrive(bars + B_TSEL); }
            mbar_wait(bars + B_TSEL, 0);
            mbar_wait(bars + B_PUB, 0);
            int gc = 0;
            const int gend = lane == 0 ? 33 : lane == 1 ? 32 : 0;
#pragma unroll 1
            for (uint32_t n = 0; n < (1u << 16) && __any_sync(0xffffffffu, gc < gend); n++) {
                asm volatile("ld.relaxed.gpu.global.u32 %0, [%1];" : "=r"(v) : "l"(chunk_flag(sp, lane == 1, part, min(gc, 32 - (lane & 1)))) : "memory");
                if (gc < gend && v >= NCTA) {
                    asm volatile("fence.acquire.gpu;" ::: "memory");
                    mbar_arrive(bars + (lane == 0 ? B_RDY : B_GATE) + 8 * gc);
                    gc++;
                }
            }
            if (lane == 0) publish_tiles(sp, bars, cta, 1);
        } else if (role == 0) {
            const int b = (cta >> 1) & 1, dq = cta & 1;
            for (int v = 0; v < V0; v++) {
                mbar_wait(bars + B_EMPTY + 8 * (v % NST), ((v / NST) & 1) ^ 1);
                if (lane == 0) {
                    mbar_arrive(bars + B_FULL + 8 * (v % NST));
                    mbar_arrive(bars + B_FULL + 8 * (v % NST));
                }
            }
            mbar_wait(bars + B_TSEL, 0);
            const uint32_t gr = ts[64], grp = gr >> 6, idx = (gr >> 2) & 15, pmask = ts[66];
            const uint32_t n0 = idx * 4 + 2 * dq + ((lane & 1) ^ 1), r0 = lane < 3 ? idx * 4 + b : R_W + n0 / 3;
            const uint32_t base = (r0 << 16) + 4096 + ((lane < 3 ? lane : n0 % 3) << 14), step = (lane < 3 ? 64 : 22) << 16;
            uint32_t sels = 0;
            for (int i = 0; i < 12; i++) sels |= run_sel(r0 + i * (step >> 16), grp, pmask) << i;
            int ld = 0;
            const uint32_t bytes = lane == 2 ? XB - 16384 : 8192;
#pragma unroll 1
            for (int h = 0; h < 64; h++) {
                const int s = step_k(h), st = (h + V0) % NST;
                const bool newx = h < HEND ? !(h & 1) : h < HEND + 4;
                const uint32_t fb = bars + B_FULL + 8 * st;
                const uint32_t k = lane < 3 ? (s >> 1) % RX : (h + RW - 64 % RW) % RW, half = lane < 3 ? s & 1 : 0;
                const uint8_t* gsrc = sp + (base + k * step + (half << 17) + ((((sels >> k) ^ half) & 1) << 13));
                const uint32_t dst = sbase + (lane < 3 ? OFF_X + (s & 3) * XB + lane * 8192 : st * 8192 + (lane == 3 ? OFF_W0 : OFF_W1));
                auto landed = [&]() {
                    if (ld < h && mbar_test(bars + B_FULL + 8 * ((ld + V0) % NST), ((ld + V0) / NST) & 1)) {
                        if (!(ld & 1) && lane < 2) red_relaxed(chunk_flag(sp, 1, lane, ld >> 1));
                        ld++;
                    }
                };
                if ((h & 1) || h == 0) {
#pragma unroll 1
                    for (uint32_t n = 0; n < (1u << 19) && !mbar_test(bars + B_RDY + 8 * ((h + 1) >> 1), 0); n++) landed();
                    asm volatile("fence.proxy.async.global;" ::: "memory");
                }
#pragma unroll 1
                for (uint32_t n = 0; n < (1u << 19) && !mbar_test(bars + B_EMPTY + 8 * st, (((h + V0) / NST) & 1) ^ 1); n++) landed();
#pragma unroll 1
                for (uint32_t n = 0; n < (1u << 19) && ld <= h - NST; n++) landed();
                if (lane == 0) mbar_expect_tx(fb, newx ? 16384 + XB : 16384);
                __syncwarp();
                if (lane < 3 ? newx : lane < 5) bulk_g2s(dst, gsrc, bytes, fb);
            }
#pragma unroll 1
            for (; ld < 63; ld++) {
                mbar_wait(bars + B_FULL + 8 * ((ld + V0) % NST), ((ld + V0) / NST) & 1);
                if (!(ld & 1) && lane < 2) red_relaxed(chunk_flag(sp, 1, lane, ld >> 1));
            }
            tail_poll(sp, gr, 0);
            mbar_wait(bars + B_T2, 0);
            tail_loads(sbase, sp, gr, pmask, 0, 5, lane);
            tail_poll(sp, gr, 1);
            tail_loads(sbase, sp, gr, pmask, 5, 8, lane);
            mbar_wait(bars + B_YS + 16, 0);
            tail_loads(sbase, sp, gr, pmask, 8, 10, lane);
            for (int v = V0 + 64; v < V0 + 64 + NST; v++) mbar_wait(bars + B_EMPTY + 8 * (v % NST), ((v / NST) & 1) ^ 1);
            if (lane == 0) {
                mbar_expect_tx(bars + B_C1, 2560);
                corr_load(sbase, gr, 2, bars + B_C1);
                corr_load(sbase, gr, 3, bars + B_C1);
            }
            tail_poll(sp, gr, 2);
            tail_loads(sbase, sp, gr, pmask, 10, 15, lane);
            tail_poll(sp, gr, 3);
            tail_loads(sbase, sp, gr, pmask, 15, 20, lane);
            mbar_wait(bars + B_GATE + 8 * 31, 0);
            unsigned exits = 0;
            if (lane == 0) exits = atomicAdd(&g_exit, 1);
            if (__shfl_sync(0xffffffffu, exits, 0) == NCTA - 1) {
                for (int i = 0; i < 4; i++) *chunk_flag(sp, i >> 1, i & 1, lane) = 0;
                if (lane < 2) *chunk_flag(sp, 0, lane, 32) = 0;
                g_tsel[lane] = 0;
                if (lane < 16) *y_flag(sp, lane >> 3, lane & 7) = 0;
                if (lane == 0) { g_exit = 0; g_epoch = ts[76]; }
            }
        } else if (role == 1) {
            auto raw_load = [&](int r, int h, uint32_t gr, uint32_t dst, uint32_t bar) {
                if (r >= 0) {
                    const int u = r * NCTA + cta, i = u % XPC, b = i >= kNT;
                    tma3d(dst, &tmx, u / XPC * 64, (i - b * kNT) * kMO, b, bar);
                } else if (h >= 0) {
                    const int c = 32 * step_k(h) + ((gr >> 1) & 30);
                    tma3d_ef(dst, c < 512 ? &tmw0 : &tmw1, step_m(h) * 256 + (gr & 3) * 64, 0, c & 511, bar);
                }
            };
            uint32_t gr;
            {
                const int v = lane >> 1, r = v < V0 ? x_round(v, lane & 1) : -1, h = v < V0 ? w_step(v, lane & 1) : -1;
                const uint32_t dst = pre_slot(sbase, v, lane & 1), bar = bars + B_PRE + 8 * lane;
                if (r >= 0 || h >= 0) mbar_expect_tx(bar, r >= 0 ? 8192 : 4096);
                if (v < PRE1) raw_load(r, -1, 0, dst, bar);
                mbar_wait(bars + B_TSEL, 0);
                gr = ts[64];
                raw_load(-1, h, gr, dst, bar);
                if (v >= PRE1) raw_load(r, -1, 0, dst, bar);
                __syncwarp();
            }
            mbar_wait(bars + B_PUB, 0);
#pragma unroll 1
            for (int v = V0; v < V0 + 64; v++) {
                mbar_wait(bars + B_EMPTY + 8 * (v % NST), ((v / NST) & 1) ^ 1);
                __syncwarp();
                const int r = lane < 2 ? x_round(v, lane) : -1, h = lane < 2 ? w_step(v, lane) : -1;
                const uint32_t fb = bars + B_FULL + 8 * (v % NST);
                const uint32_t bytes = __reduce_add_sync(0xffffffffu, r >= 0 ? 8192 : h >= 0 ? 4096 : 0);
                if (lane == 0) mbar_expect_tx(fb, bytes);
                __syncwarp();
                raw_load(r, h, gr, raw_slot(sbase, v, lane), fb);
                if (v >= 20 && v < 40) {
                    const int t = (v - 20) / 5, i = (v - 20) % 5 * 32 + lane, db = 4 * (t >> 1) + 2 * (cta & 1) + (t & 1);
                    ts[(OFF_YT - OFF_TS) / 4 + t * kNT + i] = y_unit(db, i, (cta >> 1) & 1, ts[66]);
                }
                if (v == 66 && lane == 0) {
#pragma unroll 1
                    for (uint32_t n = 0; n < (1u << 15); n++) {
                        unsigned c0, c1;
                        asm volatile("ld.relaxed.gpu.global.u32 %0, [%1];" : "=r"(c0) : "l"(&g_cready[(gr >> 6) * 64]) : "memory");
                        asm volatile("ld.relaxed.gpu.global.u32 %0, [%1];" : "=r"(c1) : "l"(&g_cready[(gr >> 6) * 64 + 32]) : "memory");
                        if (c0 == ts[76] && c1 == ts[76]) break;
                        __nanosleep(500);
                    }
                    asm volatile("fence.acquire.gpu;" ::: "memory");
                    asm volatile("fence.proxy.async.global;" ::: "memory");
                    mbar_expect_tx(bars + B_FTAB, 8192 + 2560);
                    bulk_g2s(sbase + OFF_F, g_tab.inv, 8192, bars + B_FTAB);
                    for (int t = 0; t < 2; t++) {
                        corr_load(sbase, gr, t, bars + B_FTAB);
                        asm volatile("cp.async.bulk.prefetch.L2.global [%0], 1280;" ::"l"(corr_src(gr, 2 + t)) : "memory");
                    }
                }
            }
            channel_scales(sbase, smem_raw, sp, lane);
        } else {
            uint32_t epoch;
            if (lane == 0) {
                bar_setup<B_SIG, B_END>(bars);
                mbar_arrive(bars + B_TSEL);
            }
            asm volatile("ld.relaxed.gpu.global.u32 %0, [%1];" : "=r"(epoch) : "l"(&g_epoch) : "memory");
            mbar_wait(bars + B_TSEL, 0);
            const uint32_t gr = ts[64];
#pragma unroll
            for (int i = lane; i < 256; i += 32) {
                const int d = 64 * tail_block(gr, i >> 6) + (i & 33) + 8 * ((i >> 1) & 3) + 2 * ((i >> 3) & 3);
                ts[(OFF_GB - OFF_TS) / 4 + 2 * i] = (uint32_t)__bfloat16_as_ushort(gamma[d]) << 16;
                ts[(OFF_GB - OFF_TS) / 4 + 2 * i + 1] = (uint32_t)__bfloat16_as_ushort(beta[d]) << 16;
            }
            if (lane == 0) ts[76] = epoch + 1;
            if (cta < 32) stg128(part_sums(sp, cta >> 4, (cta >> 1) & 7, epoch) + (cta & 1) * 64 + 2 * lane, 0, 0, 0, 0);
            __syncwarp();
            if (lane) return;
#pragma unroll 1
            for (int gc = 0; gc < 33;) {
                mbar_wait(bars + B_SIG + 8 * gc, 0);
                if (gc < MERGE) mbar_wait(bars + B_SIG + 8 * MERGE, 0);
                int ge = gc + 1;
                while (ge < 33 && mbar_test(bars + B_SIG + 8 * ge, 0)) ge++;
                asm volatile("fence.acq_rel.gpu;" ::: "memory");
                for (; gc < ge; gc++) {
                    red_relaxed(chunk_flag(sp, 0, 0, gc));
                    red_relaxed(chunk_flag(sp, 0, 1, gc));
                    if (gc == 0) mbar_arrive(bars + B_PUB);
                }
            }
            publish_tiles(sp, bars, cta, 0);
        }
    } else {
        asm volatile("setmaxnreg.inc.sync.aligned.u32 232;");
        uint4 fw[2];
#pragma unroll
        for (int j = 0; j < 2; j++) fw[j] = __ldg(reinterpret_cast<const uint4*>(g_tab.fwd) + tid + 256 * j);
        if (wg == 1) {
            uint4 sm[8];
#pragma unroll
            for (int j = 0; j < 4; j++) {
                const int r = 2 * j + ((tid >> 6) & 1);
                sm[j] = __ldg(reinterpret_cast<const uint4*>(x) + ((r >> 2) * kRows + 1000 + 2000 * (r & 3)) * 128 + (((j + r) & 1) << 6) + (tid & 63));
                sm[4 + j] = __ldg(reinterpret_cast<const uint4*>(wt) + (4 * r * 512 + 67 * r + 7) * 64 + (tid & 63));
            }
#pragma unroll
            for (int k = 0; k < 2; k++) {
                uint32_t mx = 0;
#pragma unroll
                for (int j = 4 * k; j < 4 * k + 4; j++)
                    mx = __vmaxu2(__vmaxu2(mx, __vmaxu2(sm[j].x & 0x7FFF7FFFu, sm[j].y & 0x7FFF7FFFu)), __vmaxu2(sm[j].z & 0x7FFF7FFFu, sm[j].w & 0x7FFF7FFFu));
                mx = __reduce_max_sync(0xffffffffu, max(mx & 0xFFFFu, mx >> 16));
                if (lane == 0) atomicMax(const_cast<uint32_t*>(ts) + 72 + k, mx);
            }
        }
        if ((cta & 3) == 0) {
            if (probing) {
                const int w = tid >> 5;
                unsigned best = 0xffffu;
#pragma unroll 1
                for (int r = 0; r < 6; r++) {
                    unsigned t0, t1;
                    asm volatile("{\n.reg .pred p;\nsetp.eq.u32 p, %1, 0xffffffff;\nmov.u32 %0, 0;\n@!p mov.u32 %0, %%clock;\n}"
                                 : "=r"(t0) : "r"(pv) : "memory");
                    asm volatile("atom.relaxed.gpu.global.exch.b32 %0, [%1], %2;" : "=r"(pv) : "l"(pw), "r"(r) : "memory");
                    asm volatile("{\n.reg .pred p;\nsetp.eq.u32 p, %1, 0xffffffff;\nmov.u32 %0, 0;\n@!p mov.u32 %0, %%clock;\n}"
                                 : "=r"(t1) : "r"(pv) : "memory");
                    ts[68 + w] = best = min(best, t1 - t0);
                    const unsigned other = ts[68 + (w ^ 1)];
                    if (min(best, other) < PROBE_NEAR && max(best, other) > PROBE_NEAR) break;
                }
            }
            if (wg == 0) {
                named_bar(2, 128);
                if (tid == 0) {
                    const uint32_t part = ts[71] < ts[70];
                    const uint32_t v = 16 | (part << 3) | ((ts[69] < ts[68]) ^ part);
                    asm volatile("st.relaxed.gpu.global.u32 [%0], %1;" ::"l"(&g_tsel[cta >> 2]), "r"(v) : "memory");
                }
            }
        }
        uint32_t plan = tid < 2 * (V0 + 65) ? plan_word(tid >> 1, tid & 1, cta) : 0;
        {
            named_bar(1, 256);
            const uint32_t ex = max(251 - (int)(ts[72] >> 7), 8), ew = max(251 - (int)(ts[73] >> 7), 8);
            if (tid == 0) { ts[74] = ex << 23; ts[75] = ew << 23; }
            const uint32_t sx = ex * 0x800080u, sw = ew * 0x800080u;
#pragma unroll
            for (int j = 0; j < 2; j++) {
                const int i = tid + 256 * j, row = i >> 3, c = (i ^ row) & 7;
                sts128(sbase + OFF_F + 16 * i, mul_bf16x2(fw[j].x, sx), mul_bf16x2(fw[j].y, sx), mul_bf16x2(fw[j].z, sx), mul_bf16x2(fw[j].w, sx));
                if (c < 2) sts128(sbase + OFF_TMP + row * 32 + c * 16, mul_bf16x2(fw[j].x, sw), mul_bf16x2(fw[j].y, sw), mul_bf16x2(fw[j].z, sw), mul_bf16x2(fw[j].w, sw));
            }
            named_bar(1, 256);
        }
        const int t = tid & 127;
        Xf f;
        f.sbase = sbase; f.lane = lane; f.xsw = cta & 4; f.dw = desc_lo(sbase + (wg ? OFF_W1 : OFF_W0));
        {
            const int w = t >> 5;
            const uint32_t nw = (8 * (w & 1) + (lane >> 2)) * 4 + (cta & 3), rw = R_W + nw / 3;
            f.pw = sp + (rw << 16) + 4096 + ((nw % 3) << 14) + (w >> 1) * 128;
            f.cw = ((lane & 7) ^ (w >> 1)) << 4;
            for (int i = 0; i < RW; i++) f.cw |= run_sel(rw + i * 22, 0, 0) << (8 + i);
            mbar_wait(bars + B_TSEL, 0);
            const uint32_t gr = ts[64], pmask = ts[66];
            const uint32_t rx = ts[8 * w + (lane >> 2)];
            f.px = sp + ((rx & 15) << 18) + 4096;
            f.cx = ((lane & 7) << 4) | ((((pmask >> ((rx >> 3) & 1)) ^ -(((rx >> 1) ^ (rx >> 4)) & 1)) & 0x55) << 8);
#pragma unroll
            for (int i = 0; i < RW; i++) f.cw ^= (((pmask >> ((rw + i * 22) >> 5)) ^ (gr >> 6)) & 1) << (8 + i);
            if (plan & 4) plan |= ((gr & 12) << 8) | ((gr & 48) << 4) | ((gr & 48) << 1);
            if (tid < 2 * (V0 + 65)) ts[(OFF_PLAN - OFF_TS) / 4 + tid] = plan;
            const int row = tid >> 2, ch = tid & 3, s = ts[32 + (gr >> 6) * 16 + ((row >> 1) & 8) + (row & 7)], p = (row >> 3) & 1;
            const int frow = 16 * (s >> 3) + 8 * p + (s & 7);
            uint32_t v[4] = {0, 0, 0, 0};
            if ((ch >> 1) == (row >> 5))
                asm volatile("ld.shared.v4.b32 {%0,%1,%2,%3}, [%4];" : "=r"(v[0]), "=r"(v[1]), "=r"(v[2]), "=r"(v[3])
                             : "r"(sbase + OFF_TMP + frow * 32 + (ch & 1) * 16) : "memory");
            sts128(sbase + OFF_G + row * 64 + ((ch ^ ((row >> 1) & 3)) << 4), v[0], v[1], v[2], v[3]);
            fence_proxy_async_smem();
            named_bar(1, 256);
        }
        {
            float at[32];
#pragma unroll 1
            for (uint32_t v = 0; v < V0; v++) {
                const uint32_t e = plan_load(f, v, wg), raw = pre_slot(sbase, v, wg);
                mbar_wait(bars + B_FULL + 8 * (v % NST), (v / NST) & 1);
                if (e & 6) mbar_wait(bars + B_PRE + 16 * v + 8 * wg, 0);
                wg_fence();
                if ((e & 6) == 2) {
                    unit_mma<false>(at, f, raw);
                    wg_wait<0>();
                    unit_store<false>(at, f, e);
                } else if (e & 4) {
                    unit_mma<true>(at, f, raw);
                    wg_wait<0>();
                    unit_store<true>(at, f, e);
                }
                if (lane == 0) mbar_arrive(bars + B_EMPTY + 8 * (v % NST));
                unit_done(f, e, v);
            }
        }
        const int slot = cta >> 2;
        f.e = plan_load(f, V0, wg);
        uint32_t a0[40], a1[40], b0[40], b1[40];
#pragma unroll
        for (int i = 0; i < 40; i++) a0[i] = a1[i] = b0[i] = b1[i] = 0;
        if (slot == 0) gemm_main<true>(a0, a1, b0, b1, f, wg);
        else gemm_main<false>(a0, a1, b0, b1, f, wg);
        const uint32_t gr = __shfl_sync(0xffffffffu, ts[64], 0);
        const float sx = __uint_as_float(ts[74]), sw = __uint_as_float(ts[75]);
#pragma unroll 1
        for (int m = 0; m < 2; m++) {
            if (slot == 0) gemm_last<true>(a0, a1, f, wg, m);
            else gemm_last<false>(a0, a1, f, wg, m);
            reg_fence(a0);
            reg_fence(a1);
            const int wsw = gr & 4;
            mbar_wait(bars + B_GATE + 8 * y_gate(2 * m + wg), 0);
            if (m) mbar_wait(bars + B_FTAB, 0);
            const uint32_t ytab = sbase + OFF_YT + (m * 2 + wg) * (kNT * 4);
            store_round<0>(a0, a1, sbase + OFF_STG + wg * 16384, t, wg, sp, slot, ytab, wsw);
            store_round<1>(a0, a1, sbase + OFF_STG + wg * 16384, t, wg, sp, slot, ytab, wsw);
            store_round<2>(a0, a1, sbase + OFF_STG + wg * 16384, t, wg, sp, slot, ytab, wsw);
            __syncwarp();
            if (lane == 0) mbar_arrive(bars + B_YS + 8 * (2 * m + wg));
            if (m) break;
#pragma unroll
            for (int i = 0; i < 40; i++) { a0[i] = b0[i]; a1[i] = b1[i]; }
        }
        tail_phase(sbase, smem_raw, sp, wg, gr, sx, sw, x, wt, gamma, beta, out);
    }
}

constexpr int C_STAGE = 32768 + 2 * XB, C_SMEM = 3 * C_STAGE + 64;
__global__ void __launch_bounds__(256, 1) corr_kernel(const __grid_constant__ CUtensorMap tmx, const __grid_constant__ CUtensorMap tmw) {
    extern __shared__ __align__(1024) uint8_t smem_raw[];
    const uint32_t sbase = smem_u32(smem_raw) & ~1023u, bars = sbase + 3 * C_STAGE;
    const int tid = threadIdx.x, wg = __shfl_sync(0xffffffffu, tid >> 7, 0), b = blockIdx.x >> 1, dh = blockIdx.x & 1;
    auto load = [&](int k) {
        const uint32_t st = sbase + (k % 3) * C_STAGE, bar = bars + 8 * (k % 3);
        mbar_expect_tx(bar, C_STAGE);
        for (int i = 0; i < 4; i++) tma2d(st + i * 8192, &tmw, 256 * dh + 64 * i, 64 * k, bar);
        tma4d(st + 32768, &tmx, 64 * k, 64 - kMO, 1, b, bar);
        tma4d(st + 32768 + XB, &tmx, 64 * k, 0, 0, b, bar);
    };
    uint32_t epoch = 0;
    if (tid == 0) {
        for (int i = 0; i < 3; i++) mbar_init(bars + 8 * i, 1);
        fence_mbar_init();
        fence_proxy_async_smem();
        for (int k = 0; k < 3; k++) load(k);
        asm volatile("ld.relaxed.gpu.global.u32 %0, [%1];" : "=r"(epoch) : "l"(&g_epoch) : "memory");
    }
    __syncthreads();
    float a[2][80];
#pragma unroll
    for (int i = 0; i < 80; i++) a[0][i] = a[1][i] = 0.f;
#pragma unroll 1
    for (int k = 0; k < 8; k++) {
        const uint32_t dA = desc_lo(sbase + (k % 3) * C_STAGE + wg * 16384), dB = desc_lo(sbase + (k % 3) * C_STAGE + 32768);
        mbar_wait(bars + 8 * (k % 3), (k / 3) & 1);
        wg_fence();
#pragma unroll
        for (int i = 0; i < 8; i++) {
            wgmma_n160_f<1>(a[i & 1], dA + (i & 1) * 512 + (i >> 1) * 128, dB + (i >> 1) * 2);
            wgmma_n160_f<-1>(a[i & 1], dA + (i & 1) * 512 + (i >> 1) * 128, dB + XB / 16 + (i >> 1) * 2);
        }
        wg_commit();
        wg_wait<0>();
        __syncthreads();
        if (tid == 0 && k + 3 < 8) load(k + 3);
    }
    reg_fence(a[0]);
    reg_fence(a[1]);
    const int w = (tid >> 5) & 3, g = (tid & 31) >> 2, q = tid & 3;
#pragma unroll
    for (int i = 0; i < 160; i++) {
        const int m = i / 80, j = i % 80, d = 16 * w + 8 * ((j >> 1) & 1) + g;
        g_corr[((b * 8 + 4 * dh + 2 * wg + m) * kNT + 8 * (j >> 2) + 2 * q + (j & 1)) * 64 + (d & 33) + 8 * ((d >> 1) & 3) + 2 * ((d >> 3) & 3)] = a[m][j];
    }
    __syncthreads();
    if (tid == 0) {
        asm volatile("fence.acq_rel.gpu;" ::: "memory");
        asm volatile("st.relaxed.gpu.global.u32 [%0], %1;" ::"l"(&g_cready[blockIdx.x * 32]), "r"(epoch + 1) : "memory");
    }
}

__global__ void __launch_bounds__(256) plain_conv(const __nv_bfloat16* __restrict__ x, const __nv_bfloat16* __restrict__ w) {
    __shared__ float xs[64][17], ws[16][65];
    float* h = g_direct;
    const int b = blockIdx.z, l0 = blockIdx.x * 64, d0 = blockIdx.y * 64, tx = threadIdx.x & 15, ty = threadIdx.x >> 4;
    float acc[4][4] = {};
    for (int k0 = 0; k0 < 31 * 512; k0 += 16) {
        for (int i = threadIdx.x; i < 1024; i += 256) {
            const int l = min(l0 + (i >> 4), kL - 1);
            xs[i >> 4][i & 15] = __bfloat162float(x[((size_t)b * kRows + l) * 1024 + k0 + (i & 15)]);
            ws[i >> 6][i & 63] = __bfloat162float(w[(size_t)(k0 + (i >> 6)) * 512 + d0 + (i & 63)]);
        }
        __syncthreads();
        for (int k = 0; k < 16; k++)
            for (int i = 0; i < 4; i++)
                for (int j = 0; j < 4; j++) acc[i][j] = fmaf(xs[ty * 4 + i][k], ws[k][tx * 4 + j], acc[i][j]);
        __syncthreads();
    }
    for (int i = 0; i < 4; i++)
        for (int j = 0; j < 4; j++)
            if (l0 + ty * 4 + i < kL) h[((size_t)b * kL + l0 + ty * 4 + i) * 512 + d0 + tx * 4 + j] = acc[i][j];
}
__global__ void __launch_bounds__(256) plain_norm(const __nv_bfloat16* __restrict__ gamma, const __nv_bfloat16* __restrict__ beta,
                                                  __nv_bfloat16* __restrict__ out) {
    __shared__ float s1[8][32], s2[8][32];
    const int c = threadIdx.x & 31, r = threadIdx.x >> 5, d = blockIdx.x * 32 + c;
    const float* h = g_direct + (size_t)blockIdx.y * kL * 512 + d;
    float a = 0.f, q = 0.f;
    for (int l = r; l < kL; l += 8) { const float v = h[(size_t)l * 512]; a += v; q = fmaf(v, v, q); }
    s1[r][c] = a; s2[r][c] = q;
    __syncthreads();
    a = q = 0.f;
    for (int i = 0; i < 8; i++) { a += s1[i][c]; q += s2[i][c]; }
    const float mean = a * (1.0f / kL), sc = __bfloat162float(gamma[d]) / sqrtf(fmaxf(q * (1.0f / kL) - mean * mean, 0.f) + 1e-5f);
    const float sh = __bfloat162float(beta[d]) - mean * sc;
    for (int l = r; l < kL; l += 8)
        out[((size_t)blockIdx.y * kL + l) * 512 + d] = __float2bfloat16(gelu_half(0.5f * fmaf(h[(size_t)l * 512], sc, sh)));
}

typedef CUresult (*EncodeTiledFn)(CUtensorMap*, CUtensorMapDataType, cuuint32_t, void*, const cuuint64_t*, const cuuint64_t*,
                                  const cuuint32_t*, const cuuint32_t*, CUtensorMapInterleave, CUtensorMapSwizzle,
                                  CUtensorMapL2promotion, CUtensorMapFloatOOBfill);

void encode(EncodeTiledFn fn, CUtensorMap* tm, const void* ptr, int rank, const cuuint64_t* dims, const cuuint64_t* strides,
            const cuuint32_t* box, CUtensorMapL2promotion promo, CUtensorMapSwizzle swz = CU_TENSOR_MAP_SWIZZLE_128B) {
    const cuuint32_t es[5] = {1, 1, 1, 1, 1};
    fn(tm, CU_TENSOR_MAP_DATA_TYPE_BFLOAT16, rank, const_cast<void*>(ptr), dims, strides, box, es, CU_TENSOR_MAP_INTERLEAVE_NONE,
       swz, promo, CU_TENSOR_MAP_FLOAT_OOB_FILL_NONE);
}

}

extern "C" void kernel_launch(void* const* d_in, const int* in_sizes, int n_in, void* d_out, int out_size) {
    const __nv_bfloat16* x = (const __nv_bfloat16*)d_in[0];
    const __nv_bfloat16* w = (const __nv_bfloat16*)d_in[1];
    const __nv_bfloat16* gamma = (const __nv_bfloat16*)d_in[2];
    const __nv_bfloat16* beta = (const __nv_bfloat16*)d_in[3];
    static EncodeTiledFn enc = nullptr;
    static int resident = 0;
    if (!enc) {
        void* fn = nullptr;
        cudaDriverEntryPointQueryResult qr;
        cudaGetDriverEntryPoint("cuTensorMapEncodeTiled", &fn, cudaEnableDefault, &qr);
        enc = (EncodeTiledFn)fn;
        cudaFuncSetAttribute(main_kernel, cudaFuncAttributeMaxDynamicSharedMemorySize, MAIN_SMEM);
        cudaFuncSetAttribute(corr_kernel, cudaFuncAttributeMaxDynamicSharedMemorySize, C_SMEM);
        int dev = 0, per_sm = 0;
        cudaGetDevice(&dev);
        cudaDeviceGetAttribute(&resident, cudaDevAttrMultiProcessorCount, dev);
        cudaOccupancyMaxActiveBlocksPerMultiprocessor(&per_sm, main_kernel, 384, MAIN_SMEM);
        resident *= per_sm;
    }
    if (resident < NCTA + 4) {
        plain_conv<<<dim3((kL + 63) / 64, 8, 2), 256>>>(x, w);
        plain_norm<<<dim3(16, 2), 256>>>(gamma, beta, (__nv_bfloat16*)d_out);
        return;
    }
    CUtensorMap tmx, tmw0, tmw1, tmcx, tmcw;
    {
        const cuuint64_t dims[3] = {1024, kRows, 2}, strides[2] = {2048, (cuuint64_t)kRows * 2048};
        const cuuint32_t box[3] = {64, 64, 1};
        encode(enc, &tmx, x, 3, dims, strides, box, CU_TENSOR_MAP_L2_PROMOTION_L2_128B);
    }
    {
        const cuuint64_t dims0[3] = {512, 16, 512}, dims1[3] = {512, 15, 512}, strides[2] = {2 * 512 * 512 * 2, 1024};
        const cuuint32_t box[3] = {64, 16, 2};
        encode(enc, &tmw0, w, 3, dims0, strides, box, CU_TENSOR_MAP_L2_PROMOTION_L2_128B);
        encode(enc, &tmw1, w + 512 * 512, 3, dims1, strides, box, CU_TENSOR_MAP_L2_PROMOTION_L2_128B);
    }
    {
        const cuuint64_t dims[4] = {512, kMO, kNT, 2}, strides[3] = {2048, kMO * 2048, (cuuint64_t)kRows * 2048};
        const cuuint32_t box[4] = {64, 1, kNT, 1};
        encode(enc, &tmcx, x, 4, dims, strides, box, CU_TENSOR_MAP_L2_PROMOTION_L2_128B);
        const cuuint64_t dimw[2] = {512, 512}, stridew[1] = {1024};
        const cuuint32_t boxw[2] = {64, 64};
        encode(enc, &tmcw, w + 30 * 512 * 512, 2, dimw, stridew, boxw, CU_TENSOR_MAP_L2_PROMOTION_L2_128B);
    }
    main_kernel<<<NCTA, 384, MAIN_SMEM>>>(tmx, tmw0, tmw1, x, w, gamma, beta, (__nv_bfloat16*)d_out);
    cudaLaunchConfig_t cfg = {};
    cudaLaunchAttribute at[1];
    cfg.gridDim = 4;
    cfg.blockDim = 256;
    cfg.dynamicSmemBytes = C_SMEM;
    cfg.stream = cudaStreamPerThread;
    at[0].id = cudaLaunchAttributeProgrammaticStreamSerialization;
    at[0].val.programmaticStreamSerializationAllowed = 1;
    cfg.attrs = at;
    cfg.numAttrs = 1;
    cudaLaunchKernelEx(&cfg, corr_kernel, tmcx, tmcw);
}
```

```cpp
#include <cuda_runtime.h>
#include <cuda_bf16.h>
#include <cuda.h>
#include <stdint.h>

namespace {

constexpr int kL    = 7985;
constexpr int kRows = 8000;
constexpr int kMO   = 50;
constexpr int kNT   = 160;

constexpr int V0 = 7;
constexpr int NPRE = 6;
constexpr int RX = 4;
constexpr int FCUT = 128;
constexpr int PAUSE = 5;
constexpr int YSLEEP = 100;
constexpr int PRE1 = 4;
constexpr int TSLEEP = 200;
constexpr int MERGE = 1;
constexpr int RW = 10;

static_assert(V0 >= 7 && V0 <= 9 && RX >= 2 && RX <= 4 && RW >= V0 - 1 && RW <= 12, "rings must fit and be as deep as the look-ahead");
constexpr uint32_t HOME_MASK = 0xB;
constexpr uint32_t R_W = 64 * RX, NPAGES = (R_W + 22 * RW + 31) / 32;

__device__ __align__(1024) uint8_t g_sp[(size_t)(NPAGES + 1) * (2u << 20)];
__device__ __align__(128) unsigned g_tsel[32];
__device__ __forceinline__ uint32_t run_sel(uint32_t r, uint32_t group, uint32_t pmask) {
    return ((pmask >> (r >> 5)) ^ __popc(r & HOME_MASK) ^ group) & 1;
}
__device__ __forceinline__ uint32_t run_off(uint32_t r, uint32_t run, uint32_t group, uint32_t pmask) {
    return (r << 16) + 4096 + (run_sel(r, group, pmask) << 13) + (run << 14);
}
__device__ __forceinline__ unsigned* chunk_flag(uint8_t* sp, int done, int part, int chunk) {
    return reinterpret_cast<unsigned*>(sp + (4 + 3 * (chunk >> 5)) * 65536 + (done ? (part ? 15 : 13) : (part ? 0 : 14)) * 4096 + (chunk & 31) * 128);
}
__device__ __forceinline__ unsigned long long* part_sums(uint8_t* sp, int b, int db, uint32_t epoch) {
    return reinterpret_cast<unsigned long long*>(sp + (8 + 2 * db + ((__popc((8 + 2 * db) & HOME_MASK) ^ b) & 1)) * 65536 + 13 * 4096 + (epoch & 1) * 1024);
}
__device__ __forceinline__ unsigned* y_flag(uint8_t* sp, int b, int db) { return reinterpret_cast<unsigned*>(part_sums(sp, b, db, 0) + 512); }
__device__ __align__(256) float g_corr[16 * kNT * 64];
__device__ unsigned g_cready[4 * 32];
__device__ float g_direct[512 * 250 * 64];
__device__ unsigned long long g_dpart[2 * 512 * 64];
__device__ unsigned g_exit, g_epoch;

__device__ __forceinline__ uint32_t smem_u32(const void* p) { return (uint32_t)__cvta_generic_to_shared(p); }

__device__ __forceinline__ void mbar_init(uint32_t bar, uint32_t count) {
    asm volatile("mbarrier.init.shared::cta.b64 [%0], %1;" ::"r"(bar), "r"(count) : "memory");
}
__device__ __forceinline__ void mbar_expect_tx(uint32_t bar, uint32_t bytes) {
    asm volatile("mbarrier.arrive.expect_tx.shared::cta.b64 _, [%0], %1;" ::"r"(bar), "r"(bytes) : "memory");
}
__device__ __forceinline__ void mbar_arrive(uint32_t bar) {
    asm volatile("mbarrier.arrive.shared::cta.b64 _, [%0];" ::"r"(bar) : "memory");
}
__device__ __forceinline__ bool mbar_try(uint32_t bar, uint32_t parity) {
    uint32_t ok;
    asm volatile(
        "{\n.reg .pred p;\n"
        "mbarrier.try_wait.parity.shared::cta.b64 p, [%1], %2;\n"
        "selp.u32 %0, 1, 0, p;\n}\n"
        : "=r"(ok) : "r"(bar), "r"(parity) : "memory");
    return ok;
}
__device__ __forceinline__ bool mbar_test(uint32_t bar, uint32_t parity) {
    uint32_t ok;
    asm volatile(
        "{\n.reg .pred p;\n"
        "mbarrier.test_wait.parity.shared::cta.b64 p, [%1], %2;\n"
        "selp.u32 %0, 1, 0, p;\n}\n"
        : "=r"(ok) : "r"(bar), "r"(parity) : "memory");
    return ok;
}
__device__ __forceinline__ void mbar_wait(uint32_t bar, uint32_t parity) {
#pragma unroll 1
    for (uint32_t n = 0; n < (1u << 14); n++)
        if (mbar_try(bar, parity)) break;
}
__device__ __forceinline__ void fence_proxy_async_smem() { asm volatile("fence.proxy.async.shared::cta;" ::: "memory"); }
__device__ __forceinline__ void fence_mbar_init() { asm volatile("fence.mbarrier_init.release.cluster;" ::: "memory"); }

__device__ __forceinline__ void bulk_g2s(uint32_t dst, const void* src, uint32_t bytes, uint32_t bar) {
    asm volatile("cp.async.bulk.shared::cluster.global.mbarrier::complete_tx::bytes [%0], [%1], %2, [%3];"
                 ::"r"(dst), "l"(src), "r"(bytes), "r"(bar) : "memory");
}
__device__ __forceinline__ void bulk_g2s_ef(uint32_t dst, const void* src, uint32_t bytes, uint32_t bar) {
    asm volatile("{\n.reg .b64 pol;\ncreatepolicy.fractional.L2::evict_first.b64 pol, 1.0;\n"
                 "cp.async.bulk.shared::cluster.global.mbarrier::complete_tx::bytes.L2::cache_hint [%0], [%1], %2, [%3], pol;\n}"
                 ::"r"(dst), "l"(src), "r"(bytes), "r"(bar) : "memory");
}
__device__ __forceinline__ void tma3d_ef(uint32_t dst, const CUtensorMap* tm, int c0, int c1, int c2, uint32_t bar) {
    asm volatile("{\n.reg .b64 pol;\ncreatepolicy.fractional.L2::evict_first.b64 pol, 1.0;\n"
                 "cp.async.bulk.tensor.3d.shared::cluster.global.mbarrier::complete_tx::bytes.L2::cache_hint [%0], [%1, {%3, %4, %5}], [%2], pol;\n}"
                 ::"r"(dst), "l"(tm), "r"(bar), "r"(c0), "r"(c1), "r"(c2) : "memory");
}
__device__ __forceinline__ void tma3d(uint32_t dst, const CUtensorMap* tm, int c0, int c1, int c2, uint32_t bar) {
    asm volatile("cp.async.bulk.tensor.3d.shared::cluster.global.mbarrier::complete_tx::bytes [%0], [%1, {%3, %4, %5}], [%2];"
                 ::"r"(dst), "l"(tm), "r"(bar), "r"(c0), "r"(c1), "r"(c2) : "memory");
}
__device__ __forceinline__ void poll_ge(const unsigned* p, unsigned target) {
#pragma unroll 1
    for (uint32_t n = 0; n < (1u << 15); n++) {
        unsigned v;
        asm volatile("ld.acquire.gpu.global.u32 %0, [%1];" : "=r"(v) : "l"(p) : "memory");
        if (v >= target) break;
        __nanosleep(32);
    }
}
__device__ __forceinline__ void red_relaxed(unsigned* p) { asm volatile("red.relaxed.gpu.global.add.u32 [%0], 1;" ::"l"(p) : "memory"); }
__device__ __forceinline__ void named_arrive(int id, int n) { asm volatile("bar.arrive %0, %1;" ::"r"(id), "r"(n) : "memory"); }
__device__ __forceinline__ void named_bar(int id, int n) { asm volatile("bar.sync %0, %1;" ::"r"(id), "r"(n) : "memory"); }

__device__ __forceinline__ void wg_fence() { asm volatile("wgmma.fence.sync.aligned;" ::: "memory"); }
__device__ __forceinline__ void wg_commit() { asm volatile("wgmma.commit_group.sync.aligned;" ::: "memory"); }
template <int N> __device__ __forceinline__ void wg_wait() { asm volatile("wgmma.wait_group.sync.aligned %0;" ::"n"(N) : "memory"); }
template <int N> __device__ __forceinline__ void reg_fence(float (&d)[N]) {
#pragma unroll
    for (int i = 0; i < N; i++) asm volatile("" : "+f"(d[i])::"memory");
}

#define F4(a, i) "+f"(a[i]), "+f"(a[i + 1]), "+f"(a[i + 2]), "+f"(a[i + 3])
#define F8(a, i) F4(a, i), F4(a, i + 4)
#define F16(a, i) F8(a, i), F8(a, i + 8)

constexpr uint32_t HI128 = 0x40000040u, HI64 = 0x80000020u;
__device__ __forceinline__ uint32_t desc_lo(uint32_t addr) { return (addr >> 4) | 0x10000u; }


#define R4(a, i) "+r"(a[i]), "+r"(a[i + 1]), "+r"(a[i + 2]), "+r"(a[i + 3])
#define R8(a, i) R4(a, i), R4(a, i + 4)
template <int N> __device__ __forceinline__ void reg_fence(uint32_t (&d)[N]) {
#pragma unroll
    for (int i = 0; i < N; i++) asm volatile("" : "+r"(d[i])::"memory");
}
__device__ __forceinline__ void tma2d(uint32_t dst, const CUtensorMap* tm, int c0, int c1, uint32_t bar) {
    asm volatile("cp.async.bulk.tensor.2d.shared::cluster.global.mbarrier::complete_tx::bytes [%0], [%1, {%3, %4}], [%2];"
                 ::"r"(dst), "l"(tm), "r"(bar), "r"(c0), "r"(c1) : "memory");
}
__device__ __forceinline__ void tma4d(uint32_t dst, const CUtensorMap* tm, int c0, int c1, int c2, int c3, uint32_t bar) {
    asm volatile("cp.async.bulk.tensor.4d.shared::cluster.global.mbarrier::complete_tx::bytes [%0], [%1, {%3, %4, %5, %6}], [%2];"
                 ::"r"(dst), "l"(tm), "r"(bar), "r"(c0), "r"(c1), "r"(c2), "r"(c3) : "memory");
}
__device__ __forceinline__ bool named_bar_or(int id, int n, bool v) {
    uint32_t r;
    asm volatile("{\n.reg .pred p, q;\nsetp.ne.u32 q, %3, 0;\nbar.red.or.pred p, %1, %2, q;\nselp.u32 %0, 1, 0, p;\n}"
                 : "=r"(r) : "r"(id), "r"(n), "r"((uint32_t)v) : "memory");
    return r;
}

template <uint32_t AHI, int ACC>
__device__ __forceinline__ void wgmma_n64_ss(float (&d)[32], uint32_t da, uint32_t db) {
    asm volatile(
        "{\n.reg .pred p;\n.reg .b64 da, db;\nsetp.ne.b32 p, %36, 0;\nmov.b64 da, {%32, %34};\nmov.b64 db, {%33, %35};\n"
        "wgmma.mma_async.sync.aligned.m64n64k16.f32.bf16.bf16 "
        "{%0,%1,%2,%3,%4,%5,%6,%7,%8,%9,%10,%11,%12,%13,%14,%15,%16,%17,%18,%19,%20,%21,%22,%23,%24,%25,%26,%27,%28,%29,%30,%31},"
        "da, db, p, 1, 1, 0, 1;\n}\n"
        : F16(d, 0), F16(d, 16)
        : "r"(da), "r"(db), "n"(AHI), "n"(HI128), "n"(ACC));
}


template <int ACC>
__device__ __forceinline__ void wgmma_n56_ss(float (&d)[28], uint32_t da, uint32_t db) {
    asm volatile(
        "{\n.reg .pred p;\n.reg .b64 da, db;\nsetp.ne.b32 p, %31, 0;\nmov.b64 da, {%28, %30};\nmov.b64 db, {%29, %30};\n"
        "wgmma.mma_async.sync.aligned.m64n56k16.f32.f16.f16 "
        "{%0,%1,%2,%3,%4,%5,%6,%7,%8,%9,%10,%11,%12,%13,%14,%15,%16,%17,%18,%19,%20,%21,%22,%23,%24,%25,%26,%27},"
        "da, db, p, 1, 1, 1, 0;\n}\n"
        : F16(d, 0), F8(d, 16), F4(d, 24)
        : "r"(da), "r"(db), "n"(HI128), "n"(ACC));
}

template <int SA>
__device__ __forceinline__ void wgmma_n160_h(uint32_t (&d)[40], uint32_t da, uint32_t db) {
    asm volatile(
        "{\n.reg .pred p;\n.reg .b64 da, db;\nsetp.eq.b32 p, 0, 0;\nmov.b64 da, {%40, %43};\nmov.b64 db, {%41, %43};\n"
        "wgmma.mma_async.sync.aligned.m64n160k16.f16.f16.f16 "
        "{%0,%1,%2,%3,%4,%5,%6,%7,%8,%9,%10,%11,%12,%13,%14,%15,%16,%17,%18,%19,%20,%21,%22,%23,%24,%25,%26,%27,"
        "%28,%29,%30,%31,%32,%33,%34,%35,%36,%37,%38,%39},"
        "da, db, p, %42, 1, 1, 0;\n}\n"
        : R8(d, 0), R8(d, 8), R8(d, 16), R8(d, 24), R8(d, 32)
        : "r"(da), "r"(db), "n"(SA), "n"(HI128));
}
template <int SA>
__device__ __forceinline__ void wgmma_n160_hr(uint32_t (&d)[40], const uint32_t (&a)[4], uint32_t db) {
    asm volatile(
        "{\n.reg .pred p;\n.reg .b64 db;\nsetp.eq.b32 p, 0, 0;\nmov.b64 db, {%44, %46};\n"
        "wgmma.mma_async.sync.aligned.m64n160k16.f16.f16.f16 "
        "{%0,%1,%2,%3,%4,%5,%6,%7,%8,%9,%10,%11,%12,%13,%14,%15,%16,%17,%18,%19,%20,%21,%22,%23,%24,%25,%26,%27,"
        "%28,%29,%30,%31,%32,%33,%34,%35,%36,%37,%38,%39},"
        "{%40,%41,%42,%43}, db, p, %45, 1, 0;\n}\n"
        : R8(d, 0), R8(d, 8), R8(d, 16), R8(d, 24), R8(d, 32)
        : "r"(a[0]), "r"(a[1]), "r"(a[2]), "r"(a[3]), "r"(db), "n"(SA), "n"(HI128));
}
template <int SA>
__device__ __forceinline__ void wgmma_n160_f(float (&d)[80], uint32_t da, uint32_t db) {
    asm volatile(
        "{\n.reg .pred p;\n.reg .b64 da, db;\nsetp.eq.b32 p, 0, 0;\nmov.b64 da, {%80, %83};\nmov.b64 db, {%81, %83};\n"
        "wgmma.mma_async.sync.aligned.m64n160k16.f32.bf16.bf16 "
        "{%0,%1,%2,%3,%4,%5,%6,%7,%8,%9,%10,%11,%12,%13,%14,%15,%16,%17,%18,%19,%20,%21,%22,%23,%24,%25,%26,%27,"
        "%28,%29,%30,%31,%32,%33,%34,%35,%36,%37,%38,%39,%40,%41,%42,%43,%44,%45,%46,%47,%48,%49,%50,%51,%52,%53,%54,%55,"
        "%56,%57,%58,%59,%60,%61,%62,%63,%64,%65,%66,%67,%68,%69,%70,%71,%72,%73,%74,%75,%76,%77,%78,%79},"
        "da, db, p, %82, 1, 1, 0;\n}\n"
        : F16(d, 0), F16(d, 16), F16(d, 32), F16(d, 48), F16(d, 64)
        : "r"(da), "r"(db), "n"(SA), "n"(HI128));
}

__device__ __forceinline__ uint32_t pack_f16(float lo, float hi) {
    uint32_t r;
    asm("cvt.rn.f16x2.f32 %0, %1, %2;" : "=r"(r) : "f"(hi), "f"(lo));
    return r;
}
__device__ __forceinline__ uint32_t mul_bf16x2(uint32_t a, uint32_t b) {
    uint32_t r;
    asm("mul.rn.bf16x2 %0, %1, %2;" : "=r"(r) : "r"(a), "r"(b));
    return r;
}
__device__ __forceinline__ void sts128(uint32_t p, uint32_t a, uint32_t b, uint32_t c, uint32_t d) {
    asm volatile("st.shared.v4.b32 [%0], {%1,%2,%3,%4};" ::"r"(p), "r"(a), "r"(b), "r"(c), "r"(d) : "memory");
}
__device__ __forceinline__ uint32_t pack_bf16(float lo, float hi) {
    uint32_t r;
    asm("cvt.rn.bf16x2.f32 %0, %1, %2;" : "=r"(r) : "f"(hi), "f"(lo));
    return r;
}
__device__ __forceinline__ void stg128(void* p, uint32_t a, uint32_t b, uint32_t c, uint32_t d) {
    asm volatile("st.global.v4.b32 [%0], {%1,%2,%3,%4};" ::"l"(p), "r"(a), "r"(b), "r"(c), "r"(d) : "memory");
}
__device__ __forceinline__ void stmatrix_x4_t(uint32_t addr, uint32_t a, uint32_t b, uint32_t c, uint32_t d) {
    asm volatile("stmatrix.sync.aligned.m8n8.x4.trans.shared.b16 [%0], {%1,%2,%3,%4};"
                 ::"r"(addr), "r"(a), "r"(b), "r"(c), "r"(d) : "memory");
}

constexpr uint32_t cos64(int k, bool half) {
    constexpr uint16_t q[17] = {0x3F80, 0x3F7F, 0x3F7B, 0x3F75, 0x3F6D, 0x3F62, 0x3F55, 0x3F46, 0x3F35, 0x3F22, 0x3F0E, 0x3EF1, 0x3EC4, 0x3E95, 0x3E48, 0x3DC9, 0x0000};
    constexpr uint16_t h[17] = {0x3C00, 0x3BF6, 0x3BD9, 0x3BA8, 0x3B64, 0x3B0E, 0x3AA7, 0x3A2F, 0x39A8, 0x3913, 0x3872, 0x378B, 0x361F, 0x34A5, 0x323E, 0x2E46, 0x0000};
    k &= 63;
    if (k > 32) k = 64 - k;
    const uint16_t* t = half ? h : q;
    return k <= 16 ? t[k] : (t[32 - k] | 0x8000u);
}
constexpr uint32_t fwd_coef(int s, int p, int t) { return (p && s == 0) ? cos64(32 * t, false) : cos64(s * t - 16 * p, false); }
constexpr uint32_t inv_coef(int l, int phi) {
    const int s = phi >> 1, p = phi & 1;
    if (l >= kMO) return 0;
    const uint32_t c = s == 0 ? cos64(32 * l * p, true) : cos64(s * l + 16 * p, true);
    return (c & 0x7FFF) ? c - ((s == 0 ? 6 : 5) << 10) : 0;
}
struct Tables {
    uint32_t fwd[2048];
    uint32_t inv[2048];
};
constexpr Tables make_tables() {
    Tables t = {};
    for (int i = 0; i < 2048; i++) {
        const int row = i >> 5, tt = 8 * (((i >> 2) & 7) ^ (row & 7)) + 2 * (i & 3), s = 8 * (row >> 4) + (row & 7), p = (row >> 3) & 1;
        t.fwd[i] = fwd_coef(s, p, tt) | (fwd_coef(s, p, tt + 1) << 16);
        t.inv[i] = inv_coef(row, tt) | (inv_coef(row, tt + 1) << 16);
    }
    return t;
}
__device__ __align__(128) const Tables g_tab = make_tables();

constexpr int NCTA = 128;
constexpr int NST = 4;
constexpr int HEND = 56;
constexpr int XB = kNT * 128;
constexpr int OFF_W1 = 0, OFF_X = OFF_W1 + NST * 8192, OFF_W0 = OFF_X + 4 * XB, OFF_RAW = OFF_W0 + NST * 8192;
constexpr int OFF_STG = OFF_RAW + 32768;
constexpr int OFF_U0 = OFF_W0, OFF_U1 = OFF_X, OFF_C1 = OFF_W1, OFF_DIR = OFF_W1 + 8192;
constexpr int OFF_F = OFF_RAW + 65536;
constexpr int OFF_G = OFF_F + 8192;
constexpr int OFF_C0 = OFF_G;
constexpr int OFF_BAR = OFF_G + 4096;
constexpr int B_FULL = 0, B_EMPTY = 8 * NST, B_TSEL = 16 * NST, B_PRE = B_TSEL + 8, B_SIG = B_PRE + 16 * V0, B_YS = B_SIG + 8 * 33,
              B_T2 = B_YS + 8 * 4, B_SUM = B_T2 + 16, B_GATE = B_SUM + 32, B_RDY = B_GATE + 8 * 32, B_PUB = B_RDY + 8 * 33, B_UNIT = B_PUB + 8,
              B_FTAB = B_UNIT + 8 * 20, B_C1 = B_FTAB + 8, B_NRM = B_C1 + 8, B_END = B_NRM + 32;
template <int O0, int O1>
__device__ __forceinline__ void bar_setup(uint32_t bars) {
#pragma unroll
    for (int o = O0; o < O1; o += 8)
        mbar_init(bars + o, o < B_EMPTY ? 2 : o < B_TSEL ? 8 : o == B_TSEL ? 2 : o < B_SIG ? 1 : o < B_YS - 8 ? 8 : o < B_GATE ? 4 : 1);
    fence_mbar_init();
    fence_proxy_async_smem();
}
constexpr int OFF_TS = OFF_BAR + B_END;
constexpr int OFF_PLAN = OFF_TS + 336;
constexpr int OFF_YT = OFF_PLAN + (V0 + 65) * 8;
constexpr int OFF_GB = (OFF_YT + 4 * kNT * 4 + 15) & ~15;
constexpr int MAIN_SMEM = OFF_GB + 2048;
static_assert(MAIN_SMEM <= 232448 && OFF_U0 + 10 * 8192 == OFF_STG + 16384, "shared memory");
constexpr int XPC = 2 * kNT;
constexpr unsigned PROBE_NEAR = 400;

__device__ __forceinline__ uint32_t raw_slot(uint32_t sbase, uint32_t v, int wg) { return sbase + OFF_RAW + ((v & 3) * 2 + wg) * 8192; }

__device__ __forceinline__ uint32_t pre_slot(uint32_t sbase, uint32_t v, int wg) {
    return v < 4 ? raw_slot(sbase, v, wg) : v < 8 ? sbase + OFF_X + (v - 4) * XB + wg * 8192 : sbase + (wg ? OFF_W1 : OFF_W0) + ((V0 + 3) % NST) * 8192;
}
constexpr int OFF_TMP = OFF_W1 + 8192;

template <bool DC, int I>
__device__ __forceinline__ void gemm_mma(uint32_t (&a0)[40], uint32_t (&a1)[40], uint32_t dx0, uint32_t dx1, uint32_t dw) {
    constexpr int ks = I >> 2;
    const uint32_t A0 = dw + ks * 128, A1 = A0 + 256, B0 = dx0 + ks * 2, B1 = dx1 + ks * 2;
    if ((I & 3) == 0) wgmma_n160_h<1>(a0, A0, B0);
    if ((I & 3) == 1) wgmma_n160_h<1>(a1, A1, DC ? B1 : B0);
    if ((I & 3) == 2 && !DC) wgmma_n160_h<1>(a0, A1, B1);
    if ((I & 3) == 3 && !DC) wgmma_n160_h<-1>(a1, A0, B1);
}

template <bool DC, int I0, int I1>
__device__ __forceinline__ void gemm_mmas(uint32_t (&a0)[40], uint32_t (&a1)[40], uint32_t dx0, uint32_t dx1, uint32_t dw) {
    if constexpr (I0 < I1) {
        gemm_mma<DC, I0>(a0, a1, dx0, dx1, dw);
        gemm_mmas<DC, I0 + 1, I1>(a0, a1, dx0, dx1, dw);
    }
}
static_assert(RX == 4 && RW == 10, "placement of the output spectra");
__device__ __forceinline__ uint32_t y_unit(uint32_t db, uint32_t tau, uint32_t b, uint32_t pmask) {
    const uint32_t n = (((db >> 1) & 2) + (db & 1)) * XPC + ((db >> 1) & 1) * kNT + tau, r = n / 3;
    return run_off(r + (r >= 192 && r < 278 ? (r < 214 ? 64 : -22) : 0), n % 3, b, pmask);
}
__device__ __forceinline__ int y_gate(int t) { return t ? 28 + t : 27; }
__device__ __forceinline__ int step_k(int h) { return h < HEND ? h >> 1 : 28 + (h & 3); }
__device__ __forceinline__ int step_m(int h) { return h < HEND ? h & 1 : (h >> 2) & 1; }
constexpr uint64_t x_mask() {
    uint64_t r = 2 | (3ull << 58);
    for (int v = 2; v < 58; v++)
        if ((0x6B >> (v & 7)) & 1) r |= 1ull << v;
    return r;
}
constexpr uint64_t XMASK = x_mask();
__device__ __forceinline__ int x_round(int v, int wg) {
    return v == 0 ? wg : (v < 60 && wg != (v & 1) && ((XMASK >> v) & 1)) ? 1 + __popcll(XMASK << (63 - v)) : -1;
}
__device__ __forceinline__ int w_step(int v, int wg) {
    return v == 0 ? -1 : v < 60 ? (wg == (v & 1) ? v - 1 : -1) : v < 62 ? 2 * v - 61 + wg : (v == 62 && wg == 0) ? 63 : -1;
}

__device__ __forceinline__ uint32_t plan_word(int v, int wg, int cta) {
    const int r = x_round(v, wg), h = w_step(v, wg);
    if (r < 0 && h < 0) return 0;
    const bool last = v >= 60 || (v & 1) || (v > 0 && wg == 0 && x_round(v + 1, 0) < 0);
    uint32_t off, row, gate;
    if (r >= 0) {
        const int u = r * NCTA + cta, cb = u / XPC, i = u - cb * XPC, b = i >= kNT, tau = i - b * kNT;
        row = tau & 63;
        off = (((cb % RX) * 64 + b) << 16) + ((tau >> 6) << 14) + b + 2;
        gate = cb >= RX ? 2 * (cb - RX) + 2 : 0;
    } else {
        const int ring = (h + RW - 64 % RW) % RW;
        row = 0;
        off = ((ring * 22) << 16) + (ring << 12) + 4;
        gate = h >= RW ? ((h - RW + 1) >> 1) + 1 : 0;
    }
    return (off + row * 128) | ((row & 7) << 4) | (last << 3) | ((v > 60) << 24) | (gate << 26);
}

struct Xf {
    uint32_t sbase;
    uint8_t *px, *pw;
    uint32_t cx, cw;
    uint32_t xsw;
    uint32_t dw;
    uint32_t e;
    int lane;
};
__device__ __forceinline__ uint32_t plan_load(const Xf& f, uint32_t v, int wg) {
    uint32_t e;
    asm volatile("ld.shared.u32 %0, [%1];" : "=r"(e) : "r"(f.sbase + OFF_PLAN + v * 8 + wg * 4));
    return __shfl_sync(0xffffffffu, e, 0);
}
template <bool W>
__device__ __forceinline__ void unit_mma(float (&acc)[32], const Xf& f, uint32_t raw) {
    const uint32_t dB = desc_lo(raw);
    if (W) {
        const uint32_t dG = desc_lo(f.sbase + OFF_G);
        wgmma_n64_ss<HI64, 0>(acc, dG, dB);
        wgmma_n64_ss<HI64, 1>(acc, dG + 2, dB + 128);
    } else {
        const uint32_t dF = desc_lo(f.sbase + OFF_F);
        wgmma_n64_ss<HI128, 0>(acc, dF, dB);
        wgmma_n64_ss<HI128, 1>(acc, dF + 2, dB + 128);
        wgmma_n64_ss<HI128, 1>(acc, dF + 4, dB + 256);
        wgmma_n64_ss<HI128, 1>(acc, dF + 6, dB + 384);
    }
    wg_commit();
}
constexpr int DROP = 3;
__device__ __forceinline__ uint32_t pack_sp(float lo, float hi) {
    const uint32_t r = pack_f16(lo, hi);
    return DROP ? (r + (0x10001u << DROP >> 1)) & ~(((1u << DROP) - 1) * 0x10001u) : r;
}
__device__ __forceinline__ void st_quad(uint8_t* p, const float (&acc)[32], int j0) {
    stg128(p, pack_sp(acc[j0], acc[j0 + 1]), pack_sp(acc[j0 + 4], acc[j0 + 5]), pack_sp(acc[j0 + 8], acc[j0 + 9]),
           pack_sp(acc[j0 + 12], acc[j0 + 13]));
}
template <bool W>
__device__ __forceinline__ void unit_store(float (&acc)[32], const Xf& f, uint32_t e) {
    const uint32_t sel = ((W ? f.cw >> (8 + ((e >> 12) & 15)) : e ^ (f.cx >> (8 + ((e >> 21) & 6)))) & 1) << 13;
    const uint32_t o = (e & (W ? 0xFF0F80u : 0xFFFF80u)) + ((e ^ (W ? f.cw : f.cx)) & 0x70);
    uint8_t* const b = W ? f.pw : f.px;
    uint8_t *p0 = b + (o + sel), *p1 = b + ((o ^ 64) + sel);
    reg_fence(acc);
    if (W) {
        st_quad(p0, acc, 0);
        st_quad(p1, acc, 16);
        st_quad(p0 + 4096, acc, 2);
        st_quad(p1 + 4096, acc, 18);
    } else {
        const int d = 131072 + 8192 - 2 * (int)sel;
        st_quad(p0, acc, 0);
        st_quad(p1, acc, 2);
        st_quad(p0 + d, acc, 16);
        st_quad(p1 + d, acc, 18);
    }
}
__device__ __forceinline__ void unit_done(const Xf& f, uint32_t e, uint32_t v) {
    if (e & 8) {
        __syncwarp();
        if (f.lane == 0) mbar_arrive(f.sbase + OFF_BAR + B_SIG + 8 * ((v >> 1) + ((e >> 24) & 1)));
    }
}
__device__ __forceinline__ void step_wait(Xf& f, uint32_t v, int wg) {
    const uint32_t bars = f.sbase + OFF_BAR;
    if (f.e >> 26) mbar_wait(bars + B_GATE - 8 + 8 * (f.e >> 26), 0);
    mbar_wait(bars + B_FULL + 8 * (v % NST), (v / NST) & 1);
}

template <bool DC, int KIND>
__device__ __forceinline__ void gemm_step(uint32_t (&a0)[40], uint32_t (&a1)[40], float (&at)[32], Xf& f, uint32_t v, uint32_t xs, int wg, bool first) {
    const uint32_t bars = f.sbase + OFF_BAR, sb = desc_lo(f.sbase), xb = sb + OFF_X / 16 + xs * (XB / 16), raw = raw_slot(f.sbase, v, wg);
    const uint32_t dx0 = xb + f.xsw, dx1 = xb + (f.xsw ^ 4), dw = f.dw + (v % NST) * 512, e = f.e;
    wg_fence();
    if (KIND) unit_mma<KIND != 1>(at, f, raw);
    constexpr int N1 = KIND == 0 ? 2 : NPRE;
    gemm_mmas<DC, 0, N1>(a0, a1, dx0, dx1, dw);
    wg_commit();
    f.e = plan_load(f, v + 1, wg);
    wg_wait<1>();
    if (!KIND && !first && f.lane == 0) mbar_arrive(bars + B_EMPTY + 8 * ((v - 1) % NST));
    if (KIND) unit_store<KIND != 1>(at, f, e);
    if (KIND) unit_done(f, e, v);
    gemm_mmas<DC, N1, 7>(a0, a1, dx0, dx1, dw);
    if (KIND && !first && f.lane == 0) mbar_arrive(bars + B_EMPTY + 8 * ((v - 1) % NST));
    gemm_mma<DC, 7>(a0, a1, dx0, dx1, dw);
    wg_commit();
}
template <bool DC>
__device__ __forceinline__ void any_step(uint32_t (&a0)[40], uint32_t (&a1)[40], float (&at)[32], Xf& f, uint32_t v, uint32_t xs, int wg, bool first) {
    step_wait(f, v, wg);
    const uint32_t kind = (f.e >> 1) & 3;
    if (kind == 1) gemm_step<DC, 1>(a0, a1, at, f, v, xs, wg, first);
    else if (kind == 2) gemm_step<DC, 2>(a0, a1, at, f, v, xs, wg, first);
    else gemm_step<DC, 0>(a0, a1, at, f, v, xs, wg, first);
}
template <bool DC>
__device__ __forceinline__ void gemm_main(uint32_t (&a0)[40], uint32_t (&a1)[40], uint32_t (&b0)[40], uint32_t (&b1)[40], Xf& f, int wg) {
    float at[32];
#pragma unroll 1
    for (uint32_t k = 0; k < HEND / 2; k++) {
        any_step<DC>(a0, a1, at, f, V0 + 2 * k, k & 3, wg, k == 0);
        any_step<DC>(b0, b1, at, f, V0 + 2 * k + 1, k & 3, wg, false);
    }
    wg_wait<0>();
    if (f.lane == 0) mbar_arrive(f.sbase + OFF_BAR + B_EMPTY + 8 * ((V0 + HEND - 1) % NST));
}
__device__ __forceinline__ void w_fetch(uint32_t (&d)[4][4], const Xf& f, uint32_t v) {
    const uint32_t bars = f.sbase + OFF_BAR, lane = f.lane;
    const uint32_t wa = ((f.dw & 0xFFFF) << 4) + (v % NST) * 8192 + (lane >> 4) * 1024 + (lane & 7) * 128 +
                        (((((threadIdx.x >> 4) & 6) + ((lane >> 3) & 1)) ^ (lane & 7)) << 4);
    mbar_wait(bars + B_FULL + 8 * (v % NST), (v / NST) & 1);
#pragma unroll
    for (int i = 0; i < 4; i++)
        asm volatile("ldmatrix.sync.aligned.m8n8.x4.trans.shared.b16 {%0,%1,%2,%3}, [%4];" : "=r"(d[i][0]), "=r"(d[i][1]), "=r"(d[i][2]), "=r"(d[i][3])
                     : "r"(wa + i * 2048) : "memory");
}
__device__ __forceinline__ void store_tile(uint32_t (&a0)[40], uint32_t (&a1)[40], const uint32_t (&b0)[40], const uint32_t (&b1)[40], uint32_t (&wn)[4][4],
                                           const Xf& f, bool first, uint32_t stg, int t, int wg, uint8_t* sp, int slot, uint32_t ytab, int wsw) {
    const int w = t >> 5, lane = t & 31, m = lane >> 3, i8 = lane & 7;
    const uint32_t addr = stg + i8 * 256 + (m >> 1) * 128 + (((2 * w + (m & 1)) ^ i8 ^ wsw) << 4);
    const int row = 2 * w + (lane >> 4), phi = 2 * slot + (m & 1);
    const uint32_t src = stg + row * 256 + (m & 1) * 128 + ((i8 ^ row) << 4);
    uint8_t* dst = sp + phi * 128 + ((i8 ^ (phi & 7)) << 4);
    named_bar(2 + wg, 128);
#pragma unroll
    for (int r = 0; r < 6; r++) {
        uint32_t v[4][4], o[4];
        if (r > 0) {
#pragma unroll
            for (int i = 0; i < 4; i++) {
                asm volatile("ld.shared.u32 %0, [%1];" : "=r"(o[i]) : "r"(ytab + (32 * (r - 1) + 8 * i + row) * 4) : "memory");
                asm volatile("ld.shared.v4.b32 {%0,%1,%2,%3}, [%4];" : "=r"(v[i][0]), "=r"(v[i][1]), "=r"(v[i][2]), "=r"(v[i][3])
                             : "r"(src + ((r - 1) & 1) * 8192 + i * 2048) : "memory");
            }
        }
        if (r < 5) {
#pragma unroll
            for (int j = 4 * r; j < 4 * r + 4; j++) stmatrix_x4_t(addr + (r & 1) * 8192 + (j & 3) * 2048, a0[2 * j], a0[2 * j + 1], a1[2 * j], a1[2 * j + 1]);
#pragma unroll
            for (int j = 8 * r; j < 8 * r + 8; j++) {
                asm volatile("mov.b32 %0, %1;" : "=r"(a0[j]) : "r"(b0[j]));
                asm volatile("mov.b32 %0, %1;" : "=r"(a1[j]) : "r"(b1[j]));
            }
        } else if (first) {
            w_fetch(wn, f, V0 + HEND + 4);
        }
        if (r > 0) {
#pragma unroll
            for (int i = 0; i < 4; i++) stg128(dst + o[i], v[i][0], v[i][1], v[i][2], v[i][3]);
        }
        if (r < 5) named_bar(2 + wg, 128);
    }
}

template <bool DC>
__device__ __forceinline__ void gemm_last(uint32_t (&a0)[40], uint32_t (&a1)[40], uint32_t (&w)[2][4][4], const Xf& f, int wg, int m) {
    const uint32_t bars = f.sbase + OFF_BAR, sb = desc_lo(f.sbase), v0 = V0 + HEND + 4 * m;
    if (2 * m + wg > 0) named_bar(3 + 2 * m + wg, 256);
#pragma unroll
    for (uint32_t k = 0; k < 4; k++) {
        const uint32_t xb = sb + OFF_X / 16 + k * (XB / 16), dx0 = xb + f.xsw, dx1 = xb + (f.xsw ^ 4);
        wg_fence();
#pragma unroll
        for (int ks = 0; ks < 2; ks++) {
            wgmma_n160_hr<1>(a0, w[k & 1][ks], dx0 + 2 * ks);
            wgmma_n160_hr<1>(a1, w[k & 1][2 + ks], (DC ? dx1 : dx0) + 2 * ks);
            if (!DC) wgmma_n160_hr<1>(a0, w[k & 1][2 + ks], dx1 + 2 * ks);
            if (!DC) wgmma_n160_hr<-1>(a1, w[k & 1][ks], dx1 + 2 * ks);
        }
        wg_commit();
        if (m == 0 && f.lane == 0) mbar_arrive(bars + B_EMPTY + 8 * ((v0 + k) % NST));
        if (k == 3 && 2 * m + wg < 3) named_arrive(4 + 2 * m + wg, 256);
        if (k > 0) wg_wait<1>();
        if (k < 3) w_fetch(w[(k + 1) & 1], f, v0 + k + 1);
    }
    wg_wait<0>();
    if (m && f.lane == 0) mbar_arrive(bars + B_T2 + 8 * wg);
}

__device__ __forceinline__ float gelu_half(float hv) {
    float th;
    asm("tanh.approx.f32 %0, %1;" : "=f"(th) : "f"(hv * fmaf(hv * hv, 8.0f * 0.7978845608028654f * 0.044715f, 2.0f * 0.7978845608028654f)));
    return fmaf(hv, th, hv);
}
__device__ __noinline__ void direct_block(const __nv_bfloat16* __restrict__ x, const __nv_bfloat16* __restrict__ w,
                                          const __nv_bfloat16* __restrict__ gamma, const __nv_bfloat16* __restrict__ beta,
                                          __nv_bfloat16* __restrict__ out, float* sm, int b, int db, int part, uint32_t epoch) {
    float *xs = sm, *ws = sm + 32 * 17, *red = ws + 16 * 65;
    const int tid = threadIdx.x & 127, bar = 2 + (threadIdx.x >> 7), tx = tid & 15, ty = tid >> 4, row0 = part * 250, lim = min(250, kL - row0);
    float* h = g_direct + (size_t)((b * 8 + db) * 32 + part) * (250 * 64);
    for (int l0 = 0; l0 < lim; l0 += 32) {
        float acc[4][4] = {};
        for (int k0 = 0; k0 < 31 * 512; k0 += 16) {
            named_bar(bar, 128);
            for (int i = tid; i < 1024; i += 128) {
                if (i < 512) xs[(i >> 4) * 17 + (i & 15)] = __bfloat162float(x[((size_t)b * kRows + row0 + min(l0 + (i >> 4), lim - 1)) * 1024 + k0 + (i & 15)]);
                ws[(i >> 6) * 65 + (i & 63)] = __bfloat162float(w[(size_t)(k0 + (i >> 6)) * 512 + 64 * db + (i & 63)]);
            }
            named_bar(bar, 128);
            for (int k = 0; k < 16; k++)
#pragma unroll
                for (int i = 0; i < 4; i++)
#pragma unroll
                    for (int j = 0; j < 4; j++) acc[i][j] = fmaf(xs[(ty * 4 + i) * 17 + k], ws[k * 65 + tx * 4 + j], acc[i][j]);
        }
#pragma unroll
        for (int i = 0; i < 4; i++)
#pragma unroll
            for (int j = 0; j < 4; j++)
                if (l0 + ty * 4 + i < lim) h[(l0 + ty * 4 + i) * 64 + tx * 4 + j] = acc[i][j];
    }
    const int c = tid & 63;
    float mean = 0.f, var = 0.f;
    for (int r = 0; r < 2; r++) {
        named_bar(bar, 128);
        float s = 0.f;
        for (int l = tid >> 6; l < lim; l += 2) {
            const float v = h[l * 64 + c] - mean;
            s += r ? v * v : v;
        }
        red[tid] = s;
        named_bar(bar, 128);
        unsigned long long* p = g_dpart + ((r * 16 + b * 8 + db) * 32) * 64 + c;
        if (tid < 64)
            asm volatile("st.relaxed.gpu.global.v2.b32 [%0], {%1, %2};" ::"l"(p + part * 64), "r"(__float_as_uint(red[c] + red[64 + c])), "r"(epoch) : "memory");
        s = 0.f;
        for (int k = 0; k < 32; k++) {
            unsigned long long v = 0;
#pragma unroll 1
            for (uint32_t n = 0; n < (1u << 19); n++) {
                asm volatile("ld.relaxed.gpu.global.u64 %0, [%1];" : "=l"(v) : "l"(p + k * 64) : "memory");
                if ((uint32_t)(v >> 32) == epoch) break;
                __nanosleep(200);
            }
            s += __uint_as_float((uint32_t)v);
        }
        (r ? var : mean) = s * (1.0f / kL);
    }
    const float a = __bfloat162float(gamma[64 * db + c]) / sqrtf(var + 1e-5f), be = __bfloat162float(beta[64 * db + c]);
    for (int l = tid >> 6; l < lim; l += 2)
        out[((size_t)b * kL + row0 + l) * 512 + 64 * db + c] = __float2bfloat16(gelu_half(0.5f * fmaf(h[l * 64 + c] - mean, a, be)));
    named_bar(bar, 128);
}

__device__ __forceinline__ int tail_block(uint32_t gr, int t) { return 4 * (t >> 1) + ((gr >> 4) & 2) + (t & 1); }
__device__ __forceinline__ void tail_poll(uint8_t* sp, uint32_t gr, int t) {
#pragma unroll 1
    for (uint32_t n = 0; n < (1u << 15); n++) {
        unsigned v;
        asm volatile("ld.relaxed.gpu.global.u32 %0, [%1];" : "=r"(v) : "l"(y_flag(sp, gr >> 6, tail_block(gr, t))) : "memory");
        if (v >= 32) break;
        __nanosleep(YSLEEP);
    }
    asm volatile("fence.acquire.gpu;" ::: "memory");
    asm volatile("fence.proxy.async.global;" ::: "memory");
}
__device__ __forceinline__ void tail_loads(uint32_t sbase, const uint8_t* sp, uint32_t gr, uint32_t pmask, int u0, int u1, int lane) {
    if (lane >= u0 && lane < u1) {
        const uint32_t bar = sbase + OFF_BAR + B_UNIT + 8 * lane;
        mbar_expect_tx(bar, 8192);
        bulk_g2s(sbase + (lane < 10 ? OFF_U0 : OFF_U1 - 81920) + lane * 8192, sp + y_unit(tail_block(gr, lane / 5), (gr & 31) * 5 + lane % 5, gr >> 6, pmask), 8192, bar);
    }
    __syncwarp();
}
__device__ __forceinline__ const float* corr_src(uint32_t gr, int t) { return &g_corr[(((gr >> 6) * 8 + tail_block(gr, t)) * kNT + (gr & 31) * 5) * 64]; }
__device__ __forceinline__ void corr_load(uint32_t sbase, uint32_t gr, int t, uint32_t bar) {
    bulk_g2s(sbase + (t < 2 ? OFF_C0 : OFF_C1) + (t & 1) * 1280, corr_src(gr, t), 1280, bar);
}
__device__ __forceinline__ void tail_phase(uint32_t sbase, uint8_t* smem, uint8_t* sp, int wg, uint32_t gr, float sx, float sw, const __nv_bfloat16* __restrict__ x,
                                           const __nv_bfloat16* __restrict__ wt, const __nv_bfloat16* __restrict__ gamma,
                                           const __nv_bfloat16* __restrict__ beta, __nv_bfloat16* __restrict__ out) {
    const uint32_t* ts = reinterpret_cast<const uint32_t*>(smem + OFF_TS);
    const int tid = threadIdx.x, w = (tid >> 5) & 3, lane = tid & 31, g = lane >> 2, q = lane & 3;
    const int b = gr >> 6, part = gr & 31;
#pragma unroll 1
    for (int rd = 0; rd < 4 - wg; rd++) {
        if (rd < 2) {
            float acc[28], acc2[28], s[8] = {0.f, 0.f, 0.f, 0.f, 0.f, 0.f, 0.f, 0.f};
            const float swq = q == 0 ? sw : 0.f;
            const uint32_t ub = sbase + (rd ? OFF_U1 : OFF_U0) + wg * 40960, ubar = sbase + OFF_BAR + B_UNIT + 80 * rd + 40 * wg;
            const float* c1 = reinterpret_cast<const float*>(smem + (rd ? OFF_C1 : OFF_C0) + wg * 1280) + 16 * w + g;
            const uint32_t ka = ub + (lane >> 4) * 1024 + (lane & 7) * 128 + (((2 * w + ((lane >> 3) & 1)) ^ (lane & 7)) << 4);
            auto inverse = [&](float (&d)[28], int u) {
                const uint32_t dA = desc_lo(ub + u * 8192), dB = desc_lo(sbase + OFF_F);
                wg_fence();
                wgmma_n56_ss<0>(d, dA, dB);
                wgmma_n56_ss<1>(d, dA + 128, dB + 2);
                wgmma_n56_ss<1>(d, dA + 256, dB + 4);
                wgmma_n56_ss<1>(d, dA + 384, dB + 6);
                wg_commit();
            };
            auto keep = [&](float (&d)[28], int u, int un) {
                const bool ok = mbar_try(ubar + 8 * un, 0);
                reg_fence(d);
                d[25] = fmaf(c1[u * 64] * sx, swq, d[25]);
                d[27] = fmaf(c1[u * 64 + 8] * sx, swq, d[27]);
                if (part == 31 && u == 4) {
                    if (q >= 2) d[16] = d[18] = 0.f;
                    if (q >= 1) d[17] = d[19] = 0.f;
#pragma unroll
                    for (int i = 20; i < 28; i++) d[i] = 0.f;
                }
                const uint32_t a = ka + u * 8192;
#pragma unroll
                for (int j = 0; j < 6; j += 2)
                    stmatrix_x4_t(a + j * 1024, pack_f16(d[4 * j], d[4 * j + 1]), pack_f16(d[4 * j + 2], d[4 * j + 3]),
                                  pack_f16(d[4 * j + 4], d[4 * j + 5]), pack_f16(d[4 * j + 6], d[4 * j + 7]));
                asm volatile("stmatrix.sync.aligned.m8n8.x2.trans.shared.b16 [%0], {%1,%2};"
                             ::"r"(a + 6 * 1024), "r"(pack_f16(d[24], d[25])), "r"(pack_f16(d[26], d[27])) : "memory");
#pragma unroll
                for (int i = 0; i < 28; i++) {
                    s[i & 3] += d[i];
                    s[4 + (i & 3)] = fmaf(d[i], d[i], s[4 + (i & 3)]);
                }
#pragma unroll
                for (int i = 0; i < 8; i++) asm volatile("" : "+f"(s[i]));
                if (!ok) mbar_wait(ubar + 8 * un, 0);
                wg_wait<0>();
            };
            if (rd) mbar_wait(sbase + OFF_BAR + B_C1, 0);
            mbar_wait(ubar, 0);
            inverse(acc, 0);
            mbar_wait(ubar + 8, 0);
            wg_wait<0>();
#pragma unroll 1
            for (int u = 0;; u += 2) {
                inverse(acc2, min(u + 1, 4));
                keep(acc, u, min(u + 2, 4));
                if (u == 4) break;
                inverse(acc, u + 2);
                keep(acc2, u + 1, min(u + 3, 4));
            }
#pragma unroll
            for (int i = 0; i < 8; i += 2) {
                s[i] += s[i + 1];
                s[i] += __shfl_xor_sync(0xffffffffu, s[i], 1);
                s[i] += __shfl_xor_sync(0xffffffffu, s[i], 2);
            }
            const float mine = q == 0 ? s[0] : q == 1 ? s[2] : q == 2 ? s[4] : s[6];
            asm volatile("red.relaxed.gpu.global.add.u64 [%0], %1;"
                         ::"l"(part_sums(sp, b, tail_block(gr, 2 * rd + wg), ts[76]) + 2 * (16 * w + 8 * (q & 1) + g) + (q >> 1)),
                         "l"(fabsf(mine) < 0x1p25f ? __float2ll_rn(mine * 0x1p21f) * 4096 + 1 : 65ll) : "memory");
            __syncwarp();
            if (lane == 0) mbar_arrive(sbase + OFF_BAR + B_SUM + 8 * (2 * rd + wg));
            if (rd == 0) continue;
        }
        const int t = rd == 3 ? 3 : 2 * rd - 2 + wg, db = tail_block(gr, t), i0 = rd == 3 ? FCUT : 0, i1 = rd == 2 && wg ? FCUT : 256;
#pragma unroll 1
        for (uint32_t n = 0; n < (1u << 20); n++)
            if (mbar_try(sbase + OFF_BAR + B_NRM + 8 * t, 0)) break;
        if (reinterpret_cast<const volatile uint32_t*>(ts)[77 + t]) {
            if (rd < 3) direct_block(x, wt, gamma, beta, out, reinterpret_cast<float*>(smem + OFF_DIR + wg * 8192), b, db, part, ts[76]);
            continue;
        }
        const int jh = g & 1, r0 = 4 * w;
        const int lim = min(250, kL - part * 250) - r0 - (g >> 1);
        float na[8], nb[8];
#pragma unroll
        for (int i = 0; i < 8; i += 2) {
            const float4 v = reinterpret_cast<const float4*>(smem + OFF_GB)[32 * t + 16 * jh + 2 * i + q];
            na[i] = v.x; nb[i] = v.y; na[i + 1] = v.z; nb[i + 1] = v.w;
        }
        __nv_bfloat16* o = out + ((size_t)b * kL + part * 250 + i0 + r0 + (g >> 1)) * 512 + 64 * db + 32 * jh + 8 * q;
        const int row = i0 + r0 + ((lane >> 1) & 3);
        int l = row % kMO;
        uint32_t ra = sbase + (t < 2 ? OFF_U0 : OFF_U1) + (t & 1) * 40960 + row / kMO * 8192 + l * 128;
        const int cc = 4 * (lane & 1) + (lane >> 3);
        auto fetch = [&](uint32_t (&r)[4]) {
            asm volatile("ldmatrix.sync.aligned.m8n8.x4.shared.b16 {%0,%1,%2,%3}, [%4];"
                         : "=r"(r[0]), "=r"(r[1]), "=r"(r[2]), "=r"(r[3]) : "r"(ra + (((cc ^ l) & 7) << 4)) : "memory");
            const bool wrap = l >= kMO - 16;
            l += wrap ? 16 - kMO : 16;
            ra += wrap ? 2048 + 8192 - kMO * 128 : 2048;
        };
        auto gelu8 = [&](const uint32_t (&r)[4], uint32_t (&p)[4]) {
#pragma unroll
            for (int i = 0; i < 4; i++) {
                float lo, hi;
                asm("{\n.reg .b16 a, b;\nmov.b32 {a, b}, %2;\ncvt.f32.f16 %0, a;\ncvt.f32.f16 %1, b;\n}" : "=f"(lo), "=f"(hi) : "r"(r[i]));
                p[i] = pack_bf16(gelu_half(fmaf(lo, na[2 * i], nb[2 * i])), gelu_half(fmaf(hi, na[2 * i + 1], nb[2 * i + 1])));
            }
        };
        uint32_t r[2][4], rn[2][4];
        fetch(r[0]);
        fetch(r[1]);
#pragma unroll 1
        for (int i = i0; i < i1; i += 32) {
            fetch(rn[0]);
            fetch(rn[1]);
            uint32_t p0[4], p1[4];
            gelu8(r[0], p0);
            gelu8(r[1], p1);
            if (i < lim) stg128(o, p0[0], p0[1], p0[2], p0[3]);
            if (i + 16 < lim) stg128(o + 16 * 512, p1[0], p1[1], p1[2], p1[3]);
            o += 32 * 512;
#pragma unroll
            for (int k = 0; k < 4; k++) { r[0][k] = rn[0][k]; r[1][k] = rn[1][k]; }
        }
    }
}
__device__ __forceinline__ void channel_scales(uint32_t sbase, uint8_t* smem, uint8_t* sp, int lane) {
    volatile uint32_t* ts = reinterpret_cast<volatile uint32_t*>(smem + OFF_TS);
    const uint32_t gr = ts[64], bars = sbase + OFF_BAR;
#pragma unroll 1
    for (int t = 0; t < 4; t++) {
#pragma unroll 1
        for (uint32_t n = 0; n < (1u << 20); n++)
            if (mbar_try(bars + B_SUM + 8 * t, 0)) break;
        long long s[4];
#pragma unroll 1
        for (uint32_t n = 0; n < (1u << 19); n++) {
            const unsigned long long* p = part_sums(sp, gr >> 6, tail_block(gr, t), ts[76]) + 4 * lane;
#pragma unroll
            for (int i = 0; i < 4; i++) asm volatile("ld.relaxed.gpu.global.u64 %0, [%1];" : "=l"(s[i]) : "l"(p + i) : "memory");
            if (__all_sync(0xffffffffu, s[0] & s[1] & s[2] & s[3] & 32)) break;
        }
        const float sx = __uint_as_float(ts[74]), sw = __uint_as_float(ts[75]);
        bool bad = false;
#pragma unroll
        for (int i = 0; i < 2; i++) {
            const float mean = (float)(s[2 * i] >> 12) * (0x1p-21f / kL), sq = (float)(s[2 * i + 1] >> 12) * (0x1p-21f / kL);
            float2* gb = reinterpret_cast<float2*>(smem + OFF_GB) + 64 * t + 2 * lane + i;
            const float den = fmaxf(sq - mean * mean, 0.f) + 1e-5f * sx * sw * sx * sw, a = gb->x * rsqrtf(den);
            *gb = make_float2(0.5f * a, 0.5f * (gb->y - mean * a));
            bad |= ((s[2 * i] | s[2 * i + 1]) & 0xFC0) || !(den >= 0x1p-22f);
        }
        bad = __any_sync(0xffffffffu, bad);
        if (lane == 0) ts[77 + t] = bad;
        __syncwarp();
        if (lane == 0) mbar_arrive(bars + B_NRM + 8 * t);
    }
}

__device__ __forceinline__ void publish_tiles(uint8_t* sp, uint32_t bars, int cta, int wg) {
#pragma unroll 1
    for (int m = 0; m < 2; m++) {
        mbar_wait(bars + B_YS + 8 * (2 * m + wg), 0);
        asm volatile("fence.acq_rel.gpu;" ::: "memory");
        red_relaxed(y_flag(sp, (cta >> 1) & 1, 4 * m + 2 * (cta & 1) + wg));
    }
}

__global__ void __launch_bounds__(384, 1)
main_kernel(const __grid_constant__ CUtensorMap tmx, const __grid_constant__ CUtensorMap tmw0, const __grid_constant__ CUtensorMap tmw1,
            const __nv_bfloat16* __restrict__ x, const __nv_bfloat16* __restrict__ wt, const __nv_bfloat16* __restrict__ gamma,
            const __nv_bfloat16* __restrict__ beta, __nv_bfloat16* __restrict__ out) {
    extern __shared__ __align__(1024) uint8_t smem_raw[];
    const uint32_t sbase = smem_u32(smem_raw) & ~1023u;
    const uint32_t bars = sbase + OFF_BAR;
    const int tid = threadIdx.x, wg = __shfl_sync(0xffffffffu, tid >> 7, 0), lane = tid & 31;
    const int cta = blockIdx.x;
    volatile uint32_t* ts = reinterpret_cast<volatile uint32_t*>(smem_raw + OFF_TS);
    uint8_t* const sp = reinterpret_cast<uint8_t*>((reinterpret_cast<uintptr_t>(g_sp) + (2u << 20) - 1) & ~(uintptr_t)((2u << 20) - 1));
    const bool probing = (cta & 3) == 0 && lane == 0 && tid < 128 && (tid >= 64 || cta < 4 * NPAGES);
    unsigned* pw = reinterpret_cast<unsigned*>(sp + (tid < 64 ? ((cta >> 2) << 21) + ((tid & 32) ? 15 : 13) * 4096
                                                              : ((tid & 32) ? 0 : 14) * 4096 + (cta >> 2) * 128));
    unsigned pv = 0;
    if (probing) {
        stg128(pw, 0, 0, 0, 0);
        stg128(pw + 4, 0, 0, 0, 0);
        asm volatile("atom.relaxed.gpu.global.exch.b32 %0, [%1], %2;" : "=r"(pv) : "l"(pw), "r"(7) : "memory");
    }
    if (tid == 320) bar_setup<0, B_SIG>(bars);
    if (tid >= 256 && tid < 262) ts[68 + tid - 256] = tid < 260 ? 0xffffu : 0;
    if (tid == 383) asm volatile("griddepcontrol.launch_dependents;");
    __syncthreads();

    if (wg == 2) {
        asm volatile("setmaxnreg.dec.sync.aligned.u32 40;");
        const int role = (tid >> 5) & 3;
        if (role == 3) {
            unsigned v = 0;
#pragma unroll 1
            for (uint32_t n = 0; n < (1u << 15); n++) {
                asm volatile("ld.relaxed.gpu.global.u32 %0, [%1];" : "=r"(v) : "l"(&g_tsel[lane]) : "memory");
                if (__all_sync(0xffffffffu, v & 16)) break;
                __nanosleep(TSLEEP);
            }
            const uint32_t m1 = __ballot_sync(0xffffffffu, v & 8), below = (1u << lane) - 1;
            const int rank = (v & 8) ? 32 - __popc(m1) + __popc(m1 & below) : __popc(~m1 & below);
            ts[lane] = rank;
            ts[32 + rank] = lane;
            const uint32_t p0 = __ballot_sync(0xffffffffu, v & 1);
            if (lane == 0) ts[66] = p0;
            if (lane == (cta >> 2)) ts[64] = rank * 4 + (cta & 3);
            const int part = (m1 >> (cta >> 2)) & 1;
            __syncwarp();
            if (lane == 0) { mbar_arrive(bars + B_TSEL); }
            mbar_wait(bars + B_TSEL, 0);
            mbar_wait(bars + B_PUB, 0);
            int gc = 0;
            const int gend = lane == 0 ? 33 : lane == 1 ? 32 : 0;
#pragma unroll 1
            for (uint32_t n = 0; n < (1u << 16) && __any_sync(0xffffffffu, gc < gend); n++) {
                asm volatile("ld.relaxed.gpu.global.u32 %0, [%1];" : "=r"(v) : "l"(chunk_flag(sp, lane == 1, part, min(gc, 32 - (lane & 1)))) : "memory");
                if (gc < gend && v >= NCTA) {
                    asm volatile("fence.acquire.gpu;" ::: "memory");
                    mbar_arrive(bars + (lane == 0 ? B_RDY : B_GATE) + 8 * gc);
                    gc++;
                }
            }
            if (lane == 0) publish_tiles(sp, bars, cta, 1);
        } else if (role == 0) {
            const int b = (cta >> 1) & 1, dq = cta & 1;
            for (int v = 0; v < V0; v++) {
                mbar_wait(bars + B_EMPTY + 8 * (v % NST), ((v / NST) & 1) ^ 1);
                if (lane == 0) {
                    mbar_arrive(bars + B_FULL + 8 * (v % NST));
                    mbar_arrive(bars + B_FULL + 8 * (v % NST));
                }
            }
            mbar_wait(bars + B_TSEL, 0);
            const uint32_t gr = ts[64], grp = gr >> 6, idx = (gr >> 2) & 15, pmask = ts[66];
            const uint32_t n0 = idx * 4 + 2 * dq + ((lane & 1) ^ 1), r0 = lane < 3 ? idx * 4 + b : R_W + n0 / 3;
            const uint32_t base = (r0 << 16) + 4096 + ((lane < 3 ? lane : n0 % 3) << 14), step = (lane < 3 ? 64 : 22) << 16;
            uint32_t sels = 0;
            for (int i = 0; i < 12; i++) sels |= run_sel(r0 + i * (step >> 16), grp, pmask) << i;
            int ld = 0;
            const uint32_t bytes = lane == 2 ? XB - 16384 : 8192;
#pragma unroll 1
            for (int h = 0; h < 64; h++) {
                const int s = step_k(h), st = (h + V0) % NST;
                const bool newx = h < HEND ? !(h & 1) : h < HEND + 4;
                const uint32_t fb = bars + B_FULL + 8 * st;
                const uint32_t k = lane < 3 ? (s >> 1) % RX : (h + RW - 64 % RW) % RW, half = lane < 3 ? s & 1 : 0;
                const uint8_t* gsrc = sp + (base + k * step + (half << 17) + ((((sels >> k) ^ half) & 1) << 13));
                const uint32_t dst = sbase + (lane < 3 ? OFF_X + (s & 3) * XB + lane * 8192 : st * 8192 + (lane == 3 ? OFF_W0 : OFF_W1));
                auto landed = [&]() {
                    if (ld < h && mbar_test(bars + B_FULL + 8 * ((ld + V0) % NST), ((ld + V0) / NST) & 1)) {
                        if (!(ld & 1) && lane < 2) red_relaxed(chunk_flag(sp, 1, lane, ld >> 1));
                        ld++;
                    }
                };
                if ((h & 1) || h == 0) {
#pragma unroll 1
                    for (uint32_t n = 0; n < (1u << 19) && !mbar_test(bars + B_RDY + 8 * ((h + 1) >> 1), 0); n++) landed();
                    asm volatile("fence.proxy.async.global;" ::: "memory");
                }
#pragma unroll 1
                for (uint32_t n = 0; n < (1u << 19) && !mbar_test(bars + B_EMPTY + 8 * st, (((h + V0) / NST) & 1) ^ 1); n++) landed();
#pragma unroll 1
                for (uint32_t n = 0; n < (1u << 19) && ld <= h - NST; n++) landed();
                if (lane == 0) mbar_expect_tx(fb, newx ? 16384 + XB : 16384);
                __syncwarp();
                if (lane < 3 ? newx : lane < 5) bulk_g2s(dst, gsrc, bytes, fb);
            }
#pragma unroll 1
            for (; ld < 63; ld++) {
                mbar_wait(bars + B_FULL + 8 * ((ld + V0) % NST), ((ld + V0) / NST) & 1);
                if (!(ld & 1) && lane < 2) red_relaxed(chunk_flag(sp, 1, lane, ld >> 1));
            }
            tail_poll(sp, gr, 0);
            mbar_wait(bars + B_T2, 0);
            tail_loads(sbase, sp, gr, pmask, 0, 5, lane);
            tail_poll(sp, gr, 1);
            tail_loads(sbase, sp, gr, pmask, 5, 8, lane);
            mbar_wait(bars + B_YS + 16, 0);
            tail_loads(sbase, sp, gr, pmask, 8, 10, lane);
            mbar_wait(bars + B_T2 + 8, 0);
            if (lane == 0) {
                mbar_expect_tx(bars + B_C1, 2560);
                corr_load(sbase, gr, 2, bars + B_C1);
                corr_load(sbase, gr, 3, bars + B_C1);
            }
            tail_poll(sp, gr, 2);
            tail_loads(sbase, sp, gr, pmask, 10, 15, lane);
            tail_poll(sp, gr, 3);
            tail_loads(sbase, sp, gr, pmask, 15, 20, lane);
            mbar_wait(bars + B_GATE + 8 * 31, 0);
            unsigned exits = 0;
            if (lane == 0) exits = atomicAdd(&g_exit, 1);
            if (__shfl_sync(0xffffffffu, exits, 0) == NCTA - 1) {
                for (int i = 0; i < 4; i++) *chunk_flag(sp, i >> 1, i & 1, lane) = 0;
                if (lane < 2) *chunk_flag(sp, 0, lane, 32) = 0;
                g_tsel[lane] = 0;
                if (lane < 16) *y_flag(sp, lane >> 3, lane & 7) = 0;
                if (lane == 0) { g_exit = 0; g_epoch = ts[76]; }
            }
        } else if (role == 1) {
            auto raw_load = [&](int r, int h, uint32_t gr, uint32_t dst, uint32_t bar) {
                if (r >= 0) {
                    const int u = r * NCTA + cta, i = u % XPC, b = i >= kNT;
                    tma3d(dst, &tmx, u / XPC * 64, (i - b * kNT) * kMO, b, bar);
                } else if (h >= 0) {
                    const int c = 32 * step_k(h) + ((gr >> 1) & 30);
                    tma3d_ef(dst, c < 512 ? &tmw0 : &tmw1, step_m(h) * 256 + (gr & 3) * 64, 0, c & 511, bar);
                }
            };
            uint32_t gr;
            {
                const int v = lane >> 1, r = v < V0 ? x_round(v, lane & 1) : -1, h = v < V0 ? w_step(v, lane & 1) : -1;
                const uint32_t dst = pre_slot(sbase, v, lane & 1), bar = bars + B_PRE + 8 * lane;
                if (r >= 0 || h >= 0) mbar_expect_tx(bar, r >= 0 ? 8192 : 4096);
                if (v < PRE1) raw_load(r, -1, 0, dst, bar);
                mbar_wait(bars + B_TSEL, 0);
                gr = ts[64];
                raw_load(-1, h, gr, dst, bar);
                if (v >= PRE1) raw_load(r, -1, 0, dst, bar);
                __syncwarp();
            }
            mbar_wait(bars + B_PUB, 0);
#pragma unroll 1
            for (int v = V0; v < V0 + 64; v++) {
                mbar_wait(bars + B_EMPTY + 8 * (v % NST), ((v / NST) & 1) ^ 1);
                __syncwarp();
                const int r = lane < 2 ? x_round(v, lane) : -1, h = lane < 2 ? w_step(v, lane) : -1;
                const uint32_t fb = bars + B_FULL + 8 * (v % NST);
                const uint32_t bytes = __reduce_add_sync(0xffffffffu, r >= 0 ? 8192 : h >= 0 ? 4096 : 0);
                if (lane == 0) mbar_expect_tx(fb, bytes);
                __syncwarp();
                raw_load(r, h, gr, raw_slot(sbase, v, lane), fb);
                if (v >= 20 && v < 40) {
                    const int t = (v - 20) / 5, i = (v - 20) % 5 * 32 + lane, db = 4 * (t >> 1) + 2 * (cta & 1) + (t & 1);
                    ts[(OFF_YT - OFF_TS) / 4 + t * kNT + i] = y_unit(db, i, (cta >> 1) & 1, ts[66]);
                }
                if (v == 66 && lane == 0) {
#pragma unroll 1
                    for (uint32_t n = 0; n < (1u << 15); n++) {
                        unsigned c0, c1;
                        asm volatile("ld.relaxed.gpu.global.u32 %0, [%1];" : "=r"(c0) : "l"(&g_cready[(gr >> 6) * 64]) : "memory");
                        asm volatile("ld.relaxed.gpu.global.u32 %0, [%1];" : "=r"(c1) : "l"(&g_cready[(gr >> 6) * 64 + 32]) : "memory");
                        if (c0 == ts[76] && c1 == ts[76]) break;
                        __nanosleep(500);
                    }
                    asm volatile("fence.acquire.gpu;" ::: "memory");
                    asm volatile("fence.proxy.async.global;" ::: "memory");
                    mbar_expect_tx(bars + B_FTAB, 8192 + 2560);
                    bulk_g2s(sbase + OFF_F, g_tab.inv, 8192, bars + B_FTAB);
                    for (int t = 0; t < 2; t++) {
                        corr_load(sbase, gr, t, bars + B_FTAB);
                        asm volatile("cp.async.bulk.prefetch.L2.global [%0], 1280;" ::"l"(corr_src(gr, 2 + t)) : "memory");
                    }
                }
            }
            channel_scales(sbase, smem_raw, sp, lane);
        } else {
            uint32_t epoch;
            if (lane == 0) {
                bar_setup<B_SIG, B_END>(bars);
                mbar_arrive(bars + B_TSEL);
            }
            asm volatile("ld.relaxed.gpu.global.u32 %0, [%1];" : "=r"(epoch) : "l"(&g_epoch) : "memory");
            mbar_wait(bars + B_TSEL, 0);
            const uint32_t gr = ts[64];
#pragma unroll
            for (int i = lane; i < 256; i += 32) {
                const int d = 64 * tail_block(gr, i >> 6) + (i & 33) + 8 * ((i >> 1) & 3) + 2 * ((i >> 3) & 3);
                ts[(OFF_GB - OFF_TS) / 4 + 2 * i] = (uint32_t)__bfloat16_as_ushort(gamma[d]) << 16;
                ts[(OFF_GB - OFF_TS) / 4 + 2 * i + 1] = (uint32_t)__bfloat16_as_ushort(beta[d]) << 16;
            }
            if (lane == 0) ts[76] = epoch + 1;
            if (cta < 32) stg128(part_sums(sp, cta >> 4, (cta >> 1) & 7, epoch) + (cta & 1) * 64 + 2 * lane, 0, 0, 0, 0);
            __syncwarp();
            if (lane) return;
#pragma unroll 1
            for (int gc = 0; gc < 33;) {
                mbar_wait(bars + B_SIG + 8 * gc, 0);
                if (gc < MERGE) mbar_wait(bars + B_SIG + 8 * MERGE, 0);
                int ge = gc + 1;
                while (ge < 33 && mbar_test(bars + B_SIG + 8 * ge, 0)) ge++;
                asm volatile("fence.acq_rel.gpu;" ::: "memory");
                for (; gc < ge; gc++) {
                    red_relaxed(chunk_flag(sp, 0, 0, gc));
                    red_relaxed(chunk_flag(sp, 0, 1, gc));
                    if (gc == 0) mbar_arrive(bars + B_PUB);
                }
            }
            publish_tiles(sp, bars, cta, 0);
        }
    } else {
        asm volatile("setmaxnreg.inc.sync.aligned.u32 232;");
        uint4 fw[2];
#pragma unroll
        for (int j = 0; j < 2; j++) fw[j] = __ldg(reinterpret_cast<const uint4*>(g_tab.fwd) + tid + 256 * j);
        if (wg == 1) {
            uint4 sm[8];
#pragma unroll
            for (int j = 0; j < 4; j++) {
                const int r = 2 * j + ((tid >> 6) & 1);
                sm[j] = __ldg(reinterpret_cast<const uint4*>(x) + ((r >> 2) * kRows + 1000 + 2000 * (r & 3)) * 128 + (((j + r) & 1) << 6) + (tid & 63));
                sm[4 + j] = __ldg(reinterpret_cast<const uint4*>(wt) + (4 * r * 512 + 67 * r + 7) * 64 + (tid & 63));
            }
#pragma unroll
            for (int k = 0; k < 2; k++) {
                uint32_t mx = 0;
#pragma unroll
                for (int j = 4 * k; j < 4 * k + 4; j++)
                    mx = __vmaxu2(__vmaxu2(mx, __vmaxu2(sm[j].x & 0x7FFF7FFFu, sm[j].y & 0x7FFF7FFFu)), __vmaxu2(sm[j].z & 0x7FFF7FFFu, sm[j].w & 0x7FFF7FFFu));
                mx = __reduce_max_sync(0xffffffffu, max(mx & 0xFFFFu, mx >> 16));
                if (lane == 0) atomicMax(const_cast<uint32_t*>(ts) + 72 + k, mx);
            }
        }
        if ((cta & 3) == 0) {
            if (probing) {
                const int w = tid >> 5;
                unsigned best = 0xffffu;
#pragma unroll 1
                for (int r = 0; r < 6; r++) {
                    unsigned t0, t1;
                    asm volatile("{\n.reg .pred p;\nsetp.eq.u32 p, %1, 0xffffffff;\nmov.u32 %0, 0;\n@!p mov.u32 %0, %%clock;\n}"
                                 : "=r"(t0) : "r"(pv) : "memory");
                    asm volatile("atom.relaxed.gpu.global.exch.b32 %0, [%1], %2;" : "=r"(pv) : "l"(pw), "r"(r) : "memory");
                    asm volatile("{\n.reg .pred p;\nsetp.eq.u32 p, %1, 0xffffffff;\nmov.u32 %0, 0;\n@!p mov.u32 %0, %%clock;\n}"
                                 : "=r"(t1) : "r"(pv) : "memory");
                    ts[68 + w] = best = min(best, t1 - t0);
                    const unsigned other = ts[68 + (w ^ 1)];
                    if (min(best, other) < PROBE_NEAR && max(best, other) > PROBE_NEAR) break;
                }
            }
            if (wg == 0) {
                named_bar(2, 128);
                if (tid == 0) {
                    const uint32_t part = ts[71] < ts[70];
                    const uint32_t v = 16 | (part << 3) | ((ts[69] < ts[68]) ^ part);
                    asm volatile("st.relaxed.gpu.global.u32 [%0], %1;" ::"l"(&g_tsel[cta >> 2]), "r"(v) : "memory");
                }
            }
        }
        uint32_t plan = tid < 2 * (V0 + 65) ? plan_word(tid >> 1, tid & 1, cta) : 0;
        {
            named_bar(1, 256);
            const uint32_t ex = min(max(251 - (int)(ts[72] >> 7), 8), 187), ew = min(max(251 - (int)(ts[73] >> 7), 8), 187);
            if (tid == 0) { ts[74] = ex << 23; ts[75] = ew << 23; }
            const uint32_t sx = ex * 0x800080u, sw = ew * 0x800080u;
#pragma unroll
            for (int j = 0; j < 2; j++) {
                const int i = tid + 256 * j, row = i >> 3, c = (i ^ row) & 7;
                sts128(sbase + OFF_F + 16 * i, mul_bf16x2(fw[j].x, sx), mul_bf16x2(fw[j].y, sx), mul_bf16x2(fw[j].z, sx), mul_bf16x2(fw[j].w, sx));
                if (c < 2) sts128(sbase + OFF_TMP + row * 32 + c * 16, mul_bf16x2(fw[j].x, sw), mul_bf16x2(fw[j].y, sw), mul_bf16x2(fw[j].z, sw), mul_bf16x2(fw[j].w, sw));
            }
            named_bar(1, 256);
        }
        const int t = tid & 127;
        Xf f;
        f.sbase = sbase; f.lane = lane; f.xsw = cta & 4; f.dw = desc_lo(sbase + (wg ? OFF_W1 : OFF_W0));
        {
            const int w = t >> 5;
            const uint32_t nw = (8 * (w & 1) + (lane >> 2)) * 4 + (cta & 3), rw = R_W + nw / 3;
            f.pw = sp + (rw << 16) + 4096 + ((nw % 3) << 14) + (w >> 1) * 128;
            f.cw = ((lane & 7) ^ (w >> 1)) << 4;
            for (int i = 0; i < RW; i++) f.cw |= run_sel(rw + i * 22, 0, 0) << (8 + i);
            mbar_wait(bars + B_TSEL, 0);
            const uint32_t gr = ts[64], pmask = ts[66];
            const uint32_t rx = ts[8 * w + (lane >> 2)];
            f.px = sp + ((rx & 15) << 18) + 4096;
            f.cx = ((lane & 7) << 4) | ((((pmask >> ((rx >> 3) & 1)) ^ -(((rx >> 1) ^ (rx >> 4)) & 1)) & 0x55) << 8);
#pragma unroll
            for (int i = 0; i < RW; i++) f.cw ^= (((pmask >> ((rw + i * 22) >> 5)) ^ (gr >> 6)) & 1) << (8 + i);
            if (plan & 4) plan |= ((gr & 12) << 8) | ((gr & 48) << 4) | ((gr & 48) << 1);
            if (tid < 2 * (V0 + 65)) ts[(OFF_PLAN - OFF_TS) / 4 + tid] = plan;
            const int row = tid >> 2, ch = tid & 3, s = ts[32 + (gr >> 6) * 16 + ((row >> 1) & 8) + (row & 7)], p = (row >> 3) & 1;
            const int frow = 16 * (s >> 3) + 8 * p + (s & 7);
            uint32_t v[4] = {0, 0, 0, 0};
            if ((ch >> 1) == (row >> 5))
                asm volatile("ld.shared.v4.b32 {%0,%1,%2,%3}, [%4];" : "=r"(v[0]), "=r"(v[1]), "=r"(v[2]), "=r"(v[3])
                             : "r"(sbase + OFF_TMP + frow * 32 + (ch & 1) * 16) : "memory");
            sts128(sbase + OFF_G + row * 64 + ((ch ^ ((row >> 1) & 3)) << 4), v[0], v[1], v[2], v[3]);
            fence_proxy_async_smem();
            named_bar(1, 256);
        }
        {
            float at[32];
#pragma unroll 1
            for (uint32_t v = 0; v < V0; v++) {
                const uint32_t e = plan_load(f, v, wg), raw = pre_slot(sbase, v, wg);
                mbar_wait(bars + B_FULL + 8 * (v % NST), (v / NST) & 1);
                if (e & 6) mbar_wait(bars + B_PRE + 16 * v + 8 * wg, 0);
                if (v == PAUSE) mbar_wait(bars + B_PUB, 0);
                wg_fence();
                if ((e & 6) == 2) {
                    unit_mma<false>(at, f, raw);
                    wg_wait<0>();
                    unit_store<false>(at, f, e);
                } else if (e & 4) {
                    unit_mma<true>(at, f, raw);
                    wg_wait<0>();
                    unit_store<true>(at, f, e);
                }
                if (lane == 0) mbar_arrive(bars + B_EMPTY + 8 * (v % NST));
                unit_done(f, e, v);
            }
        }
        const int slot = cta >> 2;
        f.e = plan_load(f, V0, wg);
        uint32_t a0[40], a1[40], b0[40], b1[40];
#pragma unroll
        for (int i = 0; i < 40; i++) a0[i] = a1[i] = b0[i] = b1[i] = 0;
        if (slot == 0) gemm_main<true>(a0, a1, b0, b1, f, wg);
        else gemm_main<false>(a0, a1, b0, b1, f, wg);
        const uint32_t gr = __shfl_sync(0xffffffffu, ts[64], 0);
        const float sx = __uint_as_float(ts[74]), sw = __uint_as_float(ts[75]);
        uint32_t wr[2][4][4];
        w_fetch(wr[0], f, V0 + HEND);
#pragma unroll 1
        for (int m = 0; m < 2; m++) {
            if (slot == 0) gemm_last<true>(a0, a1, wr, f, wg, m);
            else gemm_last<false>(a0, a1, wr, f, wg, m);
            reg_fence(a0);
            reg_fence(a1);
            const int wsw = gr & 4;
            mbar_wait(bars + B_GATE + 8 * y_gate(2 * m + wg), 0);
            if (m) mbar_wait(bars + B_FTAB, 0);
            const uint32_t ytab = sbase + OFF_YT + (m * 2 + wg) * (kNT * 4);
            store_tile(a0, a1, b0, b1, wr[0], f, m == 0, sbase + OFF_STG + wg * 16384, t, wg, sp, slot, ytab, wsw);
            __syncwarp();
            if (lane == 0) mbar_arrive(bars + B_YS + 8 * (2 * m + wg));
        }
        tail_phase(sbase, smem_raw, sp, wg, gr, sx, sw, x, wt, gamma, beta, out);
    }
}

constexpr int C_STAGE = 32768 + 2 * XB, C_SMEM = 3 * C_STAGE + 64;
__global__ void __launch_bounds__(256, 1) corr_kernel(const __grid_constant__ CUtensorMap tmx, const __grid_constant__ CUtensorMap tmw) {
    extern __shared__ __align__(1024) uint8_t smem_raw[];
    const uint32_t sbase = smem_u32(smem_raw) & ~1023u, bars = sbase + 3 * C_STAGE;
    const int tid = threadIdx.x, wg = __shfl_sync(0xffffffffu, tid >> 7, 0), b = blockIdx.x >> 1, dh = blockIdx.x & 1;
    auto load = [&](int k) {
        const uint32_t st = sbase + (k % 3) * C_STAGE, bar = bars + 8 * (k % 3);
        mbar_expect_tx(bar, C_STAGE);
        for (int i = 0; i < 4; i++) tma2d(st + i * 8192, &tmw, 256 * dh + 64 * i, 64 * k, bar);
        tma4d(st + 32768, &tmx, 64 * k, 64 - kMO, 1, b, bar);
        tma4d(st + 32768 + XB, &tmx, 64 * k, 0, 0, b, bar);
    };
    uint32_t epoch = 0;
    if (tid == 0) {
        for (int i = 0; i < 3; i++) mbar_init(bars + 8 * i, 1);
        fence_mbar_init();
        fence_proxy_async_smem();
        for (int k = 0; k < 3; k++) load(k);
        asm volatile("ld.relaxed.gpu.global.u32 %0, [%1];" : "=r"(epoch) : "l"(&g_epoch) : "memory");
    }
    __syncthreads();
    float a[2][80];
#pragma unroll
    for (int i = 0; i < 80; i++) a[0][i] = a[1][i] = 0.f;
#pragma unroll 1
    for (int k = 0; k < 8; k++) {
        const uint32_t dA = desc_lo(sbase + (k % 3) * C_STAGE + wg * 16384), dB = desc_lo(sbase + (k % 3) * C_STAGE + 32768);
        mbar_wait(bars + 8 * (k % 3), (k / 3) & 1);
        wg_fence();
#pragma unroll
        for (int i = 0; i < 8; i++) {
            wgmma_n160_f<1>(a[i & 1], dA + (i & 1) * 512 + (i >> 1) * 128, dB + (i >> 1) * 2);
            wgmma_n160_f<-1>(a[i & 1], dA + (i & 1) * 512 + (i >> 1) * 128, dB + XB / 16 + (i >> 1) * 2);
        }
        wg_commit();
        wg_wait<0>();
        __syncthreads();
        if (tid == 0 && k + 3 < 8) load(k + 3);
    }
    reg_fence(a[0]);
    reg_fence(a[1]);
    const int w = (tid >> 5) & 3, g = (tid & 31) >> 2, q = tid & 3;
#pragma unroll
    for (int i = 0; i < 160; i++) {
        const int m = i / 80, j = i % 80, d = 16 * w + 8 * ((j >> 1) & 1) + g;
        g_corr[((b * 8 + 4 * dh + 2 * wg + m) * kNT + 8 * (j >> 2) + 2 * q + (j & 1)) * 64 + (d & 33) + 8 * ((d >> 1) & 3) + 2 * ((d >> 3) & 3)] = a[m][j];
    }
    __syncthreads();
    if (tid == 0) {
        asm volatile("fence.acq_rel.gpu;" ::: "memory");
        asm volatile("st.relaxed.gpu.global.u32 [%0], %1;" ::"l"(&g_cready[blockIdx.x * 32]), "r"(epoch + 1) : "memory");
    }
}

__global__ void __launch_bounds__(256) plain_conv(const __nv_bfloat16* __restrict__ x, const __nv_bfloat16* __restrict__ w) {
    __shared__ float xs[64][17], ws[16][65];
    float* h = g_direct;
    const int b = blockIdx.z, l0 = blockIdx.x * 64, d0 = blockIdx.y * 64, tx = threadIdx.x & 15, ty = threadIdx.x >> 4;
    float acc[4][4] = {};
    for (int k0 = 0; k0 < 31 * 512; k0 += 16) {
        for (int i = threadIdx.x; i < 1024; i += 256) {
            const int l = min(l0 + (i >> 4), kL - 1);
            xs[i >> 4][i & 15] = __bfloat162float(x[((size_t)b * kRows + l) * 1024 + k0 + (i & 15)]);
            ws[i >> 6][i & 63] = __bfloat162float(w[(size_t)(k0 + (i >> 6)) * 512 + d0 + (i & 63)]);
        }
        __syncthreads();
        for (int k = 0; k < 16; k++)
            for (int i = 0; i < 4; i++)
                for (int j = 0; j < 4; j++) acc[i][j] = fmaf(xs[ty * 4 + i][k], ws[k][tx * 4 + j], acc[i][j]);
        __syncthreads();
    }
    for (int i = 0; i < 4; i++)
        for (int j = 0; j < 4; j++)
            if (l0 + ty * 4 + i < kL) h[((size_t)b * kL + l0 + ty * 4 + i) * 512 + d0 + tx * 4 + j] = acc[i][j];
}
__global__ void __launch_bounds__(256) plain_norm(const __nv_bfloat16* __restrict__ gamma, const __nv_bfloat16* __restrict__ beta,
                                                  __nv_bfloat16* __restrict__ out) {
    __shared__ float s1[8][32], s2[8][32];
    const int c = threadIdx.x & 31, r = threadIdx.x >> 5, d = blockIdx.x * 32 + c;
    const float* h = g_direct + (size_t)blockIdx.y * kL * 512 + d;
    float a = 0.f, q = 0.f;
    for (int l = r; l < kL; l += 8) { const float v = h[(size_t)l * 512]; a += v; q = fmaf(v, v, q); }
    s1[r][c] = a; s2[r][c] = q;
    __syncthreads();
    a = q = 0.f;
    for (int i = 0; i < 8; i++) { a += s1[i][c]; q += s2[i][c]; }
    const float mean = a * (1.0f / kL), sc = __bfloat162float(gamma[d]) / sqrtf(fmaxf(q * (1.0f / kL) - mean * mean, 0.f) + 1e-5f);
    const float sh = __bfloat162float(beta[d]) - mean * sc;
    for (int l = r; l < kL; l += 8)
        out[((size_t)blockIdx.y * kL + l) * 512 + d] = __float2bfloat16(gelu_half(0.5f * fmaf(h[(size_t)l * 512], sc, sh)));
}

typedef CUresult (*EncodeTiledFn)(CUtensorMap*, CUtensorMapDataType, cuuint32_t, void*, const cuuint64_t*, const cuuint64_t*,
                                  const cuuint32_t*, const cuuint32_t*, CUtensorMapInterleave, CUtensorMapSwizzle,
                                  CUtensorMapL2promotion, CUtensorMapFloatOOBfill);

void encode(EncodeTiledFn fn, CUtensorMap* tm, const void* ptr, int rank, const cuuint64_t* dims, const cuuint64_t* strides,
            const cuuint32_t* box, CUtensorMapL2promotion promo, CUtensorMapSwizzle swz = CU_TENSOR_MAP_SWIZZLE_128B) {
    const cuuint32_t es[5] = {1, 1, 1, 1, 1};
    fn(tm, CU_TENSOR_MAP_DATA_TYPE_BFLOAT16, rank, const_cast<void*>(ptr), dims, strides, box, es, CU_TENSOR_MAP_INTERLEAVE_NONE,
       swz, promo, CU_TENSOR_MAP_FLOAT_OOB_FILL_NONE);
}

}

extern "C" void kernel_launch(void* const* d_in, const int* in_sizes, int n_in, void* d_out, int out_size) {
    const __nv_bfloat16* x = (const __nv_bfloat16*)d_in[0];
    const __nv_bfloat16* w = (const __nv_bfloat16*)d_in[1];
    const __nv_bfloat16* gamma = (const __nv_bfloat16*)d_in[2];
    const __nv_bfloat16* beta = (const __nv_bfloat16*)d_in[3];
    static EncodeTiledFn enc = nullptr;
    static int resident = 0;
    if (!enc) {
        void* fn = nullptr;
        cudaDriverEntryPointQueryResult qr;
        cudaGetDriverEntryPoint("cuTensorMapEncodeTiled", &fn, cudaEnableDefault, &qr);
        enc = (EncodeTiledFn)fn;
        cudaFuncSetAttribute(main_kernel, cudaFuncAttributeMaxDynamicSharedMemorySize, MAIN_SMEM);
        cudaFuncSetAttribute(corr_kernel, cudaFuncAttributeMaxDynamicSharedMemorySize, C_SMEM);
        int dev = 0, per_sm = 0;
        cudaGetDevice(&dev);
        cudaDeviceGetAttribute(&resident, cudaDevAttrMultiProcessorCount, dev);
        cudaOccupancyMaxActiveBlocksPerMultiprocessor(&per_sm, main_kernel, 384, MAIN_SMEM);
        resident *= per_sm;
    }
    if (resident < NCTA + 4) {
        plain_conv<<<dim3((kL + 63) / 64, 8, 2), 256>>>(x, w);
        plain_norm<<<dim3(16, 2), 256>>>(gamma, beta, (__nv_bfloat16*)d_out);
        return;
    }
    CUtensorMap tmx, tmw0, tmw1, tmcx, tmcw;
    {
        const cuuint64_t dims[3] = {1024, kRows, 2}, strides[2] = {2048, (cuuint64_t)kRows * 2048};
        const cuuint32_t box[3] = {64, 64, 1};
        encode(enc, &tmx, x, 3, dims, strides, box, CU_TENSOR_MAP_L2_PROMOTION_L2_128B);
    }
    {
        const cuuint64_t dims0[3] = {512, 16, 512}, dims1[3] = {512, 15, 512}, strides[2] = {2 * 512 * 512 * 2, 1024};
        const cuuint32_t box[3] = {64, 16, 2};
        encode(enc, &tmw0, w, 3, dims0, strides, box, CU_TENSOR_MAP_L2_PROMOTION_L2_128B);
        encode(enc, &tmw1, w + 512 * 512, 3, dims1, strides, box, CU_TENSOR_MAP_L2_PROMOTION_L2_128B);
    }
    {
        const cuuint64_t dims[4] = {512, kMO, kNT, 2}, strides[3] = {2048, kMO * 2048, (cuuint64_t)kRows * 2048};
        const cuuint32_t box[4] = {64, 1, kNT, 1};
        encode(enc, &tmcx, x, 4, dims, strides, box, CU_TENSOR_MAP_L2_PROMOTION_L2_128B);
        const cuuint64_t dimw[2] = {512, 512}, stridew[1] = {1024};
        const cuuint32_t boxw[2] = {64, 64};
        encode(enc, &tmcw, w + 30 * 512 * 512, 2, dimw, stridew, boxw, CU_TENSOR_MAP_L2_PROMOTION_L2_128B);
    }
    main_kernel<<<NCTA, 384, MAIN_SMEM>>>(tmx, tmw0, tmw1, x, w, gamma, beta, (__nv_bfloat16*)d_out);
    cudaLaunchConfig_t cfg = {};
    cudaLaunchAttribute at[1];
    cfg.gridDim = 4;
    cfg.blockDim = 256;
    cfg.dynamicSmemBytes = C_SMEM;
    at[0].id = cudaLaunchAttributeProgrammaticStreamSerialization;
    at[0].val.programmaticStreamSerializationAllowed = 1;
    cfg.attrs = at;
    cfg.numAttrs = 1;
    cudaLaunchKernelEx(&cfg, corr_kernel, tmcx, tmcw);
}
```

```cpp
#include <cuda_runtime.h>
#include <cuda_bf16.h>
#include <cuda.h>
#include <stdint.h>

namespace {

constexpr int kL    = 7985;
constexpr int kRows = 8000;
constexpr int kMO   = 50;
constexpr int kNT   = 160;

constexpr int V0 = 7;
constexpr int NPRE = 6;
constexpr int RX = 4;
constexpr int FCUT = 128;
constexpr int PAUSE = 5;
constexpr int YSLEEP = 100;
constexpr int PRE1 = 4;
constexpr int TSLEEP = 200;
constexpr int MERGE = 1;
constexpr int RW = 10;

static_assert(V0 >= 7 && V0 <= 9 && RX >= 2 && RX <= 4 && RW >= V0 - 1 && RW <= 12, "rings must fit and be as deep as the look-ahead");
constexpr uint32_t HOME_MASK = 0xB;
constexpr uint32_t R_W = 64 * RX, NPAGES = (R_W + 22 * RW + 31) / 32;

__device__ __align__(1024) uint8_t g_sp[(size_t)(NPAGES + 1) * (2u << 20)];
__device__ __align__(128) unsigned g_tsel[32];
__device__ __forceinline__ uint32_t run_sel(uint32_t r, uint32_t group, uint32_t pmask) {
    return ((pmask >> (r >> 5)) ^ __popc(r & HOME_MASK) ^ group) & 1;
}
__device__ __forceinline__ uint32_t run_off(uint32_t r, uint32_t run, uint32_t group, uint32_t pmask) {
    return (r << 16) + 4096 + (run_sel(r, group, pmask) << 13) + (run << 14);
}
__device__ __forceinline__ unsigned* chunk_flag(uint8_t* sp, int done, int part, int chunk) {
    return reinterpret_cast<unsigned*>(sp + (4 + 3 * (chunk >> 5)) * 65536 + (done ? (part ? 15 : 13) : (part ? 0 : 14)) * 4096 + (chunk & 31) * 128);
}
__device__ __forceinline__ unsigned long long* part_sums(uint8_t* sp, int b, int db, uint32_t epoch) {
    return reinterpret_cast<unsigned long long*>(sp + (8 + 2 * db + ((__popc((8 + 2 * db) & HOME_MASK) ^ b) & 1)) * 65536 + 13 * 4096 + (epoch & 1) * 1024);
}
__device__ __forceinline__ unsigned* y_flag(uint8_t* sp, int b, int db) { return reinterpret_cast<unsigned*>(part_sums(sp, b, db, 0) + 512); }
__device__ __align__(256) float g_corr[16 * kNT * 64];
__device__ unsigned g_cready[4 * 32];
__device__ float g_direct[512 * 250 * 64];
__device__ unsigned long long g_dpart[2 * 512 * 64];
__device__ unsigned g_exit, g_epoch;

__device__ __forceinline__ uint32_t smem_u32(const void* p) { return (uint32_t)__cvta_generic_to_shared(p); }

__device__ __forceinline__ void mbar_init(uint32_t bar, uint32_t count) {
    asm volatile("mbarrier.init.shared::cta.b64 [%0], %1;" ::"r"(bar), "r"(count) : "memory");
}
__device__ __forceinline__ void mbar_expect_tx(uint32_t bar, uint32_t bytes) {
    asm volatile("mbarrier.arrive.expect_tx.shared::cta.b64 _, [%0], %1;" ::"r"(bar), "r"(bytes) : "memory");
}
__device__ __forceinline__ void mbar_arrive(uint32_t bar) {
    asm volatile("mbarrier.arrive.shared::cta.b64 _, [%0];" ::"r"(bar) : "memory");
}
__device__ __forceinline__ bool mbar_try(uint32_t bar, uint32_t parity) {
    uint32_t ok;
    asm volatile(
        "{\n.reg .pred p;\n"
        "mbarrier.try_wait.parity.shared::cta.b64 p, [%1], %2;\n"
        "selp.u32 %0, 1, 0, p;\n}\n"
        : "=r"(ok) : "r"(bar), "r"(parity) : "memory");
    return ok;
}
__device__ __forceinline__ bool mbar_test(uint32_t bar, uint32_t parity) {
    uint32_t ok;
    asm volatile(
        "{\n.reg .pred p;\n"
        "mbarrier.test_wait.parity.shared::cta.b64 p, [%1], %2;\n"
        "selp.u32 %0, 1, 0, p;\n}\n"
        : "=r"(ok) : "r"(bar), "r"(parity) : "memory");
    return ok;
}
__device__ __forceinline__ void mbar_wait(uint32_t bar, uint32_t parity) {
#pragma unroll 1
    for (uint32_t n = 0; n < (1u << 14); n++)
        if (mbar_try(bar, parity)) break;
}
__device__ __forceinline__ void fence_proxy_async_smem() { asm volatile("fence.proxy.async.shared::cta;" ::: "memory"); }
__device__ __forceinline__ void fence_mbar_init() { asm volatile("fence.mbarrier_init.release.cluster;" ::: "memory"); }

__device__ __forceinline__ void bulk_g2s(uint32_t dst, const void* src, uint32_t bytes, uint32_t bar) {
    asm volatile("cp.async.bulk.shared::cluster.global.mbarrier::complete_tx::bytes [%0], [%1], %2, [%3];"
                 ::"r"(dst), "l"(src), "r"(bytes), "r"(bar) : "memory");
}
__device__ __forceinline__ void bulk_g2s_ef(uint32_t dst, const void* src, uint32_t bytes, uint32_t bar) {
    asm volatile("{\n.reg .b64 pol;\ncreatepolicy.fractional.L2::evict_first.b64 pol, 1.0;\n"
                 "cp.async.bulk.shared::cluster.global.mbarrier::complete_tx::bytes.L2::cache_hint [%0], [%1], %2, [%3], pol;\n}"
                 ::"r"(dst), "l"(src), "r"(bytes), "r"(bar) : "memory");
}
__device__ __forceinline__ void tma3d_ef(uint32_t dst, const CUtensorMap* tm, int c0, int c1, int c2, uint32_t bar) {
    asm volatile("{\n.reg .b64 pol;\ncreatepolicy.fractional.L2::evict_first.b64 pol, 1.0;\n"
                 "cp.async.bulk.tensor.3d.shared::cluster.global.mbarrier::complete_tx::bytes.L2::cache_hint [%0], [%1, {%3, %4, %5}], [%2], pol;\n}"
                 ::"r"(dst), "l"(tm), "r"(bar), "r"(c0), "r"(c1), "r"(c2) : "memory");
}
__device__ __forceinline__ void tma3d(uint32_t dst, const CUtensorMap* tm, int c0, int c1, int c2, uint32_t bar) {
    asm volatile("cp.async.bulk.tensor.3d.shared::cluster.global.mbarrier::complete_tx::bytes [%0], [%1, {%3, %4, %5}], [%2];"
                 ::"r"(dst), "l"(tm), "r"(bar), "r"(c0), "r"(c1), "r"(c2) : "memory");
}
__device__ __forceinline__ void poll_ge(const unsigned* p, unsigned target) {
#pragma unroll 1
    for (uint32_t n = 0; n < (1u << 15); n++) {
        unsigned v;
        asm volatile("ld.acquire.gpu.global.u32 %0, [%1];" : "=r"(v) : "l"(p) : "memory");
        if (v >= target) break;
        __nanosleep(32);
    }
}
__device__ __forceinline__ void red_relaxed(unsigned* p) { asm volatile("red.relaxed.gpu.global.add.u32 [%0], 1;" ::"l"(p) : "memory"); }
__device__ __forceinline__ void named_arrive(int id, int n) { asm volatile("bar.arrive %0, %1;" ::"r"(id), "r"(n) : "memory"); }
__device__ __forceinline__ void named_bar(int id, int n) { asm volatile("bar.sync %0, %1;" ::"r"(id), "r"(n) : "memory"); }

__device__ __forceinline__ void wg_fence() { asm volatile("wgmma.fence.sync.aligned;" ::: "memory"); }
__device__ __forceinline__ void wg_commit() { asm volatile("wgmma.commit_group.sync.aligned;" ::: "memory"); }
template <int N> __device__ __forceinline__ void wg_wait() { asm volatile("wgmma.wait_group.sync.aligned %0;" ::"n"(N) : "memory"); }
template <int N> __device__ __forceinline__ void reg_fence(float (&d)[N]) {
#pragma unroll
    for (int i = 0; i < N; i++) asm volatile("" : "+f"(d[i])::"memory");
}

#define F4(a, i) "+f"(a[i]), "+f"(a[i + 1]), "+f"(a[i + 2]), "+f"(a[i + 3])
#define F8(a, i) F4(a, i), F4(a, i + 4)
#define F16(a, i) F8(a, i), F8(a, i + 8)

constexpr uint32_t HI128 = 0x40000040u, HI64 = 0x80000020u;
__device__ __forceinline__ uint32_t desc_lo(uint32_t addr) { return (addr >> 4) | 0x10000u; }


#define R4(a, i) "+r"(a[i]), "+r"(a[i + 1]), "+r"(a[i + 2]), "+r"(a[i + 3])
#define R8(a, i) R4(a, i), R4(a, i + 4)
template <int N> __device__ __forceinline__ void reg_fence(uint32_t (&d)[N]) {
#pragma unroll
    for (int i = 0; i < N; i++) asm volatile("" : "+r"(d[i])::"memory");
}
__device__ __forceinline__ void tma2d(uint32_t dst, const CUtensorMap* tm, int c0, int c1, uint32_t bar) {
    asm volatile("cp.async.bulk.tensor.2d.shared::cluster.global.mbarrier::complete_tx::bytes [%0], [%1, {%3, %4}], [%2];"
                 ::"r"(dst), "l"(tm), "r"(bar), "r"(c0), "r"(c1) : "memory");
}
__device__ __forceinline__ void tma4d(uint32_t dst, const CUtensorMap* tm, int c0, int c1, int c2, int c3, uint32_t bar) {
    asm volatile("cp.async.bulk.tensor.4d.shared::cluster.global.mbarrier::complete_tx::bytes [%0], [%1, {%3, %4, %5, %6}], [%2];"
                 ::"r"(dst), "l"(tm), "r"(bar), "r"(c0), "r"(c1), "r"(c2), "r"(c3) : "memory");
}
__device__ __forceinline__ bool named_bar_or(int id, int n, bool v) {
    uint32_t r;
    asm volatile("{\n.reg .pred p, q;\nsetp.ne.u32 q, %3, 0;\nbar.red.or.pred p, %1, %2, q;\nselp.u32 %0, 1, 0, p;\n}"
                 : "=r"(r) : "r"(id), "r"(n), "r"((uint32_t)v) : "memory");
    return r;
}

template <uint32_t AHI, int ACC>
__device__ __forceinline__ void wgmma_n64_ss(float (&d)[32], uint32_t da, uint32_t db) {
    asm volatile(
        "{\n.reg .pred p;\n.reg .b64 da, db;\nsetp.ne.b32 p, %36, 0;\nmov.b64 da, {%32, %34};\nmov.b64 db, {%33, %35};\n"
        "wgmma.mma_async.sync.aligned.m64n64k16.f32.bf16.bf16 "
        "{%0,%1,%2,%3,%4,%5,%6,%7,%8,%9,%10,%11,%12,%13,%14,%15,%16,%17,%18,%19,%20,%21,%22,%23,%24,%25,%26,%27,%28,%29,%30,%31},"
        "da, db, p, 1, 1, 0, 1;\n}\n"
        : F16(d, 0), F16(d, 16)
        : "r"(da), "r"(db), "n"(AHI), "n"(HI128), "n"(ACC));
}


template <int ACC>
__device__ __forceinline__ void wgmma_n56_ss(float (&d)[28], uint32_t da, uint32_t db) {
    asm volatile(
        "{\n.reg .pred p;\n.reg .b64 da, db;\nsetp.ne.b32 p, %31, 0;\nmov.b64 da, {%28, %30};\nmov.b64 db, {%29, %30};\n"
        "wgmma.mma_async.sync.aligned.m64n56k16.f32.f16.f16 "
        "{%0,%1,%2,%3,%4,%5,%6,%7,%8,%9,%10,%11,%12,%13,%14,%15,%16,%17,%18,%19,%20,%21,%22,%23,%24,%25,%26,%27},"
        "da, db, p, 1, 1, 1, 0;\n}\n"
        : F16(d, 0), F8(d, 16), F4(d, 24)
        : "r"(da), "r"(db), "n"(HI128), "n"(ACC));
}

template <int SA>
__device__ __forceinline__ void wgmma_n160_h(uint32_t (&d)[40], uint32_t da, uint32_t db) {
    asm volatile(
        "{\n.reg .pred p;\n.reg .b64 da, db;\nsetp.eq.b32 p, 0, 0;\nmov.b64 da, {%40, %43};\nmov.b64 db, {%41, %43};\n"
        "wgmma.mma_async.sync.aligned.m64n160k16.f16.f16.f16 "
        "{%0,%1,%2,%3,%4,%5,%6,%7,%8,%9,%10,%11,%12,%13,%14,%15,%16,%17,%18,%19,%20,%21,%22,%23,%24,%25,%26,%27,"
        "%28,%29,%30,%31,%32,%33,%34,%35,%36,%37,%38,%39},"
        "da, db, p, %42, 1, 1, 0;\n}\n"
        : R8(d, 0), R8(d, 8), R8(d, 16), R8(d, 24), R8(d, 32)
        : "r"(da), "r"(db), "n"(SA), "n"(HI128));
}
template <int SA>
__device__ __forceinline__ void wgmma_n160_hr(uint32_t (&d)[40], const uint32_t (&a)[4], uint32_t db) {
    asm volatile(
        "{\n.reg .pred p;\n.reg .b64 db;\nsetp.eq.b32 p, 0, 0;\nmov.b64 db, {%44, %46};\n"
        "wgmma.mma_async.sync.aligned.m64n160k16.f16.f16.f16 "
        "{%0,%1,%2,%3,%4,%5,%6,%7,%8,%9,%10,%11,%12,%13,%14,%15,%16,%17,%18,%19,%20,%21,%22,%23,%24,%25,%26,%27,"
        "%28,%29,%30,%31,%32,%33,%34,%35,%36,%37,%38,%39},"
        "{%40,%41,%42,%43}, db, p, %45, 1, 0;\n}\n"
        : R8(d, 0), R8(d, 8), R8(d, 16), R8(d, 24), R8(d, 32)
        : "r"(a[0]), "r"(a[1]), "r"(a[2]), "r"(a[3]), "r"(db), "n"(SA), "n"(HI128));
}
template <int SA>
__device__ __forceinline__ void wgmma_n160_f(float (&d)[80], uint32_t da, uint32_t db) {
    asm volatile(
        "{\n.reg .pred p;\n.reg .b64 da, db;\nsetp.eq.b32 p, 0, 0;\nmov.b64 da, {%80, %83};\nmov.b64 db, {%81, %83};\n"
        "wgmma.mma_async.sync.aligned.m64n160k16.f32.bf16.bf16 "
        "{%0,%1,%2,%3,%4,%5,%6,%7,%8,%9,%10,%11,%12,%13,%14,%15,%16,%17,%18,%19,%20,%21,%22,%23,%24,%25,%26,%27,"
        "%28,%29,%30,%31,%32,%33,%34,%35,%36,%37,%38,%39,%40,%41,%42,%43,%44,%45,%46,%47,%48,%49,%50,%51,%52,%53,%54,%55,"
        "%56,%57,%58,%59,%60,%61,%62,%63,%64,%65,%66,%67,%68,%69,%70,%71,%72,%73,%74,%75,%76,%77,%78,%79},"
        "da, db, p, %82, 1, 1, 0;\n}\n"
        : F16(d, 0), F16(d, 16), F16(d, 32), F16(d, 48), F16(d, 64)
        : "r"(da), "r"(db), "n"(SA), "n"(HI128));
}

__device__ __forceinline__ uint32_t pack_f16(float lo, float hi) {
    uint32_t r;
    asm("cvt.rn.f16x2.f32 %0, %1, %2;" : "=r"(r) : "f"(hi), "f"(lo));
    return r;
}
__device__ __forceinline__ uint32_t mul_bf16x2(uint32_t a, uint32_t b) {
    uint32_t r;
    asm("mul.rn.bf16x2 %0, %1, %2;" : "=r"(r) : "r"(a), "r"(b));
    return r;
}
__device__ __forceinline__ void sts128(uint32_t p, uint32_t a, uint32_t b, uint32_t c, uint32_t d) {
    asm volatile("st.shared.v4.b32 [%0], {%1,%2,%3,%4};" ::"r"(p), "r"(a), "r"(b), "r"(c), "r"(d) : "memory");
}
__device__ __forceinline__ uint32_t pack_bf16(float lo, float hi) {
    uint32_t r;
    asm("cvt.rn.bf16x2.f32 %0, %1, %2;" : "=r"(r) : "f"(hi), "f"(lo));
    return r;
}
__device__ __forceinline__ void stg128(void* p, uint32_t a, uint32_t b, uint32_t c, uint32_t d) {
    asm volatile("st.global.v4.b32 [%0], {%1,%2,%3,%4};" ::"l"(p), "r"(a), "r"(b), "r"(c), "r"(d) : "memory");
}
__device__ __forceinline__ void stmatrix_x4_t(uint32_t addr, uint32_t a, uint32_t b, uint32_t c, uint32_t d) {
    asm volatile("stmatrix.sync.aligned.m8n8.x4.trans.shared.b16 [%0], {%1,%2,%3,%4};"
                 ::"r"(addr), "r"(a), "r"(b), "r"(c), "r"(d) : "memory");
}

constexpr uint32_t cos64(int k, bool half) {
    constexpr uint16_t q[17] = {0x3F80, 0x3F7F, 0x3F7B, 0x3F75, 0x3F6D, 0x3F62, 0x3F55, 0x3F46, 0x3F35, 0x3F22, 0x3F0E, 0x3EF1, 0x3EC4, 0x3E95, 0x3E48, 0x3DC9, 0x0000};
    constexpr uint16_t h[17] = {0x3C00, 0x3BF6, 0x3BD9, 0x3BA8, 0x3B64, 0x3B0E, 0x3AA7, 0x3A2F, 0x39A8, 0x3913, 0x3872, 0x378B, 0x361F, 0x34A5, 0x323E, 0x2E46, 0x0000};
    k &= 63;
    if (k > 32) k = 64 - k;
    const uint16_t* t = half ? h : q;
    return k <= 16 ? t[k] : (t[32 - k] | 0x8000u);
}
constexpr uint32_t fwd_coef(int s, int p, int t) { return (p && s == 0) ? cos64(32 * t, false) : cos64(s * t - 16 * p, false); }
constexpr uint32_t inv_coef(int l, int phi) {
    const int s = phi >> 1, p = phi & 1;
    if (l >= kMO) return 0;
    const uint32_t c = s == 0 ? cos64(32 * l * p, true) : cos64(s * l + 16 * p, true);
    return (c & 0x7FFF) ? c - ((s == 0 ? 6 : 5) << 10) : 0;
}
struct Tables {
    uint32_t fwd[2048];
    uint32_t inv[2048];
};
constexpr Tables make_tables() {
    Tables t = {};
    for (int i = 0; i < 2048; i++) {
        const int row = i >> 5, tt = 8 * (((i >> 2) & 7) ^ (row & 7)) + 2 * (i & 3), s = 8 * (row >> 4) + (row & 7), p = (row >> 3) & 1;
        t.fwd[i] = fwd_coef(s, p, tt) | (fwd_coef(s, p, tt + 1) << 16);
        t.inv[i] = inv_coef(row, tt) | (inv_coef(row, tt + 1) << 16);
    }
    return t;
}
__device__ __align__(128) const Tables g_tab = make_tables();

constexpr int NCTA = 128;
constexpr int NST = 4;
constexpr int HEND = 56;
constexpr int XB = kNT * 128;
constexpr int OFF_W1 = 0, OFF_X = OFF_W1 + NST * 8192, OFF_W0 = OFF_X + 4 * XB, OFF_RAW = OFF_W0 + NST * 8192;
constexpr int OFF_STG = OFF_RAW + 32768;
constexpr int OFF_U0 = OFF_W0, OFF_U1 = OFF_X, OFF_C1 = OFF_W1, OFF_DIR = OFF_W1 + 8192;
constexpr int OFF_F = OFF_RAW + 65536;
constexpr int OFF_G = OFF_F + 8192;
constexpr int OFF_C0 = OFF_G;
constexpr int OFF_BAR = OFF_G + 4096;
constexpr int B_FULL = 0, B_EMPTY = 8 * NST, B_TSEL = 16 * NST, B_PRE = B_TSEL + 8, B_SIG = B_PRE + 16 * V0, B_YS = B_SIG + 8 * 33,
              B_T2 = B_YS + 8 * 4, B_SUM = B_T2 + 16, B_GATE = B_SUM + 32, B_RDY = B_GATE + 8 * 32, B_PUB = B_RDY + 8 * 33, B_UNIT = B_PUB + 8,
              B_FTAB = B_UNIT + 8 * 20, B_C1 = B_FTAB + 8, B_NRM = B_C1 + 8, B_END = B_NRM + 32;
template <int O0, int O1>
__device__ __forceinline__ void bar_setup(uint32_t bars) {
#pragma unroll
    for (int o = O0; o < O1; o += 8)
        mbar_init(bars + o, o < B_EMPTY ? 2 : o < B_TSEL ? 8 : o == B_TSEL ? 2 : o < B_SIG ? 1 : o < B_YS - 8 ? 8 : o < B_GATE ? 4 : 1);
    fence_mbar_init();
    fence_proxy_async_smem();
}
constexpr int OFF_TS = OFF_BAR + B_END;
constexpr int OFF_PLAN = OFF_TS + 336;
constexpr int OFF_YT = OFF_PLAN + (V0 + 65) * 8;
constexpr int OFF_GB = (OFF_YT + 4 * kNT * 4 + 15) & ~15;
constexpr int MAIN_SMEM = OFF_GB + 2048;
static_assert(MAIN_SMEM <= 232448 && OFF_U0 + 10 * 8192 == OFF_STG + 16384, "shared memory");
constexpr int XPC = 2 * kNT;
constexpr unsigned PROBE_NEAR = 400;

__device__ __forceinline__ uint32_t raw_slot(uint32_t sbase, uint32_t v, int wg) { return sbase + OFF_RAW + ((v & 3) * 2 + wg) * 8192; }

__device__ __forceinline__ uint32_t pre_slot(uint32_t sbase, uint32_t v, int wg) {
    return v < 4 ? raw_slot(sbase, v, wg) : v < 8 ? sbase + OFF_X + (v - 4) * XB + wg * 8192 : sbase + (wg ? OFF_W1 : OFF_W0) + ((V0 + 3) % NST) * 8192;
}
constexpr int OFF_TMP = OFF_W1 + 8192;

template <bool DC, int I>
__device__ __forceinline__ void gemm_mma(uint32_t (&a0)[40], uint32_t (&a1)[40], uint32_t dx0, uint32_t dx1, uint32_t dw) {
    constexpr int ks = I >> 2;
    const uint32_t A0 = dw + ks * 128, A1 = A0 + 256, B0 = dx0 + ks * 2, B1 = dx1 + ks * 2;
    if ((I & 3) == 0) wgmma_n160_h<1>(a0, A0, B0);
    if ((I & 3) == 1) wgmma_n160_h<1>(a1, A1, DC ? B1 : B0);
    if ((I & 3) == 2 && !DC) wgmma_n160_h<1>(a0, A1, B1);
    if ((I & 3) == 3 && !DC) wgmma_n160_h<-1>(a1, A0, B1);
}

template <bool DC, int I0, int I1>
__device__ __forceinline__ void gemm_mmas(uint32_t (&a0)[40], uint32_t (&a1)[40], uint32_t dx0, uint32_t dx1, uint32_t dw) {
    if constexpr (I0 < I1) {
        gemm_mma<DC, I0>(a0, a1, dx0, dx1, dw);
        gemm_mmas<DC, I0 + 1, I1>(a0, a1, dx0, dx1, dw);
    }
}
static_assert(RX == 4 && RW == 10, "placement of the output spectra");
__device__ __forceinline__ uint32_t y_unit(uint32_t db, uint32_t tau, uint32_t b, uint32_t pmask) {
    const uint32_t n = (((db >> 1) & 2) + (db & 1)) * XPC + ((db >> 1) & 1) * kNT + tau, r = n / 3;
    return run_off(r + (r >= 192 && r < 278 ? (r < 214 ? 64 : -22) : 0), n % 3, b, pmask);
}
__device__ __forceinline__ int y_gate(int t) { return t ? 28 + t : 27; }
__device__ __forceinline__ int step_k(int h) { return h < HEND ? h >> 1 : 28 + (h & 3); }
__device__ __forceinline__ int step_m(int h) { return h < HEND ? h & 1 : (h >> 2) & 1; }
constexpr uint64_t x_mask() {
    uint64_t r = 2 | (3ull << 58);
    for (int v = 2; v < 58; v++)
        if ((0x6B >> (v & 7)) & 1) r |= 1ull << v;
    return r ^ 0x18;
}
constexpr uint64_t XMASK = x_mask();
__device__ __forceinline__ int x_round(int v, int wg) {
    return v == 0 ? wg : (v < 60 && wg != (v & 1) && ((XMASK >> v) & 1)) ? 1 + __popcll(XMASK << (63 - v)) : -1;
}
__device__ __forceinline__ int w_step(int v, int wg) {
    return v == 0 ? -1 : v < 60 ? (wg == (v & 1) ? v - 1 : -1) : v < 62 ? 2 * v - 61 + wg : (v == 62 && wg == 0) ? 63 : -1;
}

__device__ __forceinline__ uint32_t plan_word(int v, int wg, int cta) {
    const int r = x_round(v, wg), h = w_step(v, wg);
    if (r < 0 && h < 0) return 0;
    const bool last = v >= 60 || (v & 1) || (v > 0 && wg == 0 && x_round(v + 1, 0) < 0);
    uint32_t off, row, gate;
    if (r >= 0) {
        const int u = r * NCTA + cta, cb = u / XPC, i = u - cb * XPC, b = i >= kNT, tau = i - b * kNT;
        row = tau & 63;
        off = (((cb % RX) * 64 + b) << 16) + ((tau >> 6) << 14) + b + 2;
        gate = cb >= RX ? 2 * (cb - RX) + 2 : 0;
    } else {
        const int ring = (h + RW - 64 % RW) % RW;
        row = 0;
        off = ((ring * 22) << 16) + (ring << 12) + 4;
        gate = h >= RW ? ((h - RW + 1) >> 1) + 1 : 0;
    }
    return (off + row * 128) | ((row & 7) << 4) | (last << 3) | ((v > 60) << 24) | (gate << 26);
}

struct Xf {
    uint32_t sbase;
    uint8_t *px, *pw;
    uint32_t cx, cw;
    uint32_t xsw;
    uint32_t dw;
    uint32_t e;
    int lane;
};
__device__ __forceinline__ uint32_t plan_load(const Xf& f, uint32_t v, int wg) {
    uint32_t e;
    asm volatile("ld.shared.u32 %0, [%1];" : "=r"(e) : "r"(f.sbase + OFF_PLAN + v * 8 + wg * 4));
    return __shfl_sync(0xffffffffu, e, 0);
}
template <bool W>
__device__ __forceinline__ void unit_mma(float (&acc)[32], const Xf& f, uint32_t raw) {
    const uint32_t dB = desc_lo(raw);
    if (W) {
        const uint32_t dG = desc_lo(f.sbase + OFF_G);
        wgmma_n64_ss<HI64, 0>(acc, dG, dB);
        wgmma_n64_ss<HI64, 1>(acc, dG + 2, dB + 128);
    } else {
        const uint32_t dF = desc_lo(f.sbase + OFF_F);
        wgmma_n64_ss<HI128, 0>(acc, dF, dB);
        wgmma_n64_ss<HI128, 1>(acc, dF + 2, dB + 128);
        wgmma_n64_ss<HI128, 1>(acc, dF + 4, dB + 256);
        wgmma_n64_ss<HI128, 1>(acc, dF + 6, dB + 384);
    }
    wg_commit();
}
constexpr int DROP = 3;
__device__ __forceinline__ uint32_t pack_sp(float lo, float hi) {
    const uint32_t r = pack_f16(lo, hi);
    return DROP ? (r + (0x10001u << DROP >> 1)) & ~(((1u << DROP) - 1) * 0x10001u) : r;
}
__device__ __forceinline__ void st_quad(uint8_t* p, const float (&acc)[32], int j0) {
    stg128(p, pack_sp(acc[j0], acc[j0 + 1]), pack_sp(acc[j0 + 4], acc[j0 + 5]), pack_sp(acc[j0 + 8], acc[j0 + 9]),
           pack_sp(acc[j0 + 12], acc[j0 + 13]));
}
template <bool W>
__device__ __forceinline__ void unit_store(float (&acc)[32], const Xf& f, uint32_t e) {
    const uint32_t sel = ((W ? f.cw >> (8 + ((e >> 12) & 15)) : e ^ (f.cx >> (8 + ((e >> 21) & 6)))) & 1) << 13;
    const uint32_t o = (e & (W ? 0xFF0F80u : 0xFFFF80u)) + ((e ^ (W ? f.cw : f.cx)) & 0x70);
    uint8_t* const b = W ? f.pw : f.px;
    uint8_t *p0 = b + (o + sel), *p1 = b + ((o ^ 64) + sel);
    reg_fence(acc);
    if (W) {
        st_quad(p0, acc, 0);
        st_quad(p1, acc, 16);
        st_quad(p0 + 4096, acc, 2);
        st_quad(p1 + 4096, acc, 18);
    } else {
        const int d = 131072 + 8192 - 2 * (int)sel;
        st_quad(p0, acc, 0);
        st_quad(p1, acc, 2);
        st_quad(p0 + d, acc, 16);
        st_quad(p1 + d, acc, 18);
    }
}
__device__ __forceinline__ void unit_done(const Xf& f, uint32_t e, uint32_t v) {
    if (e & 8) {
        __syncwarp();
        if (f.lane == 0) mbar_arrive(f.sbase + OFF_BAR + B_SIG + 8 * ((v >> 1) + ((e >> 24) & 1)));
    }
}
__device__ __forceinline__ void step_wait(Xf& f, uint32_t v, int wg) {
    const uint32_t bars = f.sbase + OFF_BAR;
    if (f.e >> 26) mbar_wait(bars + B_GATE - 8 + 8 * (f.e >> 26), 0);
    mbar_wait(bars + B_FULL + 8 * (v % NST), (v / NST) & 1);
}

template <bool DC, int KIND>
__device__ __forceinline__ void gemm_step(uint32_t (&a0)[40], uint32_t (&a1)[40], float (&at)[32], Xf& f, uint32_t v, uint32_t xs, int wg, bool first) {
    const uint32_t bars = f.sbase + OFF_BAR, sb = desc_lo(f.sbase), xb = sb + OFF_X / 16 + xs * (XB / 16), raw = raw_slot(f.sbase, v, wg);
    const uint32_t dx0 = xb + f.xsw, dx1 = xb + (f.xsw ^ 4), dw = f.dw + (v % NST) * 512, e = f.e;
    wg_fence();
    if (KIND) unit_mma<KIND != 1>(at, f, raw);
    constexpr int N1 = KIND == 0 ? 2 : NPRE;
    gemm_mmas<DC, 0, N1>(a0, a1, dx0, dx1, dw);
    wg_commit();
    f.e = plan_load(f, v + 1, wg);
    wg_wait<1>();
    if (!KIND && !first && f.lane == 0) mbar_arrive(bars + B_EMPTY + 8 * ((v - 1) % NST));
    if (KIND) unit_store<KIND != 1>(at, f, e);
    if (KIND) unit_done(f, e, v);
    gemm_mmas<DC, N1, 7>(a0, a1, dx0, dx1, dw);
    if (KIND && !first && f.lane == 0) mbar_arrive(bars + B_EMPTY + 8 * ((v - 1) % NST));
    gemm_mma<DC, 7>(a0, a1, dx0, dx1, dw);
    wg_commit();
}
template <bool DC>
__device__ __forceinline__ void any_step(uint32_t (&a0)[40], uint32_t (&a1)[40], float (&at)[32], Xf& f, uint32_t v, uint32_t xs, int wg, bool first) {
    step_wait(f, v, wg);
    const uint32_t kind = (f.e >> 1) & 3;
    if (kind == 1) gemm_step<DC, 1>(a0, a1, at, f, v, xs, wg, first);
    else if (kind == 2) gemm_step<DC, 2>(a0, a1, at, f, v, xs, wg, first);
    else gemm_step<DC, 0>(a0, a1, at, f, v, xs, wg, first);
}
template <bool DC>
__device__ __forceinline__ void gemm_main(uint32_t (&a0)[40], uint32_t (&a1)[40], uint32_t (&b0)[40], uint32_t (&b1)[40], Xf& f, int wg) {
    float at[32];
#pragma unroll 1
    for (uint32_t k = 0; k < HEND / 2; k++) {
        any_step<DC>(a0, a1, at, f, V0 + 2 * k, k & 3, wg, k == 0);
        any_step<DC>(b0, b1, at, f, V0 + 2 * k + 1, k & 3, wg, false);
    }
    wg_wait<0>();
    if (f.lane == 0) mbar_arrive(f.sbase + OFF_BAR + B_EMPTY + 8 * ((V0 + HEND - 1) % NST));
}
__device__ __forceinline__ void w_fetch(uint32_t (&d)[4][4], const Xf& f, uint32_t v) {
    const uint32_t bars = f.sbase + OFF_BAR, lane = f.lane;
    const uint32_t wa = ((f.dw & 0xFFFF) << 4) + (v % NST) * 8192 + (lane >> 4) * 1024 + (lane & 7) * 128 +
                        (((((threadIdx.x >> 4) & 6) + ((lane >> 3) & 1)) ^ (lane & 7)) << 4);
    mbar_wait(bars + B_FULL + 8 * (v % NST), (v / NST) & 1);
#pragma unroll
    for (int i = 0; i < 4; i++)
        asm volatile("ldmatrix.sync.aligned.m8n8.x4.trans.shared.b16 {%0,%1,%2,%3}, [%4];" : "=r"(d[i][0]), "=r"(d[i][1]), "=r"(d[i][2]), "=r"(d[i][3])
                     : "r"(wa + i * 2048) : "memory");
}
__device__ __forceinline__ void store_tile(uint32_t (&a0)[40], uint32_t (&a1)[40], const uint32_t (&b0)[40], const uint32_t (&b1)[40], uint32_t (&wn)[4][4],
                                           const Xf& f, bool first, uint32_t stg, int t, int wg, uint8_t* sp, int slot, uint32_t ytab, int wsw) {
    const int w = t >> 5, lane = t & 31, m = lane >> 3, i8 = lane & 7;
    const uint32_t addr = stg + i8 * 256 + (m >> 1) * 128 + (((2 * w + (m & 1)) ^ i8 ^ wsw) << 4);
    const int row = 2 * w + (lane >> 4), phi = 2 * slot + (m & 1);
    const uint32_t src = stg + row * 256 + (m & 1) * 128 + ((i8 ^ row) << 4);
    uint8_t* dst = sp + phi * 128 + ((i8 ^ (phi & 7)) << 4);
    named_bar(2 + wg, 128);
#pragma unroll
    for (int r = 0; r < 6; r++) {
        uint32_t v[4][4], o[4];
        if (r > 0) {
#pragma unroll
            for (int i = 0; i < 4; i++) {
                asm volatile("ld.shared.u32 %0, [%1];" : "=r"(o[i]) : "r"(ytab + (32 * (r - 1) + 8 * i + row) * 4) : "memory");
                asm volatile("ld.shared.v4.b32 {%0,%1,%2,%3}, [%4];" : "=r"(v[i][0]), "=r"(v[i][1]), "=r"(v[i][2]), "=r"(v[i][3])
                             : "r"(src + ((r - 1) & 1) * 8192 + i * 2048) : "memory");
            }
        }
        if (r < 5) {
#pragma unroll
            for (int j = 4 * r; j < 4 * r + 4; j++) stmatrix_x4_t(addr + (r & 1) * 8192 + (j & 3) * 2048, a0[2 * j], a0[2 * j + 1], a1[2 * j], a1[2 * j + 1]);
#pragma unroll
            for (int j = 8 * r; j < 8 * r + 8; j++) {
                asm volatile("mov.b32 %0, %1;" : "=r"(a0[j]) : "r"(b0[j]));
                asm volatile("mov.b32 %0, %1;" : "=r"(a1[j]) : "r"(b1[j]));
            }
        } else if (first) {
            w_fetch(wn, f, V0 + HEND + 4);
        }
        if (r > 0) {
#pragma unroll
            for (int i = 0; i < 4; i++) stg128(dst + o[i], v[i][0], v[i][1], v[i][2], v[i][3]);
        }
        if (r < 5) named_bar(2 + wg, 128);
    }
}

template <bool DC>
__device__ __forceinline__ void gemm_last(uint32_t (&a0)[40], uint32_t (&a1)[40], uint32_t (&w)[2][4][4], const Xf& f, int wg, int m) {
    const uint32_t bars = f.sbase + OFF_BAR, sb = desc_lo(f.sbase), v0 = V0 + HEND + 4 * m;
    if (2 * m + wg > 0) named_bar(3 + 2 * m + wg, 256);
#pragma unroll
    for (uint32_t k = 0; k < 4; k++) {
        const uint32_t xb = sb + OFF_X / 16 + k * (XB / 16), dx0 = xb + f.xsw, dx1 = xb + (f.xsw ^ 4);
        wg_fence();
#pragma unroll
        for (int ks = 0; ks < 2; ks++) {
            wgmma_n160_hr<1>(a0, w[k & 1][ks], dx0 + 2 * ks);
            wgmma_n160_hr<1>(a1, w[k & 1][2 + ks], (DC ? dx1 : dx0) + 2 * ks);
            if (!DC) wgmma_n160_hr<1>(a0, w[k & 1][2 + ks], dx1 + 2 * ks);
            if (!DC) wgmma_n160_hr<-1>(a1, w[k & 1][ks], dx1 + 2 * ks);
        }
        wg_commit();
        if (m == 0 && f.lane == 0) mbar_arrive(bars + B_EMPTY + 8 * ((v0 + k) % NST));
        if (k == 3 && 2 * m + wg < 3) named_arrive(4 + 2 * m + wg, 256);
        if (k > 0) wg_wait<1>();
        if (k < 3) w_fetch(w[(k + 1) & 1], f, v0 + k + 1);
    }
    wg_wait<0>();
    if (m && f.lane == 0) mbar_arrive(bars + B_T2 + 8 * wg);
}

__device__ __forceinline__ float gelu_half(float hv) {
    float th;
    asm("tanh.approx.f32 %0, %1;" : "=f"(th) : "f"(hv * fmaf(hv * hv, 8.0f * 0.7978845608028654f * 0.044715f, 2.0f * 0.7978845608028654f)));
    return fmaf(hv, th, hv);
}
__device__ __noinline__ void direct_block(const __nv_bfloat16* __restrict__ x, const __nv_bfloat16* __restrict__ w,
                                          const __nv_bfloat16* __restrict__ gamma, const __nv_bfloat16* __restrict__ beta,
                                          __nv_bfloat16* __restrict__ out, float* sm, int b, int db, int part, uint32_t epoch) {
    float *xs = sm, *ws = sm + 32 * 17, *red = ws + 16 * 65;
    const int tid = threadIdx.x & 127, bar = 2 + (threadIdx.x >> 7), tx = tid & 15, ty = tid >> 4, row0 = part * 250, lim = min(250, kL - row0);
    float* h = g_direct + (size_t)((b * 8 + db) * 32 + part) * (250 * 64);
    for (int l0 = 0; l0 < lim; l0 += 32) {
        float acc[4][4] = {};
        for (int k0 = 0; k0 < 31 * 512; k0 += 16) {
            named_bar(bar, 128);
            for (int i = tid; i < 1024; i += 128) {
                if (i < 512) xs[(i >> 4) * 17 + (i & 15)] = __bfloat162float(x[((size_t)b * kRows + row0 + min(l0 + (i >> 4), lim - 1)) * 1024 + k0 + (i & 15)]);
                ws[(i >> 6) * 65 + (i & 63)] = __bfloat162float(w[(size_t)(k0 + (i >> 6)) * 512 + 64 * db + (i & 63)]);
            }
            named_bar(bar, 128);
            for (int k = 0; k < 16; k++)
#pragma unroll
                for (int i = 0; i < 4; i++)
#pragma unroll
                    for (int j = 0; j < 4; j++) acc[i][j] = fmaf(xs[(ty * 4 + i) * 17 + k], ws[k * 65 + tx * 4 + j], acc[i][j]);
        }
#pragma unroll
        for (int i = 0; i < 4; i++)
#pragma unroll
            for (int j = 0; j < 4; j++)
                if (l0 + ty * 4 + i < lim) h[(l0 + ty * 4 + i) * 64 + tx * 4 + j] = acc[i][j];
    }
    const int c = tid & 63;
    float mean = 0.f, var = 0.f;
    for (int r = 0; r < 2; r++) {
        named_bar(bar, 128);
        float s = 0.f;
        for (int l = tid >> 6; l < lim; l += 2) {
            const float v = h[l * 64 + c] - mean;
            s += r ? v * v : v;
        }
        red[tid] = s;
        named_bar(bar, 128);
        unsigned long long* p = g_dpart + ((r * 16 + b * 8 + db) * 32) * 64 + c;
        if (tid < 64)
            asm volatile("st.relaxed.gpu.global.v2.b32 [%0], {%1, %2};" ::"l"(p + part * 64), "r"(__float_as_uint(red[c] + red[64 + c])), "r"(epoch) : "memory");
        s = 0.f;
        for (int k = 0; k < 32; k++) {
            unsigned long long v = 0;
#pragma unroll 1
            for (uint32_t n = 0; n < (1u << 19); n++) {
                asm volatile("ld.relaxed.gpu.global.u64 %0, [%1];" : "=l"(v) : "l"(p + k * 64) : "memory");
                if ((uint32_t)(v >> 32) == epoch) break;
                __nanosleep(200);
            }
            s += __uint_as_float((uint32_t)v);
        }
        (r ? var : mean) = s * (1.0f / kL);
    }
    const float a = __bfloat162float(gamma[64 * db + c]) / sqrtf(var + 1e-5f), be = __bfloat162float(beta[64 * db + c]);
    for (int l = tid >> 6; l < lim; l += 2)
        out[((size_t)b * kL + row0 + l) * 512 + 64 * db + c] = __float2bfloat16(gelu_half(0.5f * fmaf(h[l * 64 + c] - mean, a, be)));
    named_bar(bar, 128);
}

__device__ __forceinline__ int tail_block(uint32_t gr, int t) { return 4 * (t >> 1) + ((gr >> 4) & 2) + (t & 1); }
__device__ __forceinline__ void tail_poll(uint8_t* sp, uint32_t gr, int t) {
#pragma unroll 1
    for (uint32_t n = 0; n < (1u << 15); n++) {
        unsigned v;
        asm volatile("ld.relaxed.gpu.global.u32 %0, [%1];" : "=r"(v) : "l"(y_flag(sp, gr >> 6, tail_block(gr, t))) : "memory");
        if (v >= 32) break;
        __nanosleep(YSLEEP);
    }
    asm volatile("fence.acquire.gpu;" ::: "memory");
    asm volatile("fence.proxy.async.global;" ::: "memory");
}
__device__ __forceinline__ void tail_loads(uint32_t sbase, const uint8_t* sp, uint32_t gr, uint32_t pmask, int u0, int u1, int lane) {
    if (lane >= u0 && lane < u1) {
        const uint32_t bar = sbase + OFF_BAR + B_UNIT + 8 * lane;
        mbar_expect_tx(bar, 8192);
        bulk_g2s(sbase + (lane < 10 ? OFF_U0 : OFF_U1 - 81920) + lane * 8192, sp + y_unit(tail_block(gr, lane / 5), (gr & 31) * 5 + lane % 5, gr >> 6, pmask), 8192, bar);
    }
    __syncwarp();
}
__device__ __forceinline__ const float* corr_src(uint32_t gr, int t) { return &g_corr[(((gr >> 6) * 8 + tail_block(gr, t)) * kNT + (gr & 31) * 5) * 64]; }
__device__ __forceinline__ void corr_load(uint32_t sbase, uint32_t gr, int t, uint32_t bar) {
    bulk_g2s(sbase + (t < 2 ? OFF_C0 : OFF_C1) + (t & 1) * 1280, corr_src(gr, t), 1280, bar);
}
__device__ __forceinline__ void tail_phase(uint32_t sbase, uint8_t* smem, uint8_t* sp, int wg, uint32_t gr, float sx, float sw, const __nv_bfloat16* __restrict__ x,
                                           const __nv_bfloat16* __restrict__ wt, const __nv_bfloat16* __restrict__ gamma,
                                           const __nv_bfloat16* __restrict__ beta, __nv_bfloat16* __restrict__ out) {
    const uint32_t* ts = reinterpret_cast<const uint32_t*>(smem + OFF_TS);
    const int tid = threadIdx.x, w = (tid >> 5) & 3, lane = tid & 31, g = lane >> 2, q = lane & 3;
    const int b = gr >> 6, part = gr & 31;
#pragma unroll 1
    for (int rd = 0; rd < 4 - wg; rd++) {
        if (rd < 2) {
            float acc[28], acc2[28], s[8] = {0.f, 0.f, 0.f, 0.f, 0.f, 0.f, 0.f, 0.f};
            const float swq = q == 0 ? sw : 0.f;
            const int t = 2 * rd + wg;
            const uint32_t ub = sbase + (t < 2 ? OFF_U0 : OFF_U1) + (t & 1) * 40960, ubar = sbase + OFF_BAR + B_UNIT + 40 * t;
            const float* c1 = reinterpret_cast<const float*>(smem + (t < 2 ? OFF_C0 : OFF_C1) + (t & 1) * 1280) + 16 * w + g;
            const uint32_t ka = ub + (lane >> 4) * 1024 + (lane & 7) * 128 + (((2 * w + ((lane >> 3) & 1)) ^ (lane & 7)) << 4);
            auto inverse = [&](float (&d)[28], int u) {
                const uint32_t dA = desc_lo(ub + u * 8192), dB = desc_lo(sbase + OFF_F);
                wg_fence();
                wgmma_n56_ss<0>(d, dA, dB);
                wgmma_n56_ss<1>(d, dA + 128, dB + 2);
                wgmma_n56_ss<1>(d, dA + 256, dB + 4);
                wgmma_n56_ss<1>(d, dA + 384, dB + 6);
                wg_commit();
            };
            auto keep = [&](float (&d)[28], int u, int un) {
                const bool ok = mbar_try(ubar + 8 * un, 0);
                reg_fence(d);
                d[25] = fmaf(c1[u * 64] * sx, swq, d[25]);
                d[27] = fmaf(c1[u * 64 + 8] * sx, swq, d[27]);
                if (part == 31 && u == 4) {
                    if (q >= 2) d[16] = d[18] = 0.f;
                    if (q >= 1) d[17] = d[19] = 0.f;
#pragma unroll
                    for (int i = 20; i < 28; i++) d[i] = 0.f;
                }
                const uint32_t a = ka + u * 8192;
#pragma unroll
                for (int j = 0; j < 6; j += 2)
                    stmatrix_x4_t(a + j * 1024, pack_f16(d[4 * j], d[4 * j + 1]), pack_f16(d[4 * j + 2], d[4 * j + 3]),
                                  pack_f16(d[4 * j + 4], d[4 * j + 5]), pack_f16(d[4 * j + 6], d[4 * j + 7]));
                asm volatile("stmatrix.sync.aligned.m8n8.x2.trans.shared.b16 [%0], {%1,%2};"
                             ::"r"(a + 6 * 1024), "r"(pack_f16(d[24], d[25])), "r"(pack_f16(d[26], d[27])) : "memory");
#pragma unroll
                for (int i = 0; i < 28; i++) {
                    s[i & 3] += d[i];
                    s[4 + (i & 3)] = fmaf(d[i], d[i], s[4 + (i & 3)]);
                }
#pragma unroll
                for (int i = 0; i < 8; i++) asm volatile("" : "+f"(s[i]));
                if (!ok) mbar_wait(ubar + 8 * un, 0);
                wg_wait<0>();
            };
            if (t >= 2) mbar_wait(sbase + OFF_BAR + B_C1, 0);
            mbar_wait(ubar, 0);
            inverse(acc, 0);
            mbar_wait(ubar + 8, 0);
            wg_wait<0>();
#pragma unroll 1
            for (int u = 0;; u += 2) {
                inverse(acc2, min(u + 1, 4));
                keep(acc, u, min(u + 2, 4));
                if (u == 4) break;
                inverse(acc, u + 2);
                keep(acc2, u + 1, min(u + 3, 4));
            }
#pragma unroll
            for (int i = 0; i < 4; i++) s[i] = s[2 * i] + s[2 * i + 1];
#pragma unroll
            for (int i = 0; i < 2; i++) s[i] = (q & 2 ? s[2 + i] : s[i]) + __shfl_xor_sync(0xffffffffu, q & 2 ? s[i] : s[2 + i], 2);
            const float mine = (q & 1 ? s[1] : s[0]) + __shfl_xor_sync(0xffffffffu, q & 1 ? s[0] : s[1], 1);
            asm volatile("red.relaxed.gpu.global.add.u64 [%0], %1;"
                         ::"l"(part_sums(sp, b, tail_block(gr, t), ts[76]) + 2 * (16 * w + 8 * (q & 1) + g) + (q >> 1)),
                         "l"(fabsf(mine) < 0x1p25f ? __float2ll_rn(mine * 0x1p21f) * 4096 + 1 : 65ll) : "memory");
            __syncwarp();
            if (lane == 0) mbar_arrive(sbase + OFF_BAR + B_SUM + 8 * t);
            if (rd == 0) continue;
        }
        const int t = rd == 3 ? 3 : 2 * rd - 2 + wg, db = tail_block(gr, t), i0 = rd == 3 ? FCUT : 0, i1 = rd == 2 && wg ? FCUT : 256;
#pragma unroll 1
        for (uint32_t n = 0; n < (1u << 20); n++)
            if (mbar_try(sbase + OFF_BAR + B_NRM + 8 * t, 0)) break;
        if (reinterpret_cast<const volatile uint32_t*>(ts)[77 + t]) {
            if (rd < 3) direct_block(x, wt, gamma, beta, out, reinterpret_cast<float*>(smem + OFF_DIR + wg * 8192), b, db, part, ts[76]);
            continue;
        }
        const int jh = g & 1, r0 = 4 * w;
        const int lim = min(250, kL - part * 250) - r0 - (g >> 1);
        float na[8], nb[8];
#pragma unroll
        for (int i = 0; i < 8; i += 2) {
            const float4 v = reinterpret_cast<const float4*>(smem + OFF_GB)[32 * t + 16 * jh + 2 * i + q];
            na[i] = v.x; nb[i] = v.y; na[i + 1] = v.z; nb[i + 1] = v.w;
        }
        __nv_bfloat16* o = out + ((size_t)b * kL + part * 250 + i0 + r0 + (g >> 1)) * 512 + 64 * db + 32 * jh + 8 * q;
        const int row = i0 + r0 + ((lane >> 1) & 3);
        int l = row % kMO;
        uint32_t ra = sbase + (t < 2 ? OFF_U0 : OFF_U1) + (t & 1) * 40960 + row / kMO * 8192 + l * 128;
        const int cc = 4 * (lane & 1) + (lane >> 3);
        auto fetch = [&](uint32_t (&r)[4]) {
            asm volatile("ldmatrix.sync.aligned.m8n8.x4.shared.b16 {%0,%1,%2,%3}, [%4];"
                         : "=r"(r[0]), "=r"(r[1]), "=r"(r[2]), "=r"(r[3]) : "r"(ra + (((cc ^ l) & 7) << 4)) : "memory");
            const bool wrap = l >= kMO - 16;
            l += wrap ? 16 - kMO : 16;
            ra += wrap ? 2048 + 8192 - kMO * 128 : 2048;
        };
        auto gelu8 = [&](const uint32_t (&r)[4], uint32_t (&p)[4]) {
#pragma unroll
            for (int i = 0; i < 4; i++) {
                float lo, hi;
                asm("{\n.reg .b16 a, b;\nmov.b32 {a, b}, %2;\ncvt.f32.f16 %0, a;\ncvt.f32.f16 %1, b;\n}" : "=f"(lo), "=f"(hi) : "r"(r[i]));
                p[i] = pack_bf16(gelu_half(fmaf(lo, na[2 * i], nb[2 * i])), gelu_half(fmaf(hi, na[2 * i + 1], nb[2 * i + 1])));
            }
        };
        uint32_t r[2][4], rn[2][4];
        fetch(r[0]);
        fetch(r[1]);
#pragma unroll 1
        for (int i = i0; i < i1; i += 32) {
            fetch(rn[0]);
            fetch(rn[1]);
            uint32_t p0[4], p1[4];
            gelu8(r[0], p0);
            gelu8(r[1], p1);
            if (i < lim) stg128(o, p0[0], p0[1], p0[2], p0[3]);
            if (i + 16 < lim) stg128(o + 16 * 512, p1[0], p1[1], p1[2], p1[3]);
            o += 32 * 512;
#pragma unroll
            for (int k = 0; k < 4; k++) { r[0][k] = rn[0][k]; r[1][k] = rn[1][k]; }
        }
    }
}
__device__ __forceinline__ void channel_scales(uint32_t sbase, uint8_t* smem, uint8_t* sp, int lane) {
    volatile uint32_t* ts = reinterpret_cast<volatile uint32_t*>(smem + OFF_TS);
    const uint32_t gr = ts[64], bars = sbase + OFF_BAR;
#pragma unroll 1
    for (int t = 0; t < 4; t++) {
#pragma unroll 1
        for (uint32_t n = 0; n < (1u << 20); n++)
            if (mbar_try(bars + B_SUM + 8 * t, 0)) break;
        long long s[4];
#pragma unroll 1
        for (uint32_t n = 0; n < (1u << 19); n++) {
            const unsigned long long* p = part_sums(sp, gr >> 6, tail_block(gr, t), ts[76]) + 4 * lane;
#pragma unroll
            for (int i = 0; i < 4; i++) asm volatile("ld.relaxed.gpu.global.u64 %0, [%1];" : "=l"(s[i]) : "l"(p + i) : "memory");
            if (__all_sync(0xffffffffu, s[0] & s[1] & s[2] & s[3] & 32)) break;
        }
        const float sx = __uint_as_float(ts[74]), sw = __uint_as_float(ts[75]);
        bool bad = false;
#pragma unroll
        for (int i = 0; i < 2; i++) {
            const float mean = (float)(s[2 * i] >> 12) * (0x1p-21f / kL), sq = (float)(s[2 * i + 1] >> 12) * (0x1p-21f / kL);
            float2* gb = reinterpret_cast<float2*>(smem + OFF_GB) + 64 * t + 2 * lane + i;
            const float den = fmaxf(sq - mean * mean, 0.f) + 1e-5f * sx * sw * sx * sw, a = gb->x * rsqrtf(den);
            *gb = make_float2(0.5f * a, 0.5f * (gb->y - mean * a));
            bad |= ((s[2 * i] | s[2 * i + 1]) & 0xFC0) || !(den >= 0x1p-22f);
        }
        bad = __any_sync(0xffffffffu, bad);
        if (lane == 0) ts[77 + t] = bad;
        __syncwarp();
        if (lane == 0) mbar_arrive(bars + B_NRM + 8 * t);
    }
}

__device__ __forceinline__ void publish_tiles(uint8_t* sp, uint32_t bars, int cta, int wg) {
#pragma unroll 1
    for (int m = 0; m < 2; m++) {
        mbar_wait(bars + B_YS + 8 * (2 * m + wg), 0);
        asm volatile("fence.acq_rel.gpu;" ::: "memory");
        red_relaxed(y_flag(sp, (cta >> 1) & 1, 4 * m + 2 * (cta & 1) + wg));
    }
}

__global__ void __launch_bounds__(384, 1)
main_kernel(const __grid_constant__ CUtensorMap tmx, const __grid_constant__ CUtensorMap tmw0, const __grid_constant__ CUtensorMap tmw1,
            const __nv_bfloat16* __restrict__ x, const __nv_bfloat16* __restrict__ wt, const __nv_bfloat16* __restrict__ gamma,
            const __nv_bfloat16* __restrict__ beta, __nv_bfloat16* __restrict__ out) {
    extern __shared__ __align__(1024) uint8_t smem_raw[];
    const uint32_t sbase = smem_u32(smem_raw) & ~1023u;
    const uint32_t bars = sbase + OFF_BAR;
    const int tid = threadIdx.x, wg = __shfl_sync(0xffffffffu, tid >> 7, 0), lane = tid & 31;
    const int cta = blockIdx.x;
    volatile uint32_t* ts = reinterpret_cast<volatile uint32_t*>(smem_raw + OFF_TS);
    uint8_t* const sp = reinterpret_cast<uint8_t*>((reinterpret_cast<uintptr_t>(g_sp) + (2u << 20) - 1) & ~(uintptr_t)((2u << 20) - 1));
    const bool probing = (cta & 3) == 0 && lane == 0 && tid < 128 && (tid >= 64 || cta < 4 * NPAGES);
    unsigned* pw = reinterpret_cast<unsigned*>(sp + (tid < 64 ? ((cta >> 2) << 21) + ((tid & 32) ? 15 : 13) * 4096
                                                              : ((tid & 32) ? 0 : 14) * 4096 + (cta >> 2) * 128));
    unsigned pv = 0;
    if (probing) {
        stg128(pw, 0, 0, 0, 0);
        stg128(pw + 4, 0, 0, 0, 0);
        asm volatile("atom.relaxed.gpu.global.exch.b32 %0, [%1], %2;" : "=r"(pv) : "l"(pw), "r"(7) : "memory");
    }
    if (tid == 320) bar_setup<0, B_SIG>(bars);
    if (tid >= 256 && tid < 262) ts[68 + tid - 256] = tid < 260 ? 0xffffu : 0;
    if (tid == 383) asm volatile("griddepcontrol.launch_dependents;");
    __syncthreads();

    if (wg == 2) {
        asm volatile("setmaxnreg.dec.sync.aligned.u32 40;");
        const int role = (tid >> 5) & 3;
        if (role == 3) {
            unsigned v = 0;
#pragma unroll 1
            for (uint32_t n = 0; n < (1u << 15); n++) {
                asm volatile("ld.relaxed.gpu.global.u32 %0, [%1];" : "=r"(v) : "l"(&g_tsel[lane]) : "memory");
                if (__all_sync(0xffffffffu, v & 16)) break;
                __nanosleep(TSLEEP);
            }
            const uint32_t m1 = __ballot_sync(0xffffffffu, v & 8), below = (1u << lane) - 1;
            const int rank = (v & 8) ? 32 - __popc(m1) + __popc(m1 & below) : __popc(~m1 & below);
            ts[lane] = rank;
            ts[32 + rank] = lane;
            const uint32_t p0 = __ballot_sync(0xffffffffu, v & 1);
            if (lane == 0) ts[66] = p0;
            if (lane == (cta >> 2)) ts[64] = rank * 4 + (cta & 3);
            const int part = (m1 >> (cta >> 2)) & 1;
            __syncwarp();
            if (lane == 0) { mbar_arrive(bars + B_TSEL); }
            mbar_wait(bars + B_TSEL, 0);
            mbar_wait(bars + B_PUB, 0);
            int gc = 0;
            const int gend = lane == 0 ? 33 : lane == 1 ? 32 : 0;
#pragma unroll 1
            for (uint32_t n = 0; n < (1u << 16) && __any_sync(0xffffffffu, gc < gend); n++) {
                asm volatile("ld.relaxed.gpu.global.u32 %0, [%1];" : "=r"(v) : "l"(chunk_flag(sp, lane == 1, part, min(gc, 32 - (lane & 1)))) : "memory");
                if (gc < gend && v >= NCTA) {
                    asm volatile("fence.acquire.gpu;" ::: "memory");
                    mbar_arrive(bars + (lane == 0 ? B_RDY : B_GATE) + 8 * gc);
                    gc++;
                }
            }
            if (lane == 0) publish_tiles(sp, bars, cta, 1);
        } else if (role == 0) {
            const int b = (cta >> 1) & 1, dq = cta & 1;
            for (int v = 0; v < V0; v++) {
                mbar_wait(bars + B_EMPTY + 8 * (v % NST), ((v / NST) & 1) ^ 1);
                if (lane == 0) {
                    mbar_arrive(bars + B_FULL + 8 * (v % NST));
                    mbar_arrive(bars + B_FULL + 8 * (v % NST));
                }
            }
            mbar_wait(bars + B_TSEL, 0);
            const uint32_t gr = ts[64], grp = gr >> 6, idx = (gr >> 2) & 15, pmask = ts[66];
            const uint32_t n0 = idx * 4 + 2 * dq + ((lane & 1) ^ 1), r0 = lane < 3 ? idx * 4 + b : R_W + n0 / 3;
            const uint32_t base = (r0 << 16) + 4096 + ((lane < 3 ? lane : n0 % 3) << 14), step = (lane < 3 ? 64 : 22) << 16;
            uint32_t sels = 0;
            for (int i = 0; i < 12; i++) sels |= run_sel(r0 + i * (step >> 16), grp, pmask) << i;
            int ld = 0;
            const uint32_t bytes = lane == 2 ? XB - 16384 : 8192;
#pragma unroll 1
            for (int h = 0; h < 64; h++) {
                const int s = step_k(h), st = (h + V0) % NST;
                const bool newx = h < HEND ? !(h & 1) : h < HEND + 4;
                const uint32_t fb = bars + B_FULL + 8 * st;
                const uint32_t k = lane < 3 ? (s >> 1) % RX : (h + RW - 64 % RW) % RW, half = lane < 3 ? s & 1 : 0;
                const uint8_t* gsrc = sp + (base + k * step + (half << 17) + ((((sels >> k) ^ half) & 1) << 13));
                const uint32_t dst = sbase + (lane < 3 ? OFF_X + (s & 3) * XB + lane * 8192 : st * 8192 + (lane == 3 ? OFF_W0 : OFF_W1));
                auto landed = [&]() {
                    if (ld < h && mbar_test(bars + B_FULL + 8 * ((ld + V0) % NST), ((ld + V0) / NST) & 1)) {
                        if (!(ld & 1) && lane < 2) red_relaxed(chunk_flag(sp, 1, lane, ld >> 1));
                        ld++;
                    }
                };
                if ((h & 1) || h == 0) {
#pragma unroll 1
                    for (uint32_t n = 0; n < (1u << 19) && !mbar_test(bars + B_RDY + 8 * ((h + 1) >> 1), 0); n++) landed();
                    asm volatile("fence.proxy.async.global;" ::: "memory");
                }
#pragma unroll 1
                for (uint32_t n = 0; n < (1u << 19) && !mbar_test(bars + B_EMPTY + 8 * st, (((h + V0) / NST) & 1) ^ 1); n++) landed();
#pragma unroll 1
                for (uint32_t n = 0; n < (1u << 19) && ld <= h - NST; n++) landed();
                if (lane == 0) mbar_expect_tx(fb, newx ? 16384 + XB : 16384);
                __syncwarp();
                if (lane < 3 ? newx : lane < 5) bulk_g2s(dst, gsrc, bytes, fb);
            }
#pragma unroll 1
            for (; ld < 63; ld++) {
                mbar_wait(bars + B_FULL + 8 * ((ld + V0) % NST), ((ld + V0) / NST) & 1);
                if (!(ld & 1) && lane < 2) red_relaxed(chunk_flag(sp, 1, lane, ld >> 1));
            }
            tail_poll(sp, gr, 0);
            mbar_wait(bars + B_T2, 0);
            tail_loads(sbase, sp, gr, pmask, 0, 5, lane);
            tail_poll(sp, gr, 1);
            tail_loads(sbase, sp, gr, pmask, 5, 8, lane);
            mbar_wait(bars + B_YS + 16, 0);
            tail_loads(sbase, sp, gr, pmask, 8, 10, lane);
            mbar_wait(bars + B_T2 + 8, 0);
            if (lane == 0) {
                mbar_expect_tx(bars + B_C1, 2560);
                corr_load(sbase, gr, 2, bars + B_C1);
                corr_load(sbase, gr, 3, bars + B_C1);
            }
            tail_poll(sp, gr, 2);
            tail_loads(sbase, sp, gr, pmask, 10, 15, lane);
            tail_poll(sp, gr, 3);
            tail_loads(sbase, sp, gr, pmask, 15, 20, lane);
            mbar_wait(bars + B_GATE + 8 * 31, 0);
            unsigned exits = 0;
            if (lane == 0) exits = atomicAdd(&g_exit, 1);
            if (__shfl_sync(0xffffffffu, exits, 0) == NCTA - 1) {
                for (int i = 0; i < 4; i++) *chunk_flag(sp, i >> 1, i & 1, lane) = 0;
                if (lane < 2) *chunk_flag(sp, 0, lane, 32) = 0;
                g_tsel[lane] = 0;
                if (lane < 16) *y_flag(sp, lane >> 3, lane & 7) = 0;
                if (lane == 0) { g_exit = 0; g_epoch = ts[76]; }
            }
        } else if (role == 1) {
            auto raw_load = [&](int r, int h, uint32_t gr, uint32_t dst, uint32_t bar) {
                if (r >= 0) {
                    const int u = r * NCTA + cta, i = u % XPC, b = i >= kNT;
                    tma3d(dst, &tmx, u / XPC * 64, (i - b * kNT) * kMO, b, bar);
                } else if (h >= 0) {
                    const int c = 32 * step_k(h) + ((gr >> 1) & 30);
                    tma3d_ef(dst, c < 512 ? &tmw0 : &tmw1, step_m(h) * 256 + (gr & 3) * 64, 0, c & 511, bar);
                }
            };
            uint32_t gr;
            {
                const int v = lane >> 1, r = v < V0 ? x_round(v, lane & 1) : -1, h = v < V0 ? w_step(v, lane & 1) : -1;
                const uint32_t dst = pre_slot(sbase, v, lane & 1), bar = bars + B_PRE + 8 * lane;
                if (r >= 0 || h >= 0) mbar_expect_tx(bar, r >= 0 ? 8192 : 4096);
                if (v < PRE1) raw_load(r, -1, 0, dst, bar);
                mbar_wait(bars + B_TSEL, 0);
                gr = ts[64];
                raw_load(-1, h, gr, dst, bar);
                if (v >= PRE1) raw_load(r, -1, 0, dst, bar);
                __syncwarp();
            }
            mbar_wait(bars + B_PUB, 0);
#pragma unroll 1
            for (int v = V0; v < V0 + 64; v++) {
                mbar_wait(bars + B_EMPTY + 8 * (v % NST), ((v / NST) & 1) ^ 1);
                __syncwarp();
                const int r = lane < 2 ? x_round(v, lane) : -1, h = lane < 2 ? w_step(v, lane) : -1;
                const uint32_t fb = bars + B_FULL + 8 * (v % NST);
                const uint32_t bytes = __reduce_add_sync(0xffffffffu, r >= 0 ? 8192 : h >= 0 ? 4096 : 0);
                if (lane == 0) mbar_expect_tx(fb, bytes);
                __syncwarp();
                raw_load(r, h, gr, raw_slot(sbase, v, lane), fb);
                if (v >= 20 && v < 40) {
                    const int t = (v - 20) / 5, i = (v - 20) % 5 * 32 + lane, db = 4 * (t >> 1) + 2 * (cta & 1) + (t & 1);
                    ts[(OFF_YT - OFF_TS) / 4 + t * kNT + i] = y_unit(db, i, (cta >> 1) & 1, ts[66]);
                }
                if (v == 66 && lane == 0) {
#pragma unroll 1
                    for (uint32_t n = 0; n < (1u << 15); n++) {
                        unsigned c0, c1;
                        asm volatile("ld.relaxed.gpu.global.u32 %0, [%1];" : "=r"(c0) : "l"(&g_cready[(gr >> 6) * 64]) : "memory");
                        asm volatile("ld.relaxed.gpu.global.u32 %0, [%1];" : "=r"(c1) : "l"(&g_cready[(gr >> 6) * 64 + 32]) : "memory");
                        if (c0 == ts[76] && c1 == ts[76]) break;
                        __nanosleep(500);
                    }
                    asm volatile("fence.acquire.gpu;" ::: "memory");
                    asm volatile("fence.proxy.async.global;" ::: "memory");
                    mbar_expect_tx(bars + B_FTAB, 8192 + 2560);
                    bulk_g2s(sbase + OFF_F, g_tab.inv, 8192, bars + B_FTAB);
                    for (int t = 0; t < 2; t++) {
                        corr_load(sbase, gr, t, bars + B_FTAB);
                        asm volatile("cp.async.bulk.prefetch.L2.global [%0], 1280;" ::"l"(corr_src(gr, 2 + t)) : "memory");
                    }
                }
            }
            channel_scales(sbase, smem_raw, sp, lane);
        } else {
            uint32_t epoch;
            if (lane == 0) {
                bar_setup<B_SIG, B_END>(bars);
                mbar_arrive(bars + B_TSEL);
            }
            asm volatile("ld.relaxed.gpu.global.u32 %0, [%1];" : "=r"(epoch) : "l"(&g_epoch) : "memory");
            mbar_wait(bars + B_TSEL, 0);
            const uint32_t gr = ts[64];
#pragma unroll
            for (int i = lane; i < 256; i += 32) {
                const int d = 64 * tail_block(gr, i >> 6) + (i & 33) + 8 * ((i >> 1) & 3) + 2 * ((i >> 3) & 3);
                ts[(OFF_GB - OFF_TS) / 4 + 2 * i] = (uint32_t)__bfloat16_as_ushort(gamma[d]) << 16;
                ts[(OFF_GB - OFF_TS) / 4 + 2 * i + 1] = (uint32_t)__bfloat16_as_ushort(beta[d]) << 16;
            }
            if (lane == 0) ts[76] = epoch + 1;
            if (cta < 32) stg128(part_sums(sp, cta >> 4, (cta >> 1) & 7, epoch) + (cta & 1) * 64 + 2 * lane, 0, 0, 0, 0);
            __syncwarp();
            if (lane) return;
#pragma unroll 1
            for (int gc = 0; gc < 33;) {
                mbar_wait(bars + B_SIG + 8 * gc, 0);
                if (gc < MERGE) mbar_wait(bars + B_SIG + 8 * MERGE, 0);
                int ge = gc + 1;
                while (ge < 33 && mbar_test(bars + B_SIG + 8 * ge, 0)) ge++;
                asm volatile("fence.acq_rel.gpu;" ::: "memory");
                for (; gc < ge; gc++) {
                    red_relaxed(chunk_flag(sp, 0, 0, gc));
                    red_relaxed(chunk_flag(sp, 0, 1, gc));
                    if (gc == 0) mbar_arrive(bars + B_PUB);
                }
            }
            publish_tiles(sp, bars, cta, 0);
        }
    } else {
        asm volatile("setmaxnreg.inc.sync.aligned.u32 232;");
        uint4 fw[2];
#pragma unroll
        for (int j = 0; j < 2; j++) fw[j] = __ldg(reinterpret_cast<const uint4*>(g_tab.fwd) + tid + 256 * j);
        if (wg == 1) {
            uint4 sm[8];
#pragma unroll
            for (int j = 0; j < 4; j++) {
                const int r = 2 * j + ((tid >> 6) & 1);
                sm[j] = __ldg(reinterpret_cast<const uint4*>(x) + ((r >> 2) * kRows + 1000 + 2000 * (r & 3)) * 128 + (((j + r) & 1) << 6) + (tid & 63));
                sm[4 + j] = __ldg(reinterpret_cast<const uint4*>(wt) + (4 * r * 512 + 67 * r + 7) * 64 + (tid & 63));
            }
#pragma unroll
            for (int k = 0; k < 2; k++) {
                uint32_t mx = 0;
#pragma unroll
                for (int j = 4 * k; j < 4 * k + 4; j++)
                    mx = __vmaxu2(__vmaxu2(mx, __vmaxu2(sm[j].x & 0x7FFF7FFFu, sm[j].y & 0x7FFF7FFFu)), __vmaxu2(sm[j].z & 0x7FFF7FFFu, sm[j].w & 0x7FFF7FFFu));
                mx = __reduce_max_sync(0xffffffffu, max(mx & 0xFFFFu, mx >> 16));
                if (lane == 0) atomicMax(const_cast<uint32_t*>(ts) + 72 + k, mx);
            }
        }
        if ((cta & 3) == 0) {
            if (probing) {
                const int w = tid >> 5;
                unsigned best = 0xffffu;
#pragma unroll 1
                for (int r = 0; r < 6; r++) {
                    unsigned t0, t1;
                    asm volatile("{\n.reg .pred p;\nsetp.eq.u32 p, %1, 0xffffffff;\nmov.u32 %0, 0;\n@!p mov.u32 %0, %%clock;\n}"
                                 : "=r"(t0) : "r"(pv) : "memory");
                    asm volatile("atom.relaxed.gpu.global.exch.b32 %0, [%1], %2;" : "=r"(pv) : "l"(pw), "r"(r) : "memory");
                    asm volatile("{\n.reg .pred p;\nsetp.eq.u32 p, %1, 0xffffffff;\nmov.u32 %0, 0;\n@!p mov.u32 %0, %%clock;\n}"
                                 : "=r"(t1) : "r"(pv) : "memory");
                    ts[68 + w] = best = min(best, t1 - t0);
                    const unsigned other = ts[68 + (w ^ 1)];
                    if (min(best, other) < PROBE_NEAR && max(best, other) > PROBE_NEAR) break;
                }
            }
            if (wg == 0) {
                named_bar(2, 128);
                if (tid == 0) {
                    const uint32_t part = ts[71] < ts[70];
                    const uint32_t v = 16 | (part << 3) | ((ts[69] < ts[68]) ^ part);
                    asm volatile("st.relaxed.gpu.global.u32 [%0], %1;" ::"l"(&g_tsel[cta >> 2]), "r"(v) : "memory");
                }
            }
        }
        uint32_t plan = tid < 2 * (V0 + 65) ? plan_word(tid >> 1, tid & 1, cta) : 0;
        {
            named_bar(1, 256);
            const uint32_t ex = min(max(251 - (int)(ts[72] >> 7), 8), 187), ew = min(max(251 - (int)(ts[73] >> 7), 8), 187);
            if (tid == 0) { ts[74] = ex << 23; ts[75] = ew << 23; }
            const uint32_t sx = ex * 0x800080u, sw = ew * 0x800080u;
#pragma unroll
            for (int j = 0; j < 2; j++) {
                const int i = tid + 256 * j, row = i >> 3, c = (i ^ row) & 7;
                sts128(sbase + OFF_F + 16 * i, mul_bf16x2(fw[j].x, sx), mul_bf16x2(fw[j].y, sx), mul_bf16x2(fw[j].z, sx), mul_bf16x2(fw[j].w, sx));
                if (c < 2) sts128(sbase + OFF_TMP + row * 32 + c * 16, mul_bf16x2(fw[j].x, sw), mul_bf16x2(fw[j].y, sw), mul_bf16x2(fw[j].z, sw), mul_bf16x2(fw[j].w, sw));
            }
            named_bar(1, 256);
        }
        const int t = tid & 127;
        Xf f;
        f.sbase = sbase; f.lane = lane; f.xsw = cta & 4; f.dw = desc_lo(sbase + (wg ? OFF_W1 : OFF_W0));
        {
            const int w = t >> 5;
            const uint32_t nw = (8 * (w & 1) + (lane >> 2)) * 4 + (cta & 3), rw = R_W + nw / 3;
            f.pw = sp + (rw << 16) + 4096 + ((nw % 3) << 14) + (w >> 1) * 128;
            f.cw = ((lane & 7) ^ (w >> 1)) << 4;
            for (int i = 0; i < RW; i++) f.cw |= run_sel(rw + i * 22, 0, 0) << (8 + i);
            mbar_wait(bars + B_TSEL, 0);
            const uint32_t gr = ts[64], pmask = ts[66];
            const uint32_t rx = ts[8 * w + (lane >> 2)];
            f.px = sp + ((rx & 15) << 18) + 4096;
            f.cx = ((lane & 7) << 4) | ((((pmask >> ((rx >> 3) & 1)) ^ -(((rx >> 1) ^ (rx >> 4)) & 1)) & 0x55) << 8);
#pragma unroll
            for (int i = 0; i < RW; i++) f.cw ^= (((pmask >> ((rw + i * 22) >> 5)) ^ (gr >> 6)) & 1) << (8 + i);
            if (plan & 4) plan |= ((gr & 12) << 8) | ((gr & 48) << 4) | ((gr & 48) << 1);
            if (tid < 2 * (V0 + 65)) ts[(OFF_PLAN - OFF_TS) / 4 + tid] = plan;
            const int row = tid >> 2, ch = tid & 3, s = ts[32 + (gr >> 6) * 16 + ((row >> 1) & 8) + (row & 7)], p = (row >> 3) & 1;
            const int frow = 16 * (s >> 3) + 8 * p + (s & 7);
            uint32_t v[4] = {0, 0, 0, 0};
            if ((ch >> 1) == (row >> 5))
                asm volatile("ld.shared.v4.b32 {%0,%1,%2,%3}, [%4];" : "=r"(v[0]), "=r"(v[1]), "=r"(v[2]), "=r"(v[3])
                             : "r"(sbase + OFF_TMP + frow * 32 + (ch & 1) * 16) : "memory");
            sts128(sbase + OFF_G + row * 64 + ((ch ^ ((row >> 1) & 3)) << 4), v[0], v[1], v[2], v[3]);
            fence_proxy_async_smem();
            named_bar(1, 256);
        }
        {
            float at[32];
#pragma unroll 1
            for (uint32_t v = 0; v < V0; v++) {
                const uint32_t e = plan_load(f, v, wg), raw = pre_slot(sbase, v, wg);
                mbar_wait(bars + B_FULL + 8 * (v % NST), (v / NST) & 1);
                if (e & 6) mbar_wait(bars + B_PRE + 16 * v + 8 * wg, 0);
                if (v == PAUSE) mbar_wait(bars + B_PUB, 0);
                wg_fence();
                if ((e & 6) == 2) {
                    unit_mma<false>(at, f, raw);
                    wg_wait<0>();
                    unit_store<false>(at, f, e);
                } else if (e & 4) {
                    unit_mma<true>(at, f, raw);
                    wg_wait<0>();
                    unit_store<true>(at, f, e);
                }
                if (lane == 0) mbar_arrive(bars + B_EMPTY + 8 * (v % NST));
                unit_done(f, e, v);
            }
        }
        const int slot = cta >> 2;
        f.e = plan_load(f, V0, wg);
        uint32_t a0[40], a1[40], b0[40], b1[40];
#pragma unroll
        for (int i = 0; i < 40; i++) a0[i] = a1[i] = b0[i] = b1[i] = 0;
        if (slot == 0) gemm_main<true>(a0, a1, b0, b1, f, wg);
        else gemm_main<false>(a0, a1, b0, b1, f, wg);
        const uint32_t gr = __shfl_sync(0xffffffffu, ts[64], 0);
        const float sx = __uint_as_float(ts[74]), sw = __uint_as_float(ts[75]);
        uint32_t wr[2][4][4];
        w_fetch(wr[0], f, V0 + HEND);
#pragma unroll 1
        for (int m = 0; m < 2; m++) {
            if (slot == 0) gemm_last<true>(a0, a1, wr, f, wg, m);
            else gemm_last<false>(a0, a1, wr, f, wg, m);
            reg_fence(a0);
            reg_fence(a1);
            const int wsw = gr & 4;
            mbar_wait(bars + B_GATE + 8 * y_gate(2 * m + wg), 0);
            if (m) mbar_wait(bars + B_FTAB, 0);
            const uint32_t ytab = sbase + OFF_YT + (m * 2 + wg) * (kNT * 4);
            store_tile(a0, a1, b0, b1, wr[0], f, m == 0, sbase + OFF_STG + wg * 16384, t, wg, sp, slot, ytab, wsw);
            __syncwarp();
            if (lane == 0) mbar_arrive(bars + B_YS + 8 * (2 * m + wg));
        }
        tail_phase(sbase, smem_raw, sp, wg, gr, sx, sw, x, wt, gamma, beta, out);
    }
}

constexpr int C_STAGE = 32768 + 2 * XB, C_SMEM = 3 * C_STAGE + 64;
__global__ void __launch_bounds__(256, 1) corr_kernel(const __grid_constant__ CUtensorMap tmx, const __grid_constant__ CUtensorMap tmw) {
    extern __shared__ __align__(1024) uint8_t smem_raw[];
    const uint32_t sbase = smem_u32(smem_raw) & ~1023u, bars = sbase + 3 * C_STAGE;
    const int tid = threadIdx.x, wg = __shfl_sync(0xffffffffu, tid >> 7, 0), b = blockIdx.x >> 1, dh = blockIdx.x & 1;
    auto load = [&](int k) {
        const uint32_t st = sbase + (k % 3) * C_STAGE, bar = bars + 8 * (k % 3);
        mbar_expect_tx(bar, C_STAGE);
        for (int i = 0; i < 4; i++) tma2d(st + i * 8192, &tmw, 256 * dh + 64 * i, 64 * k, bar);
        tma4d(st + 32768, &tmx, 64 * k, 64 - kMO, 1, b, bar);
        tma4d(st + 32768 + XB, &tmx, 64 * k, 0, 0, b, bar);
    };
    uint32_t epoch = 0;
    if (tid == 0) {
        for (int i = 0; i < 3; i++) mbar_init(bars + 8 * i, 1);
        fence_mbar_init();
        fence_proxy_async_smem();
        for (int k = 0; k < 3; k++) load(k);
        asm volatile("ld.relaxed.gpu.global.u32 %0, [%1];" : "=r"(epoch) : "l"(&g_epoch) : "memory");
    }
    __syncthreads();
    float a[2][80];
#pragma unroll
    for (int i = 0; i < 80; i++) a[0][i] = a[1][i] = 0.f;
#pragma unroll 1
    for (int k = 0; k < 8; k++) {
        const uint32_t dA = desc_lo(sbase + (k % 3) * C_STAGE + wg * 16384), dB = desc_lo(sbase + (k % 3) * C_STAGE + 32768);
        mbar_wait(bars + 8 * (k % 3), (k / 3) & 1);
        wg_fence();
#pragma unroll
        for (int i = 0; i < 8; i++) {
            wgmma_n160_f<1>(a[i & 1], dA + (i & 1) * 512 + (i >> 1) * 128, dB + (i >> 1) * 2);
            wgmma_n160_f<-1>(a[i & 1], dA + (i & 1) * 512 + (i >> 1) * 128, dB + XB / 16 + (i >> 1) * 2);
        }
        wg_commit();
        wg_wait<0>();
        __syncthreads();
        if (tid == 0 && k + 3 < 8) load(k + 3);
    }
    reg_fence(a[0]);
    reg_fence(a[1]);
    const int w = (tid >> 5) & 3, g = (tid & 31) >> 2, q = tid & 3;
    float* stage = reinterpret_cast<float*>(smem_raw);
#pragma unroll
    for (int i = 0; i < 160; i++) {
        const int m = i / 80, j = i % 80, d = 16 * w + 8 * ((j >> 1) & 1) + g;
        stage[((2 * wg + m) * kNT + 8 * (j >> 2) + 2 * q + (j & 1)) * 64 + (d & 33) + 8 * ((d >> 1) & 3) + 2 * ((d >> 3) & 3)] = a[m][j];
    }
    __syncthreads();
    for (int i = tid; i < 4 * kNT * 16; i += 256)
        reinterpret_cast<float4*>(g_corr)[(b * 8 + 4 * dh) * kNT * 16 + i] = reinterpret_cast<const float4*>(stage)[i];
    __syncthreads();
    if (tid == 0) {
        asm volatile("fence.acq_rel.gpu;" ::: "memory");
        asm volatile("st.relaxed.gpu.global.u32 [%0], %1;" ::"l"(&g_cready[blockIdx.x * 32]), "r"(epoch + 1) : "memory");
    }
}

__global__ void __launch_bounds__(256) plain_conv(const __nv_bfloat16* __restrict__ x, const __nv_bfloat16* __restrict__ w) {
    __shared__ float xs[64][17], ws[16][65];
    float* h = g_direct;
    const int b = blockIdx.z, l0 = blockIdx.x * 64, d0 = blockIdx.y * 64, tx = threadIdx.x & 15, ty = threadIdx.x >> 4;
    float acc[4][4] = {};
    for (int k0 = 0; k0 < 31 * 512; k0 += 16) {
        for (int i = threadIdx.x; i < 1024; i += 256) {
            const int l = min(l0 + (i >> 4), kL - 1);
            xs[i >> 4][i & 15] = __bfloat162float(x[((size_t)b * kRows + l) * 1024 + k0 + (i & 15)]);
            ws[i >> 6][i & 63] = __bfloat162float(w[(size_t)(k0 + (i >> 6)) * 512 + d0 + (i & 63)]);
        }
        __syncthreads();
        for (int k = 0; k < 16; k++)
            for (int i = 0; i < 4; i++)
                for (int j = 0; j < 4; j++) acc[i][j] = fmaf(xs[ty * 4 + i][k], ws[k][tx * 4 + j], acc[i][j]);
        __syncthreads();
    }
    for (int i = 0; i < 4; i++)
        for (int j = 0; j < 4; j++)
            if (l0 + ty * 4 + i < kL) h[((size_t)b * kL + l0 + ty * 4 + i) * 512 + d0 + tx * 4 + j] = acc[i][j];
}
__global__ void __launch_bounds__(256) plain_norm(const __nv_bfloat16* __restrict__ gamma, const __nv_bfloat16* __restrict__ beta,
                                                  __nv_bfloat16* __restrict__ out) {
    __shared__ float s1[8][32], s2[8][32];
    const int c = threadIdx.x & 31, r = threadIdx.x >> 5, d = blockIdx.x * 32 + c;
    const float* h = g_direct + (size_t)blockIdx.y * kL * 512 + d;
    float a = 0.f, q = 0.f;
    for (int l = r; l < kL; l += 8) { const float v = h[(size_t)l * 512]; a += v; q = fmaf(v, v, q); }
    s1[r][c] = a; s2[r][c] = q;
    __syncthreads();
    a = q = 0.f;
    for (int i = 0; i < 8; i++) { a += s1[i][c]; q += s2[i][c]; }
    const float mean = a * (1.0f / kL), sc = __bfloat162float(gamma[d]) / sqrtf(fmaxf(q * (1.0f / kL) - mean * mean, 0.f) + 1e-5f);
    const float sh = __bfloat162float(beta[d]) - mean * sc;
    for (int l = r; l < kL; l += 8)
        out[((size_t)blockIdx.y * kL + l) * 512 + d] = __float2bfloat16(gelu_half(0.5f * fmaf(h[(size_t)l * 512], sc, sh)));
}

typedef CUresult (*EncodeTiledFn)(CUtensorMap*, CUtensorMapDataType, cuuint32_t, void*, const cuuint64_t*, const cuuint64_t*,
                                  const cuuint32_t*, const cuuint32_t*, CUtensorMapInterleave, CUtensorMapSwizzle,
                                  CUtensorMapL2promotion, CUtensorMapFloatOOBfill);

void encode(EncodeTiledFn fn, CUtensorMap* tm, const void* ptr, int rank, const cuuint64_t* dims, const cuuint64_t* strides,
            const cuuint32_t* box, CUtensorMapL2promotion promo, CUtensorMapSwizzle swz = CU_TENSOR_MAP_SWIZZLE_128B) {
    const cuuint32_t es[5] = {1, 1, 1, 1, 1};
    fn(tm, CU_TENSOR_MAP_DATA_TYPE_BFLOAT16, rank, const_cast<void*>(ptr), dims, strides, box, es, CU_TENSOR_MAP_INTERLEAVE_NONE,
       swz, promo, CU_TENSOR_MAP_FLOAT_OOB_FILL_NONE);
}

}

extern "C" void kernel_launch(void* const* d_in, const int* in_sizes, int n_in, void* d_out, int out_size) {
    const __nv_bfloat16* x = (const __nv_bfloat16*)d_in[0];
    const __nv_bfloat16* w = (const __nv_bfloat16*)d_in[1];
    const __nv_bfloat16* gamma = (const __nv_bfloat16*)d_in[2];
    const __nv_bfloat16* beta = (const __nv_bfloat16*)d_in[3];
    static EncodeTiledFn enc = nullptr;
    static int resident = 0;
    if (!enc) {
        void* fn = nullptr;
        cudaDriverEntryPointQueryResult qr;
        cudaGetDriverEntryPoint("cuTensorMapEncodeTiled", &fn, cudaEnableDefault, &qr);
        enc = (EncodeTiledFn)fn;
        cudaFuncSetAttribute(main_kernel, cudaFuncAttributeMaxDynamicSharedMemorySize, MAIN_SMEM);
        cudaFuncSetAttribute(corr_kernel, cudaFuncAttributeMaxDynamicSharedMemorySize, C_SMEM);
        int dev = 0, per_sm = 0;
        cudaGetDevice(&dev);
        cudaDeviceGetAttribute(&resident, cudaDevAttrMultiProcessorCount, dev);
        cudaOccupancyMaxActiveBlocksPerMultiprocessor(&per_sm, main_kernel, 384, MAIN_SMEM);
        resident *= per_sm;
    }
    if (resident < NCTA + 4) {
        plain_conv<<<dim3((kL + 63) / 64, 8, 2), 256>>>(x, w);
        plain_norm<<<dim3(16, 2), 256>>>(gamma, beta, (__nv_bfloat16*)d_out);
        return;
    }
    CUtensorMap tmx, tmw0, tmw1, tmcx, tmcw;
    {
        const cuuint64_t dims[3] = {1024, kRows, 2}, strides[2] = {2048, (cuuint64_t)kRows * 2048};
        const cuuint32_t box[3] = {64, 64, 1};
        encode(enc, &tmx, x, 3, dims, strides, box, CU_TENSOR_MAP_L2_PROMOTION_L2_128B);
    }
    {
        const cuuint64_t dims0[3] = {512, 16, 512}, dims1[3] = {512, 15, 512}, strides[2] = {2 * 512 * 512 * 2, 1024};
        const cuuint32_t box[3] = {64, 16, 2};
        encode(enc, &tmw0, w, 3, dims0, strides, box, CU_TENSOR_MAP_L2_PROMOTION_L2_128B);
        encode(enc, &tmw1, w + 512 * 512, 3, dims1, strides, box, CU_TENSOR_MAP_L2_PROMOTION_L2_128B);
    }
    {
        const cuuint64_t dims[4] = {512, kMO, kNT, 2}, strides[3] = {2048, kMO * 2048, (cuuint64_t)kRows * 2048};
        const cuuint32_t box[4] = {64, 1, kNT, 1};
        encode(enc, &tmcx, x, 4, dims, strides, box, CU_TENSOR_MAP_L2_PROMOTION_L2_128B);
        const cuuint64_t dimw[2] = {512, 512}, stridew[1] = {1024};
        const cuuint32_t boxw[2] = {64, 64};
        encode(enc, &tmcw, w + 30 * 512 * 512, 2, dimw, stridew, boxw, CU_TENSOR_MAP_L2_PROMOTION_L2_128B);
    }
    main_kernel<<<NCTA, 384, MAIN_SMEM>>>(tmx, tmw0, tmw1, x, w, gamma, beta, (__nv_bfloat16*)d_out);
    cudaLaunchConfig_t cfg = {};
    cudaLaunchAttribute at[1];
    cfg.gridDim = 4;
    cfg.blockDim = 256;
    cfg.dynamicSmemBytes = C_SMEM;
    at[0].id = cudaLaunchAttributeProgrammaticStreamSerialization;
    at[0].val.programmaticStreamSerializationAllowed = 1;
    cfg.attrs = at;
    cfg.numAttrs = 1;
    cudaLaunchKernelEx(&cfg, corr_kernel, tmcx, tmcw);
}
```

```cpp
#include <cuda_runtime.h>
#include <cuda_bf16.h>
#include <cuda.h>
#include <stdint.h>

namespace {

constexpr int kL    = 7985;
constexpr int kRows = 8000;
constexpr int kMO   = 50;
constexpr int kNT   = 160;

constexpr int V0 = 7;
constexpr int NPRE = 6;
constexpr int RX = 4;
constexpr int FCUT = 128;
constexpr int PAUSE = 5;
constexpr int YSLEEP = 100;
constexpr int PRE1 = 4;
constexpr int TSLEEP = 200;
constexpr int MERGE = 1;
constexpr int RW = 10;

static_assert(V0 >= 7 && V0 <= 9 && RX >= 2 && RX <= 4 && RW >= V0 - 1 && RW <= 12, "rings must fit and be as deep as the look-ahead");
constexpr uint32_t HOME_MASK = 0xB;
constexpr uint32_t R_W = 64 * RX, NPAGES = (R_W + 22 * RW + 31) / 32;

__device__ __align__(1024) uint8_t g_sp[(size_t)(NPAGES + 1) * (2u << 20)];
__device__ __align__(128) unsigned g_tsel[32];
__device__ __forceinline__ uint32_t run_sel(uint32_t r, uint32_t group, uint32_t pmask) {
    return ((pmask >> (r >> 5)) ^ __popc(r & HOME_MASK) ^ group) & 1;
}
__device__ __forceinline__ uint32_t run_off(uint32_t r, uint32_t run, uint32_t group, uint32_t pmask) {
    return (r << 16) + 4096 + (run_sel(r, group, pmask) << 13) + (run << 14);
}
__device__ __forceinline__ unsigned* chunk_flag(uint8_t* sp, int done, int part, int chunk) {
    return reinterpret_cast<unsigned*>(sp + (4 + 3 * (chunk >> 5)) * 65536 + (done ? (part ? 15 : 13) : (part ? 0 : 14)) * 4096 + (chunk & 31) * 128);
}
__device__ __forceinline__ unsigned long long* part_sums(uint8_t* sp, int b, int db, uint32_t epoch) {
    return reinterpret_cast<unsigned long long*>(sp + (8 + 2 * db + ((__popc((8 + 2 * db) & HOME_MASK) ^ b) & 1)) * 65536 + 13 * 4096 + (epoch & 1) * 1024);
}
__device__ __forceinline__ unsigned* y_flag(uint8_t* sp, int b, int db) { return reinterpret_cast<unsigned*>(part_sums(sp, b, db, 0) + 512); }
__device__ __align__(256) float g_corr[16 * kNT * 64];
__device__ unsigned g_cready[4 * 32];
__device__ float g_direct[512 * 250 * 64];
__device__ unsigned long long g_dpart[2 * 512 * 64];
__device__ unsigned g_exit, g_epoch;

__device__ __forceinline__ uint32_t smem_u32(const void* p) { return (uint32_t)__cvta_generic_to_shared(p); }

__device__ __forceinline__ void mbar_init(uint32_t bar, uint32_t count) {
    asm volatile("mbarrier.init.shared::cta.b64 [%0], %1;" ::"r"(bar), "r"(count) : "memory");
}
__device__ __forceinline__ void mbar_expect_tx(uint32_t bar, uint32_t bytes) {
    asm volatile("mbarrier.arrive.expect_tx.shared::cta.b64 _, [%0], %1;" ::"r"(bar), "r"(bytes) : "memory");
}
__device__ __forceinline__ void mbar_arrive(uint32_t bar) {
    asm volatile("mbarrier.arrive.shared::cta.b64 _, [%0];" ::"r"(bar) : "memory");
}
__device__ __forceinline__ bool mbar_try(uint32_t bar, uint32_t parity) {
    uint32_t ok;
    asm volatile(
        "{\n.reg .pred p;\n"
        "mbarrier.try_wait.parity.shared::cta.b64 p, [%1], %2;\n"
        "selp.u32 %0, 1, 0, p;\n}\n"
        : "=r"(ok) : "r"(bar), "r"(parity) : "memory");
    return ok;
}
__device__ __forceinline__ bool mbar_test(uint32_t bar, uint32_t parity) {
    uint32_t ok;
    asm volatile(
        "{\n.reg .pred p;\n"
        "mbarrier.test_wait.parity.shared::cta.b64 p, [%1], %2;\n"
        "selp.u32 %0, 1, 0, p;\n}\n"
        : "=r"(ok) : "r"(bar), "r"(parity) : "memory");
    return ok;
}
__device__ __forceinline__ void mbar_wait(uint32_t bar, uint32_t parity) {
#pragma unroll 1
    for (uint32_t n = 0; n < (1u << 14); n++)
        if (mbar_try(bar, parity)) break;
}
__device__ __forceinline__ void fence_proxy_async_smem() { asm volatile("fence.proxy.async.shared::cta;" ::: "memory"); }
__device__ __forceinline__ void fence_mbar_init() { asm volatile("fence.mbarrier_init.release.cluster;" ::: "memory"); }

__device__ __forceinline__ void bulk_g2s(uint32_t dst, const void* src, uint32_t bytes, uint32_t bar) {
    asm volatile("cp.async.bulk.shared::cluster.global.mbarrier::complete_tx::bytes [%0], [%1], %2, [%3];"
                 ::"r"(dst), "l"(src), "r"(bytes), "r"(bar) : "memory");
}
__device__ __forceinline__ void tma3d_ef(uint32_t dst, const CUtensorMap* tm, int c0, int c1, int c2, uint32_t bar) {
    asm volatile("{\n.reg .b64 pol;\ncreatepolicy.fractional.L2::evict_first.b64 pol, 1.0;\n"
                 "cp.async.bulk.tensor.3d.shared::cluster.global.mbarrier::complete_tx::bytes.L2::cache_hint [%0], [%1, {%3, %4, %5}], [%2], pol;\n}"
                 ::"r"(dst), "l"(tm), "r"(bar), "r"(c0), "r"(c1), "r"(c2) : "memory");
}
__device__ __forceinline__ void tma3d(uint32_t dst, const CUtensorMap* tm, int c0, int c1, int c2, uint32_t bar) {
    asm volatile("cp.async.bulk.tensor.3d.shared::cluster.global.mbarrier::complete_tx::bytes [%0], [%1, {%3, %4, %5}], [%2];"
                 ::"r"(dst), "l"(tm), "r"(bar), "r"(c0), "r"(c1), "r"(c2) : "memory");
}
__device__ __forceinline__ void red_relaxed(unsigned* p) { asm volatile("red.relaxed.gpu.global.add.u32 [%0], 1;" ::"l"(p) : "memory"); }
__device__ __forceinline__ void named_arrive(int id, int n) { asm volatile("bar.arrive %0, %1;" ::"r"(id), "r"(n) : "memory"); }
__device__ __forceinline__ void named_bar(int id, int n) { asm volatile("bar.sync %0, %1;" ::"r"(id), "r"(n) : "memory"); }

__device__ __forceinline__ void wg_fence() { asm volatile("wgmma.fence.sync.aligned;" ::: "memory"); }
__device__ __forceinline__ void wg_commit() { asm volatile("wgmma.commit_group.sync.aligned;" ::: "memory"); }
template <int N> __device__ __forceinline__ void wg_wait() { asm volatile("wgmma.wait_group.sync.aligned %0;" ::"n"(N) : "memory"); }
template <int N> __device__ __forceinline__ void reg_fence(float (&d)[N]) {
#pragma unroll
    for (int i = 0; i < N; i++) asm volatile("" : "+f"(d[i])::"memory");
}

#define F4(a, i) "+f"(a[i]), "+f"(a[i + 1]), "+f"(a[i + 2]), "+f"(a[i + 3])
#define F8(a, i) F4(a, i), F4(a, i + 4)
#define F16(a, i) F8(a, i), F8(a, i + 8)

constexpr uint32_t HI128 = 0x40000040u, HI64 = 0x80000020u;
__device__ __forceinline__ uint32_t desc_lo(uint32_t addr) { return (addr >> 4) | 0x10000u; }

#define R4(a, i) "+r"(a[i]), "+r"(a[i + 1]), "+r"(a[i + 2]), "+r"(a[i + 3])
#define R8(a, i) R4(a, i), R4(a, i + 4)
template <int N> __device__ __forceinline__ void reg_fence(uint32_t (&d)[N]) {
#pragma unroll
    for (int i = 0; i < N; i++) asm volatile("" : "+r"(d[i])::"memory");
}
__device__ __forceinline__ void tma2d(uint32_t dst, const CUtensorMap* tm, int c0, int c1, uint32_t bar) {
    asm volatile("cp.async.bulk.tensor.2d.shared::cluster.global.mbarrier::complete_tx::bytes [%0], [%1, {%3, %4}], [%2];"
                 ::"r"(dst), "l"(tm), "r"(bar), "r"(c0), "r"(c1) : "memory");
}
__device__ __forceinline__ void tma4d(uint32_t dst, const CUtensorMap* tm, int c0, int c1, int c2, int c3, uint32_t bar) {
    asm volatile("cp.async.bulk.tensor.4d.shared::cluster.global.mbarrier::complete_tx::bytes [%0], [%1, {%3, %4, %5, %6}], [%2];"
                 ::"r"(dst), "l"(tm), "r"(bar), "r"(c0), "r"(c1), "r"(c2), "r"(c3) : "memory");
}

template <uint32_t AHI, int ACC>
__device__ __forceinline__ void wgmma_n64_ss(float (&d)[32], uint32_t da, uint32_t db) {
    asm volatile(
        "{\n.reg .pred p;\n.reg .b64 da, db;\nsetp.ne.b32 p, %36, 0;\nmov.b64 da, {%32, %34};\nmov.b64 db, {%33, %35};\n"
        "wgmma.mma_async.sync.aligned.m64n64k16.f32.bf16.bf16 "
        "{%0,%1,%2,%3,%4,%5,%6,%7,%8,%9,%10,%11,%12,%13,%14,%15,%16,%17,%18,%19,%20,%21,%22,%23,%24,%25,%26,%27,%28,%29,%30,%31},"
        "da, db, p, 1, 1, 0, 1;\n}\n"
        : F16(d, 0), F16(d, 16)
        : "r"(da), "r"(db), "n"(AHI), "n"(HI128), "n"(ACC));
}

template <int ACC>
__device__ __forceinline__ void wgmma_n56_ss(float (&d)[28], uint32_t da, uint32_t db) {
    asm volatile(
        "{\n.reg .pred p;\n.reg .b64 da, db;\nsetp.ne.b32 p, %31, 0;\nmov.b64 da, {%28, %30};\nmov.b64 db, {%29, %30};\n"
        "wgmma.mma_async.sync.aligned.m64n56k16.f32.f16.f16 "
        "{%0,%1,%2,%3,%4,%5,%6,%7,%8,%9,%10,%11,%12,%13,%14,%15,%16,%17,%18,%19,%20,%21,%22,%23,%24,%25,%26,%27},"
        "da, db, p, 1, 1, 1, 0;\n}\n"
        : F16(d, 0), F8(d, 16), F4(d, 24)
        : "r"(da), "r"(db), "n"(HI128), "n"(ACC));
}

template <int SA>
__device__ __forceinline__ void wgmma_n160_h(uint32_t (&d)[40], uint32_t da, uint32_t db) {
    asm volatile(
        "{\n.reg .pred p;\n.reg .b64 da, db;\nsetp.eq.b32 p, 0, 0;\nmov.b64 da, {%40, %43};\nmov.b64 db, {%41, %43};\n"
        "wgmma.mma_async.sync.aligned.m64n160k16.f16.f16.f16 "
        "{%0,%1,%2,%3,%4,%5,%6,%7,%8,%9,%10,%11,%12,%13,%14,%15,%16,%17,%18,%19,%20,%21,%22,%23,%24,%25,%26,%27,"
        "%28,%29,%30,%31,%32,%33,%34,%35,%36,%37,%38,%39},"
        "da, db, p, %42, 1, 1, 0;\n}\n"
        : R8(d, 0), R8(d, 8), R8(d, 16), R8(d, 24), R8(d, 32)
        : "r"(da), "r"(db), "n"(SA), "n"(HI128));
}
template <int SA>
__device__ __forceinline__ void wgmma_n160_hr(uint32_t (&d)[40], const uint32_t (&a)[4], uint32_t db) {
    asm volatile(
        "{\n.reg .pred p;\n.reg .b64 db;\nsetp.eq.b32 p, 0, 0;\nmov.b64 db, {%44, %46};\n"
        "wgmma.mma_async.sync.aligned.m64n160k16.f16.f16.f16 "
        "{%0,%1,%2,%3,%4,%5,%6,%7,%8,%9,%10,%11,%12,%13,%14,%15,%16,%17,%18,%19,%20,%21,%22,%23,%24,%25,%26,%27,"
        "%28,%29,%30,%31,%32,%33,%34,%35,%36,%37,%38,%39},"
        "{%40,%41,%42,%43}, db, p, %45, 1, 0;\n}\n"
        : R8(d, 0), R8(d, 8), R8(d, 16), R8(d, 24), R8(d, 32)
        : "r"(a[0]), "r"(a[1]), "r"(a[2]), "r"(a[3]), "r"(db), "n"(SA), "n"(HI128));
}
template <int SA>
__device__ __forceinline__ void wgmma_n160_f(float (&d)[80], uint32_t da, uint32_t db) {
    asm volatile(
        "{\n.reg .pred p;\n.reg .b64 da, db;\nsetp.eq.b32 p, 0, 0;\nmov.b64 da, {%80, %83};\nmov.b64 db, {%81, %83};\n"
        "wgmma.mma_async.sync.aligned.m64n160k16.f32.bf16.bf16 "
        "{%0,%1,%2,%3,%4,%5,%6,%7,%8,%9,%10,%11,%12,%13,%14,%15,%16,%17,%18,%19,%20,%21,%22,%23,%24,%25,%26,%27,"
        "%28,%29,%30,%31,%32,%33,%34,%35,%36,%37,%38,%39,%40,%41,%42,%43,%44,%45,%46,%47,%48,%49,%50,%51,%52,%53,%54,%55,"
        "%56,%57,%58,%59,%60,%61,%62,%63,%64,%65,%66,%67,%68,%69,%70,%71,%72,%73,%74,%75,%76,%77,%78,%79},"
        "da, db, p, %82, 1, 1, 0;\n}\n"
        : F16(d, 0), F16(d, 16), F16(d, 32), F16(d, 48), F16(d, 64)
        : "r"(da), "r"(db), "n"(SA), "n"(HI128));
}

__device__ __forceinline__ uint32_t pack_f16(float lo, float hi) {
    uint32_t r;
    asm("cvt.rn.f16x2.f32 %0, %1, %2;" : "=r"(r) : "f"(hi), "f"(lo));
    return r;
}
__device__ __forceinline__ uint32_t mul_bf16x2(uint32_t a, uint32_t b) {
    uint32_t r;
    asm("mul.rn.bf16x2 %0, %1, %2;" : "=r"(r) : "r"(a), "r"(b));
    return r;
}
__device__ __forceinline__ void sts128(uint32_t p, uint32_t a, uint32_t b, uint32_t c, uint32_t d) {
    asm volatile("st.shared.v4.b32 [%0], {%1,%2,%3,%4};" ::"r"(p), "r"(a), "r"(b), "r"(c), "r"(d) : "memory");
}
__device__ __forceinline__ uint32_t pack_bf16(float lo, float hi) {
    uint32_t r;
    asm("cvt.rn.bf16x2.f32 %0, %1, %2;" : "=r"(r) : "f"(hi), "f"(lo));
    return r;
}
__device__ __forceinline__ void stg128(void* p, uint32_t a, uint32_t b, uint32_t c, uint32_t d) {
    asm volatile("st.global.v4.b32 [%0], {%1,%2,%3,%4};" ::"l"(p), "r"(a), "r"(b), "r"(c), "r"(d) : "memory");
}
__device__ __forceinline__ void stmatrix_x4_t(uint32_t addr, uint32_t a, uint32_t b, uint32_t c, uint32_t d) {
    asm volatile("stmatrix.sync.aligned.m8n8.x4.trans.shared.b16 [%0], {%1,%2,%3,%4};"
                 ::"r"(addr), "r"(a), "r"(b), "r"(c), "r"(d) : "memory");
}

constexpr uint32_t cos64(int k, bool half) {
    constexpr uint16_t q[17] = {0x3F80, 0x3F7F, 0x3F7B, 0x3F75, 0x3F6D, 0x3F62, 0x3F55, 0x3F46, 0x3F35, 0x3F22, 0x3F0E, 0x3EF1, 0x3EC4, 0x3E95, 0x3E48, 0x3DC9, 0x0000};
    constexpr uint16_t h[17] = {0x3C00, 0x3BF6, 0x3BD9, 0x3BA8, 0x3B64, 0x3B0E, 0x3AA7, 0x3A2F, 0x39A8, 0x3913, 0x3872, 0x378B, 0x361F, 0x34A5, 0x323E, 0x2E46, 0x0000};
    k &= 63;
    if (k > 32) k = 64 - k;
    const uint16_t* t = half ? h : q;
    return k <= 16 ? t[k] : (t[32 - k] | 0x8000u);
}
constexpr uint32_t fwd_coef(int s, int p, int t) { return (p && s == 0) ? cos64(32 * t, false) : cos64(s * t - 16 * p, false); }
constexpr uint32_t inv_coef(int l, int phi) {
    const int s = phi >> 1, p = phi & 1;
    if (l >= kMO) return 0;
    const uint32_t c = s == 0 ? cos64(32 * l * p, true) : cos64(s * l + 16 * p, true);
    return (c & 0x7FFF) ? c - ((s == 0 ? 6 : 5) << 10) : 0;
}
struct Tables {
    uint32_t fwd[2048];
    uint32_t inv[2048];
};
constexpr Tables make_tables() {
    Tables t = {};
    for (int i = 0; i < 2048; i++) {
        const int row = i >> 5, tt = 8 * (((i >> 2) & 7) ^ (row & 7)) + 2 * (i & 3), s = 8 * (row >> 4) + (row & 7), p = (row >> 3) & 1;
        t.fwd[i] = fwd_coef(s, p, tt) | (fwd_coef(s, p, tt + 1) << 16);
        t.inv[i] = inv_coef(row, tt) | (inv_coef(row, tt + 1) << 16);
    }
    return t;
}
__device__ __align__(128) const Tables g_tab = make_tables();

constexpr int NCTA = 128;
constexpr int NST = 4;
constexpr int HEND = 56;
constexpr int XB = kNT * 128;
constexpr int OFF_W1 = 0, OFF_X = OFF_W1 + NST * 8192, OFF_W0 = OFF_X + 4 * XB, OFF_RAW = OFF_W0 + NST * 8192;
constexpr int OFF_STG = OFF_RAW + 32768;
constexpr int OFF_U0 = OFF_W0, OFF_U1 = OFF_X, OFF_C1 = OFF_W1, OFF_DIR = OFF_W1 + 8192;
constexpr int OFF_F = OFF_RAW + 65536;
constexpr int OFF_G = OFF_F + 8192;
constexpr int OFF_C0 = OFF_G;
constexpr int OFF_BAR = OFF_G + 4096;
constexpr int B_FULL = 0, B_EMPTY = 8 * NST, B_TSEL = 16 * NST, B_PRE = B_TSEL + 8, B_SIG = B_PRE + 16 * V0, B_YS = B_SIG + 8 * 33,
              B_T2 = B_YS + 8 * 4, B_SUM = B_T2 + 16, B_GATE = B_SUM + 32, B_RDY = B_GATE + 8 * 32, B_PUB = B_RDY + 8 * 33, B_UNIT = B_PUB + 8,
              B_FTAB = B_UNIT + 8 * 20, B_C1 = B_FTAB + 8, B_NRM = B_C1 + 8, B_END = B_NRM + 32;
template <int O0, int O1>
__device__ __forceinline__ void bar_setup(uint32_t bars) {
#pragma unroll
    for (int o = O0; o < O1; o += 8)
        mbar_init(bars + o, o < B_EMPTY ? 2 : o < B_TSEL ? 8 : o == B_TSEL ? 2 : o < B_SIG ? 1 : o < B_YS - 8 ? 8 : o < B_GATE ? 4 : 1);
    fence_mbar_init();
    fence_proxy_async_smem();
}
constexpr int OFF_TS = OFF_BAR + B_END;
constexpr int OFF_PLAN = OFF_TS + 336;
constexpr int OFF_YT = OFF_PLAN + (V0 + 65) * 8;
constexpr int OFF_GB = (OFF_YT + 4 * kNT * 4 + 15) & ~15;
constexpr int MAIN_SMEM = OFF_GB + 2048;
static_assert(MAIN_SMEM <= 232448 && OFF_U0 + 10 * 8192 == OFF_STG + 16384, "shared memory");
constexpr int XPC = 2 * kNT;
constexpr unsigned PROBE_NEAR = 400;

__device__ __forceinline__ uint32_t raw_slot(uint32_t sbase, uint32_t v, int wg) { return sbase + OFF_RAW + ((v & 3) * 2 + wg) * 8192; }

__device__ __forceinline__ uint32_t pre_slot(uint32_t sbase, uint32_t v, int wg) {
    return v < 4 ? raw_slot(sbase, v, wg) : v < 8 ? sbase + OFF_X + (v - 4) * XB + wg * 8192 : sbase + (wg ? OFF_W1 : OFF_W0) + ((V0 + 3) % NST) * 8192;
}
constexpr int OFF_TMP = OFF_W1 + 8192;

template <bool DC, int I>
__device__ __forceinline__ void gemm_mma(uint32_t (&a0)[40], uint32_t (&a1)[40], uint32_t dx0, uint32_t dx1, uint32_t dw) {
    constexpr int ks = I >> 2;
    const uint32_t A0 = dw + ks * 128, A1 = A0 + 256, B0 = dx0 + ks * 2, B1 = dx1 + ks * 2;
    if ((I & 3) == 0) wgmma_n160_h<1>(a0, A0, B0);
    if ((I & 3) == 1) wgmma_n160_h<1>(a1, A1, DC ? B1 : B0);
    if ((I & 3) == 2 && !DC) wgmma_n160_h<1>(a0, A1, B1);
    if ((I & 3) == 3 && !DC) wgmma_n160_h<-1>(a1, A0, B1);
}

template <bool DC, int I0, int I1>
__device__ __forceinline__ void gemm_mmas(uint32_t (&a0)[40], uint32_t (&a1)[40], uint32_t dx0, uint32_t dx1, uint32_t dw) {
    if constexpr (I0 < I1) {
        gemm_mma<DC, I0>(a0, a1, dx0, dx1, dw);
        gemm_mmas<DC, I0 + 1, I1>(a0, a1, dx0, dx1, dw);
    }
}
static_assert(RX == 4 && RW == 10, "placement of the output spectra");
__device__ __forceinline__ uint32_t y_unit(uint32_t db, uint32_t tau, uint32_t b, uint32_t pmask) {
    const uint32_t n = (((db >> 1) & 2) + (db & 1)) * XPC + ((db >> 1) & 1) * kNT + tau, r = n / 3;
    return run_off(r + (r >= 192 && r < 278 ? (r < 214 ? 64 : -22) : 0), n % 3, b, pmask);
}
__device__ __forceinline__ int y_gate(int t) { return t ? 28 + t : 27; }
__device__ __forceinline__ int step_k(int h) { return h < HEND ? h >> 1 : 28 + (h & 3); }
__device__ __forceinline__ int step_m(int h) { return h < HEND ? h & 1 : (h >> 2) & 1; }
constexpr uint64_t x_mask() {
    uint64_t r = 2 | (3ull << 58);
    for (int v = 2; v < 58; v++)
        if ((0x73 >> (v & 7)) & 1) r |= 1ull << v;
    return r;
}
constexpr uint64_t XMASK = x_mask();
__device__ __forceinline__ int x_round(int v, int wg) {
    return v == 0 ? wg : (v < 60 && wg != (v & 1) && ((XMASK >> v) & 1)) ? 1 + __popcll(XMASK << (63 - v)) : -1;
}
__device__ __forceinline__ int w_step(int v, int wg) {
    return v == 0 ? -1 : v < 60 ? (wg == (v & 1) ? v - 1 : -1) : v < 62 ? 2 * v - 61 + wg : (v == 62 && wg == 1) ? 63 : -1;
}

__device__ __forceinline__ uint32_t plan_word(int v, int wg, int cta) {
    const int r = x_round(v, wg), h = w_step(v, wg);
    if (r < 0 && h < 0) return 0;
    const bool last = v >= 60 || (v & 1) || (v > 0 && wg == 0 && x_round(v + 1, 0) < 0);
    uint32_t off, row, gate;
    if (r >= 0) {
        const int u = r * NCTA + cta, cb = u / XPC, i = u - cb * XPC, b = i >= kNT, tau = i - b * kNT;
        row = tau & 63;
        off = (((cb % RX) * 64 + b) << 16) + ((tau >> 6) << 14) + b + 2;
        gate = cb >= RX ? 2 * (cb - RX) + 2 : 0;
    } else {
        const int ring = (h + RW - 64 % RW) % RW;
        row = 0;
        off = ((ring * 22) << 16) + (ring << 12) + 4;
        gate = h >= RW ? ((h - RW + 1) >> 1) + 1 : 0;
    }
    return (off + row * 128) | ((row & 7) << 4) | (last << 3) | ((v > 60) << 24) | (gate << 26);
}

struct Xf {
    uint32_t sbase;
    uint8_t *px, *pw;
    uint32_t cx, cw;
    uint32_t xsw;
    uint32_t dw;
    uint32_t e;
    int lane;
};
__device__ __forceinline__ uint32_t plan_load(const Xf& f, uint32_t v, int wg) {
    uint32_t e;
    asm volatile("ld.shared.u32 %0, [%1];" : "=r"(e) : "r"(f.sbase + OFF_PLAN + v * 8 + wg * 4));
    return __shfl_sync(0xffffffffu, e, 0);
}
template <bool W>
__device__ __forceinline__ void unit_mma(float (&acc)[32], const Xf& f, uint32_t raw) {
    const uint32_t dB = desc_lo(raw);
    if (W) {
        const uint32_t dG = desc_lo(f.sbase + OFF_G);
        wgmma_n64_ss<HI64, 0>(acc, dG, dB);
        wgmma_n64_ss<HI64, 1>(acc, dG + 2, dB + 128);
    } else {
        const uint32_t dF = desc_lo(f.sbase + OFF_F);
        wgmma_n64_ss<HI128, 0>(acc, dF, dB);
        wgmma_n64_ss<HI128, 1>(acc, dF + 2, dB + 128);
        wgmma_n64_ss<HI128, 1>(acc, dF + 4, dB + 256);
        wgmma_n64_ss<HI128, 1>(acc, dF + 6, dB + 384);
    }
    wg_commit();
}
constexpr int DROP = 3;
__device__ __forceinline__ uint32_t pack_sp(float lo, float hi) {
    const uint32_t r = pack_f16(lo, hi);
    return DROP ? (r + (0x10001u << DROP >> 1)) & ~(((1u << DROP) - 1) * 0x10001u) : r;
}
__device__ __forceinline__ void st_quad(uint8_t* p, const float (&acc)[32], int j0) {
    stg128(p, pack_sp(acc[j0], acc[j0 + 1]), pack_sp(acc[j0 + 4], acc[j0 + 5]), pack_sp(acc[j0 + 8], acc[j0 + 9]),
           pack_sp(acc[j0 + 12], acc[j0 + 13]));
}
template <bool W>
__device__ __forceinline__ void unit_store(float (&acc)[32], const Xf& f, uint32_t e) {
    const uint32_t sel = ((W ? f.cw >> (8 + ((e >> 12) & 15)) : e ^ (f.cx >> (8 + ((e >> 21) & 6)))) & 1) << 13;
    const uint32_t o = (e & (W ? 0xFF0F80u : 0xFFFF80u)) + ((e ^ (W ? f.cw : f.cx)) & 0x70);
    uint8_t* const b = W ? f.pw : f.px;
    uint8_t *p0 = b + (o + sel), *p1 = b + ((o ^ 64) + sel);
    reg_fence(acc);
    if (W) {
        st_quad(p0, acc, 0);
        st_quad(p1, acc, 16);
        st_quad(p0 + 4096, acc, 2);
        st_quad(p1 + 4096, acc, 18);
    } else {
        const int d = 131072 + 8192 - 2 * (int)sel;
        st_quad(p0, acc, 0);
        st_quad(p1, acc, 2);
        st_quad(p0 + d, acc, 16);
        st_quad(p1 + d, acc, 18);
    }
}
__device__ __forceinline__ void unit_done(const Xf& f, uint32_t e, uint32_t v) {
    if (e & 8) {
        __syncwarp();
        if (f.lane == 0) mbar_arrive(f.sbase + OFF_BAR + B_SIG + 8 * ((v >> 1) + ((e >> 24) & 1)));
    }
}
__device__ __forceinline__ void step_wait(Xf& f, uint32_t v, int wg) {
    const uint32_t bars = f.sbase + OFF_BAR;
    if (f.e >> 26) mbar_wait(bars + B_GATE - 8 + 8 * (f.e >> 26), 0);
    mbar_wait(bars + B_FULL + 8 * (v % NST), (v / NST) & 1);
}

template <bool DC, int KIND>
__device__ __forceinline__ void gemm_step(uint32_t (&a0)[40], uint32_t (&a1)[40], float (&at)[32], Xf& f, uint32_t v, uint32_t xs, int wg, bool first) {
    const uint32_t bars = f.sbase + OFF_BAR, sb = desc_lo(f.sbase), xb = sb + OFF_X / 16 + xs * (XB / 16), raw = raw_slot(f.sbase, v, wg);
    const uint32_t dx0 = xb + f.xsw, dx1 = xb + (f.xsw ^ 4), dw = f.dw + (v % NST) * 512, e = f.e;
    wg_fence();
    if (KIND) unit_mma<KIND != 1>(at, f, raw);
    constexpr int N1 = KIND == 0 ? 2 : NPRE;
    gemm_mmas<DC, 0, N1>(a0, a1, dx0, dx1, dw);
    wg_commit();
    f.e = plan_load(f, v + 1, wg);
    wg_wait<1>();
    if (!KIND && !first && f.lane == 0) mbar_arrive(bars + B_EMPTY + 8 * ((v - 1) % NST));
    if (KIND) unit_store<KIND != 1>(at, f, e);
    if (KIND) unit_done(f, e, v);
    gemm_mmas<DC, N1, 7>(a0, a1, dx0, dx1, dw);
    if (KIND && !first && f.lane == 0) mbar_arrive(bars + B_EMPTY + 8 * ((v - 1) % NST));
    gemm_mma<DC, 7>(a0, a1, dx0, dx1, dw);
    wg_commit();
}
template <bool DC>
__device__ __forceinline__ void any_step(uint32_t (&a0)[40], uint32_t (&a1)[40], float (&at)[32], Xf& f, uint32_t v, uint32_t xs, int wg, bool first) {
    step_wait(f, v, wg);
    const uint32_t kind = (f.e >> 1) & 3;
    if (kind == 1) gemm_step<DC, 1>(a0, a1, at, f, v, xs, wg, first);
    else if (kind == 2) gemm_step<DC, 2>(a0, a1, at, f, v, xs, wg, first);
    else gemm_step<DC, 0>(a0, a1, at, f, v, xs, wg, first);
}
template <bool DC>
__device__ __forceinline__ void gemm_main(uint32_t (&a0)[40], uint32_t (&a1)[40], uint32_t (&b0)[40], uint32_t (&b1)[40], Xf& f, int wg) {
    float at[32];
#pragma unroll 1
    for (uint32_t k = 0; k < HEND / 2; k++) {
        any_step<DC>(a0, a1, at, f, V0 + 2 * k, k & 3, wg, k == 0);
        any_step<DC>(b0, b1, at, f, V0 + 2 * k + 1, k & 3, wg, false);
    }
    wg_wait<0>();
    if (f.lane == 0) mbar_arrive(f.sbase + OFF_BAR + B_EMPTY + 8 * ((V0 + HEND - 1) % NST));
}
__device__ __forceinline__ void w_fetch(uint32_t (&d)[4][4], const Xf& f, uint32_t v) {
    const uint32_t bars = f.sbase + OFF_BAR, lane = f.lane;
    const uint32_t wa = ((f.dw & 0xFFFF) << 4) + (v % NST) * 8192 + (lane >> 4) * 1024 + (lane & 7) * 128 +
                        (((((threadIdx.x >> 4) & 6) + ((lane >> 3) & 1)) ^ (lane & 7)) << 4);
    mbar_wait(bars + B_FULL + 8 * (v % NST), (v / NST) & 1);
#pragma unroll
    for (int i = 0; i < 4; i++)
        asm volatile("ldmatrix.sync.aligned.m8n8.x4.trans.shared.b16 {%0,%1,%2,%3}, [%4];" : "=r"(d[i][0]), "=r"(d[i][1]), "=r"(d[i][2]), "=r"(d[i][3])
                     : "r"(wa + i * 2048) : "memory");
}
__device__ __forceinline__ void store_tile(uint32_t (&a0)[40], uint32_t (&a1)[40], const uint32_t (&b0)[40], const uint32_t (&b1)[40], uint32_t (&wn)[4][4],
                                           const Xf& f, bool first, uint32_t stg, int t, int wg, uint8_t* sp, int slot, uint32_t ytab, int wsw) {
    const int w = t >> 5, lane = t & 31, m = lane >> 3, i8 = lane & 7;
    const uint32_t addr = stg + i8 * 256 + (m >> 1) * 128 + (((2 * w + (m & 1)) ^ i8 ^ wsw) << 4);
    const int row = 2 * w + (lane >> 4), phi = 2 * slot + (m & 1);
    const uint32_t src = stg + row * 256 + (m & 1) * 128 + ((i8 ^ row) << 4);
    uint8_t* dst = sp + phi * 128 + ((i8 ^ (phi & 7)) << 4);
    named_bar(2 + wg, 128);
#pragma unroll
    for (int r = 0; r < 6; r++) {
        uint32_t v[4][4], o[4];
        if (r > 0) {
#pragma unroll
            for (int i = 0; i < 4; i++) {
                asm volatile("ld.shared.u32 %0, [%1];" : "=r"(o[i]) : "r"(ytab + (32 * (r - 1) + 8 * i + row) * 4) : "memory");
                asm volatile("ld.shared.v4.b32 {%0,%1,%2,%3}, [%4];" : "=r"(v[i][0]), "=r"(v[i][1]), "=r"(v[i][2]), "=r"(v[i][3])
                             : "r"(src + ((r - 1) & 1) * 8192 + i * 2048) : "memory");
            }
        }
        if (r < 5) {
#pragma unroll
            for (int j = 4 * r; j < 4 * r + 4; j++) stmatrix_x4_t(addr + (r & 1) * 8192 + (j & 3) * 2048, a0[2 * j], a0[2 * j + 1], a1[2 * j], a1[2 * j + 1]);
#pragma unroll
            for (int j = 8 * r; j < 8 * r + 8; j++) {
                asm volatile("mov.b32 %0, %1;" : "=r"(a0[j]) : "r"(b0[j]));
                asm volatile("mov.b32 %0, %1;" : "=r"(a1[j]) : "r"(b1[j]));
            }
        } else if (first) {
            w_fetch(wn, f, V0 + HEND + 4);
        }
        if (r > 0) {
#pragma unroll
            for (int i = 0; i < 4; i++) stg128(dst + o[i], v[i][0], v[i][1], v[i][2], v[i][3]);
        }
        if (r < 5) named_bar(2 + wg, 128);
    }
}

template <bool DC>
__device__ __forceinline__ void gemm_last(uint32_t (&a0)[40], uint32_t (&a1)[40], uint32_t (&w)[2][4][4], const Xf& f, int wg, int m) {
    const uint32_t bars = f.sbase + OFF_BAR, sb = desc_lo(f.sbase), v0 = V0 + HEND + 4 * m;
    if (2 * m + wg > 0) named_bar(3 + 2 * m + wg, 256);
#pragma unroll
    for (uint32_t k = 0; k < 4; k++) {
        const uint32_t xb = sb + OFF_X / 16 + k * (XB / 16), dx0 = xb + f.xsw, dx1 = xb + (f.xsw ^ 4);
        wg_fence();
#pragma unroll
        for (int ks = 0; ks < 2; ks++) {
            wgmma_n160_hr<1>(a0, w[k & 1][ks], dx0 + 2 * ks);
            wgmma_n160_hr<1>(a1, w[k & 1][2 + ks], (DC ? dx1 : dx0) + 2 * ks);
            if (!DC) wgmma_n160_hr<1>(a0, w[k & 1][2 + ks], dx1 + 2 * ks);
            if (!DC) wgmma_n160_hr<-1>(a1, w[k & 1][ks], dx1 + 2 * ks);
        }
        wg_commit();
        if (m == 0 && f.lane == 0) mbar_arrive(bars + B_EMPTY + 8 * ((v0 + k) % NST));
        if (k == 3 && 2 * m + wg < 3) named_arrive(4 + 2 * m + wg, 256);
        if (k > 0) wg_wait<1>();
        if (k < 3) w_fetch(w[(k + 1) & 1], f, v0 + k + 1);
    }
    wg_wait<0>();
    if (m && f.lane == 0) mbar_arrive(bars + B_T2 + 8 * wg);
}

__device__ __forceinline__ float gelu_half(float hv) {
    float th;
    asm("tanh.approx.f32 %0, %1;" : "=f"(th) : "f"(hv * fmaf(hv * hv, 8.0f * 0.7978845608028654f * 0.044715f, 2.0f * 0.7978845608028654f)));
    return fmaf(hv, th, hv);
}
__device__ __noinline__ void direct_block(const __nv_bfloat16* __restrict__ x, const __nv_bfloat16* __restrict__ w,
                                          const __nv_bfloat16* __restrict__ gamma, const __nv_bfloat16* __restrict__ beta,
                                          __nv_bfloat16* __restrict__ out, float* sm, int b, int db, int part, uint32_t epoch) {
    float *xs = sm, *ws = sm + 32 * 17, *red = ws + 16 * 65;
    const int tid = threadIdx.x & 127, bar = 2 + (threadIdx.x >> 7), tx = tid & 15, ty = tid >> 4, row0 = part * 250, lim = min(250, kL - row0);
    float* h = g_direct + (size_t)((b * 8 + db) * 32 + part) * (250 * 64);
    for (int l0 = 0; l0 < lim; l0 += 32) {
        float acc[4][4] = {};
        for (int k0 = 0; k0 < 31 * 512; k0 += 16) {
            named_bar(bar, 128);
            for (int i = tid; i < 1024; i += 128) {
                if (i < 512) xs[(i >> 4) * 17 + (i & 15)] = __bfloat162float(x[((size_t)b * kRows + row0 + min(l0 + (i >> 4), lim - 1)) * 1024 + k0 + (i & 15)]);
                ws[(i >> 6) * 65 + (i & 63)] = __bfloat162float(w[(size_t)(k0 + (i >> 6)) * 512 + 64 * db + (i & 63)]);
            }
            named_bar(bar, 128);
            for (int k = 0; k < 16; k++)
#pragma unroll
                for (int i = 0; i < 4; i++)
#pragma unroll
                    for (int j = 0; j < 4; j++) acc[i][j] = fmaf(xs[(ty * 4 + i) * 17 + k], ws[k * 65 + tx * 4 + j], acc[i][j]);
        }
#pragma unroll
        for (int i = 0; i < 4; i++)
#pragma unroll
            for (int j = 0; j < 4; j++)
                if (l0 + ty * 4 + i < lim) h[(l0 + ty * 4 + i) * 64 + tx * 4 + j] = acc[i][j];
    }
    const int c = tid & 63;
    float mean = 0.f, var = 0.f;
    for (int r = 0; r < 2; r++) {
        named_bar(bar, 128);
        float s = 0.f;
        for (int l = tid >> 6; l < lim; l += 2) {
            const float v = h[l * 64 + c] - mean;
            s += r ? v * v : v;
        }
        red[tid] = s;
        named_bar(bar, 128);
        unsigned long long* p = g_dpart + ((r * 16 + b * 8 + db) * 32) * 64 + c;
        if (tid < 64)
            asm volatile("st.relaxed.gpu.global.v2.b32 [%0], {%1, %2};" ::"l"(p + part * 64), "r"(__float_as_uint(red[c] + red[64 + c])), "r"(epoch) : "memory");
        s = 0.f;
        for (int k = 0; k < 32; k++) {
            unsigned long long v = 0;
#pragma unroll 1
            for (uint32_t n = 0; n < (1u << 19); n++) {
                asm volatile("ld.relaxed.gpu.global.u64 %0, [%1];" : "=l"(v) : "l"(p + k * 64) : "memory");
                if ((uint32_t)(v >> 32) == epoch) break;
                __nanosleep(200);
            }
            s += __uint_as_float((uint32_t)v);
        }
        (r ? var : mean) = s * (1.0f / kL);
    }
    const float a = __bfloat162float(gamma[64 * db + c]) / sqrtf(var + 1e-5f), be = __bfloat162float(beta[64 * db + c]);
    for (int l = tid >> 6; l < lim; l += 2)
        out[((size_t)b * kL + row0 + l) * 512 + 64 * db + c] = __float2bfloat16(gelu_half(0.5f * fmaf(h[l * 64 + c] - mean, a, be)));
    named_bar(bar, 128);
}

__device__ __forceinline__ int tail_block(uint32_t gr, int t) { return 4 * (t >> 1) + ((gr >> 4) & 2) + (t & 1); }
__device__ __forceinline__ void tail_poll(uint8_t* sp, uint32_t gr, int t) {
#pragma unroll 1
    for (uint32_t n = 0; n < (1u << 15); n++) {
        unsigned v;
        asm volatile("ld.relaxed.gpu.global.u32 %0, [%1];" : "=r"(v) : "l"(y_flag(sp, gr >> 6, tail_block(gr, t))) : "memory");
        if (v >= 32) break;
        __nanosleep(YSLEEP);
    }
    asm volatile("fence.acquire.gpu;" ::: "memory");
    asm volatile("fence.proxy.async.global;" ::: "memory");
}
__device__ __forceinline__ void tail_loads(uint32_t sbase, const uint8_t* sp, uint32_t gr, uint32_t pmask, int u0, int u1, int lane) {
    if (lane >= u0 && lane < u1) {
        const uint32_t bar = sbase + OFF_BAR + B_UNIT + 8 * lane;
        mbar_expect_tx(bar, 8192);
        bulk_g2s(sbase + (lane < 10 ? OFF_U0 : OFF_U1 - 81920) + lane * 8192, sp + y_unit(tail_block(gr, lane / 5), (gr & 31) * 5 + lane % 5, gr >> 6, pmask), 8192, bar);
    }
    __syncwarp();
}
__device__ __forceinline__ const float* corr_src(uint32_t gr, int t) { return &g_corr[(((gr >> 6) * 8 + tail_block(gr, t)) * kNT + (gr & 31) * 5) * 64]; }
__device__ __forceinline__ void corr_load(uint32_t sbase, uint32_t gr, int t, uint32_t bar) {
    bulk_g2s(sbase + (t < 2 ? OFF_C0 : OFF_C1) + (t & 1) * 1280, corr_src(gr, t), 1280, bar);
}
__device__ __forceinline__ void tail_phase(uint32_t sbase, uint8_t* smem, uint8_t* sp, int wg, uint32_t gr, float sx, float sw, const __nv_bfloat16* __restrict__ x,
                                           const __nv_bfloat16* __restrict__ wt, const __nv_bfloat16* __restrict__ gamma,
                                           const __nv_bfloat16* __restrict__ beta, __nv_bfloat16* __restrict__ out) {
    const uint32_t* ts = reinterpret_cast<const uint32_t*>(smem + OFF_TS);
    const int tid = threadIdx.x, w = (tid >> 5) & 3, lane = tid & 31, g = lane >> 2, q = lane & 3;
    const int b = gr >> 6, part = gr & 31;
#pragma unroll 1
    for (int rd = 0; rd < 4 - wg; rd++) {
        if (rd < 2) {
            float acc[28], acc2[28], s[8] = {0.f, 0.f, 0.f, 0.f, 0.f, 0.f, 0.f, 0.f};
            const float swq = q == 0 ? sw : 0.f;
            const int t = 2 * rd + wg;
            const uint32_t ub = sbase + (t < 2 ? OFF_U0 : OFF_U1) + (t & 1) * 40960, ubar = sbase + OFF_BAR + B_UNIT + 40 * t;
            const float* c1 = reinterpret_cast<const float*>(smem + (t < 2 ? OFF_C0 : OFF_C1) + (t & 1) * 1280) + 16 * w + g;
            const uint32_t ka = ub + (lane >> 4) * 1024 + (lane & 7) * 128 + (((2 * w + ((lane >> 3) & 1)) ^ (lane & 7)) << 4);
            auto inverse = [&](float (&d)[28], int u) {
                const uint32_t dA = desc_lo(ub + u * 8192), dB = desc_lo(sbase + OFF_F);
                wg_fence();
                wgmma_n56_ss<0>(d, dA, dB);
                wgmma_n56_ss<1>(d, dA + 128, dB + 2);
                wgmma_n56_ss<1>(d, dA + 256, dB + 4);
                wgmma_n56_ss<1>(d, dA + 384, dB + 6);
                wg_commit();
            };
            auto keep = [&](float (&d)[28], int u, int un) {
                const bool ok = mbar_try(ubar + 8 * un, 0);
                reg_fence(d);
                d[25] = fmaf(c1[u * 64] * sx, swq, d[25]);
                d[27] = fmaf(c1[u * 64 + 8] * sx, swq, d[27]);
                if (part == 31 && u == 4) {
                    if (q >= 2) d[16] = d[18] = 0.f;
                    if (q >= 1) d[17] = d[19] = 0.f;
#pragma unroll
                    for (int i = 20; i < 28; i++) d[i] = 0.f;
                }
                const uint32_t a = ka + u * 8192;
#pragma unroll
                for (int j = 0; j < 6; j += 2)
                    stmatrix_x4_t(a + j * 1024, pack_f16(d[4 * j], d[4 * j + 1]), pack_f16(d[4 * j + 2], d[4 * j + 3]),
                                  pack_f16(d[4 * j + 4], d[4 * j + 5]), pack_f16(d[4 * j + 6], d[4 * j + 7]));
                asm volatile("stmatrix.sync.aligned.m8n8.x2.trans.shared.b16 [%0], {%1,%2};"
                             ::"r"(a + 6 * 1024), "r"(pack_f16(d[24], d[25])), "r"(pack_f16(d[26], d[27])) : "memory");
#pragma unroll
                for (int i = 0; i < 28; i++) {
                    s[i & 3] += d[i];
                    s[4 + (i & 3)] = fmaf(d[i], d[i], s[4 + (i & 3)]);
                }
#pragma unroll
                for (int i = 0; i < 8; i++) asm volatile("" : "+f"(s[i]));
                if (!ok) mbar_wait(ubar + 8 * un, 0);
                wg_wait<0>();
            };
            if (t >= 2) mbar_wait(sbase + OFF_BAR + B_C1, 0);
            mbar_wait(ubar, 0);
            inverse(acc, 0);
            mbar_wait(ubar + 8, 0);
            wg_wait<0>();
#pragma unroll 1
            for (int u = 0;; u += 2) {
                inverse(acc2, min(u + 1, 4));
                keep(acc, u, min(u + 2, 4));
                if (u == 4) break;
                inverse(acc, u + 2);
                keep(acc2, u + 1, min(u + 3, 4));
            }
#pragma unroll
            for (int i = 0; i < 4; i++) s[i] = s[2 * i] + s[2 * i + 1];
#pragma unroll
            for (int i = 0; i < 2; i++) s[i] = (q & 2 ? s[2 + i] : s[i]) + __shfl_xor_sync(0xffffffffu, q & 2 ? s[i] : s[2 + i], 2);
            const float mine = (q & 1 ? s[1] : s[0]) + __shfl_xor_sync(0xffffffffu, q & 1 ? s[0] : s[1], 1);
            asm volatile("red.relaxed.gpu.global.add.u64 [%0], %1;"
                         ::"l"(part_sums(sp, b, tail_block(gr, t), ts[76]) + 2 * (16 * w + 8 * (q & 1) + g) + (q >> 1)),
                         "l"(fabsf(mine) < 0x1p25f ? __float2ll_rn(mine * 0x1p21f) * 4096 + 1 : 65ll) : "memory");
            __syncwarp();
            if (lane == 0) mbar_arrive(sbase + OFF_BAR + B_SUM + 8 * t);
            if (rd == 0) continue;
        }
        const int t = rd == 3 ? 3 : 2 * rd - 2 + wg, db = tail_block(gr, t), i0 = rd == 3 ? FCUT : 0, i1 = rd == 2 && wg ? FCUT : 256;
#pragma unroll 1
        for (uint32_t n = 0; n < (1u << 20); n++)
            if (mbar_try(sbase + OFF_BAR + B_NRM + 8 * t, 0)) break;
        if (reinterpret_cast<const volatile uint32_t*>(ts)[77 + t]) {
            if (rd < 3) direct_block(x, wt, gamma, beta, out, reinterpret_cast<float*>(smem + OFF_DIR + wg * 8192), b, db, part, ts[76]);
            continue;
        }
        const int jh = g & 1, r0 = 4 * w;
        const int lim = min(250, kL - part * 250) - r0 - (g >> 1);
        float na[8], nb[8];
#pragma unroll
        for (int i = 0; i < 8; i += 2) {
            const float4 v = reinterpret_cast<const float4*>(smem + OFF_GB)[32 * t + 16 * jh + 2 * i + q];
            na[i] = v.x; nb[i] = v.y; na[i + 1] = v.z; nb[i + 1] = v.w;
        }
        __nv_bfloat16* o = out + ((size_t)b * kL + part * 250 + i0 + r0 + (g >> 1)) * 512 + 64 * db + 32 * jh + 8 * q;
        const int row = i0 + r0 + ((lane >> 1) & 3);
        int l = row % kMO;
        uint32_t ra = sbase + (t < 2 ? OFF_U0 : OFF_U1) + (t & 1) * 40960 + row / kMO * 8192 + l * 128;
        const int cc = 4 * (lane & 1) + (lane >> 3);
        auto fetch = [&](uint32_t (&r)[4]) {
            asm volatile("ldmatrix.sync.aligned.m8n8.x4.shared.b16 {%0,%1,%2,%3}, [%4];"
                         : "=r"(r[0]), "=r"(r[1]), "=r"(r[2]), "=r"(r[3]) : "r"(ra + (((cc ^ l) & 7) << 4)) : "memory");
            const bool wrap = l >= kMO - 16;
            l += wrap ? 16 - kMO : 16;
            ra += wrap ? 2048 + 8192 - kMO * 128 : 2048;
        };
        auto gelu8 = [&](const uint32_t (&r)[4], uint32_t (&p)[4]) {
#pragma unroll
            for (int i = 0; i < 4; i++) {
                float lo, hi;
                asm("{\n.reg .b16 a, b;\nmov.b32 {a, b}, %2;\ncvt.f32.f16 %0, a;\ncvt.f32.f16 %1, b;\n}" : "=f"(lo), "=f"(hi) : "r"(r[i]));
                p[i] = pack_bf16(gelu_half(fmaf(lo, na[2 * i], nb[2 * i])), gelu_half(fmaf(hi, na[2 * i + 1], nb[2 * i + 1])));
            }
        };
        uint32_t r[2][4], rn[2][4];
        fetch(r[0]);
        fetch(r[1]);
#pragma unroll 1
        for (int i = i0; i < i1; i += 32) {
            fetch(rn[0]);
            fetch(rn[1]);
            uint32_t p0[4], p1[4];
            gelu8(r[0], p0);
            gelu8(r[1], p1);
            if (i < lim) stg128(o, p0[0], p0[1], p0[2], p0[3]);
            if (i + 16 < lim) stg128(o + 16 * 512, p1[0], p1[1], p1[2], p1[3]);
            o += 32 * 512;
#pragma unroll
            for (int k = 0; k < 4; k++) { r[0][k] = rn[0][k]; r[1][k] = rn[1][k]; }
        }
    }
}
__device__ __forceinline__ void channel_scales(uint32_t sbase, uint8_t* smem, uint8_t* sp, int lane) {
    volatile uint32_t* ts = reinterpret_cast<volatile uint32_t*>(smem + OFF_TS);
    const uint32_t gr = ts[64], bars = sbase + OFF_BAR;
#pragma unroll 1
    for (int t = 0; t < 4; t++) {
#pragma unroll 1
        for (uint32_t n = 0; n < (1u << 20); n++)
            if (mbar_try(bars + B_SUM + 8 * t, 0)) break;
        long long s[4];
#pragma unroll 1
        for (uint32_t n = 0; n < (1u << 19); n++) {
            const unsigned long long* p = part_sums(sp, gr >> 6, tail_block(gr, t), ts[76]) + 4 * lane;
#pragma unroll
            for (int i = 0; i < 4; i++) asm volatile("ld.relaxed.gpu.global.u64 %0, [%1];" : "=l"(s[i]) : "l"(p + i) : "memory");
            if (__all_sync(0xffffffffu, s[0] & s[1] & s[2] & s[3] & 32)) break;
        }
        const float sx = __uint_as_float(ts[74]), sw = __uint_as_float(ts[75]);
        bool bad = false;
#pragma unroll
        for (int i = 0; i < 2; i++) {
            const float mean = (float)(s[2 * i] >> 12) * (0x1p-21f / kL), sq = (float)(s[2 * i + 1] >> 12) * (0x1p-21f / kL);
            float2* gb = reinterpret_cast<float2*>(smem + OFF_GB) + 64 * t + 2 * lane + i;
            const float den = fmaxf(sq - mean * mean, 0.f) + 1e-5f * sx * sw * sx * sw, a = gb->x * rsqrtf(den);
            *gb = make_float2(0.5f * a, 0.5f * (gb->y - mean * a));
            bad |= ((s[2 * i] | s[2 * i + 1]) & 0xFC0) || !(den >= 0x1p-22f);
        }
        bad = __any_sync(0xffffffffu, bad);
        if (lane == 0) ts[77 + t] = bad;
        __syncwarp();
        if (lane == 0) mbar_arrive(bars + B_NRM + 8 * t);
    }
}

__device__ __forceinline__ void publish_tiles(uint8_t* sp, uint32_t bars, int cta, int wg) {
#pragma unroll 1
    for (int m = 0; m < 2; m++) {
        mbar_wait(bars + B_YS + 8 * (2 * m + wg), 0);
        asm volatile("fence.acq_rel.gpu;" ::: "memory");
        red_relaxed(y_flag(sp, (cta >> 1) & 1, 4 * m + 2 * (cta & 1) + wg));
    }
}

__global__ void __launch_bounds__(384, 1)
main_kernel(const __grid_constant__ CUtensorMap tmx, const __grid_constant__ CUtensorMap tmw0, const __grid_constant__ CUtensorMap tmw1,
            const __nv_bfloat16* __restrict__ x, const __nv_bfloat16* __restrict__ wt, const __nv_bfloat16* __restrict__ gamma,
            const __nv_bfloat16* __restrict__ beta, __nv_bfloat16* __restrict__ out) {
    extern __shared__ __align__(1024) uint8_t smem_raw[];
    const uint32_t sbase = smem_u32(smem_raw) & ~1023u;
    const uint32_t bars = sbase + OFF_BAR;
    const int tid = threadIdx.x, wg = __shfl_sync(0xffffffffu, tid >> 7, 0), lane = tid & 31;
    const int cta = blockIdx.x;
    volatile uint32_t* ts = reinterpret_cast<volatile uint32_t*>(smem_raw + OFF_TS);
    uint8_t* const sp = reinterpret_cast<uint8_t*>((reinterpret_cast<uintptr_t>(g_sp) + (2u << 20) - 1) & ~(uintptr_t)((2u << 20) - 1));
    const bool probing = (cta & 3) == 0 && lane == 0 && tid < 128 && (tid >= 64 || cta < 4 * NPAGES);
    unsigned* pw = reinterpret_cast<unsigned*>(sp + (tid < 64 ? ((cta >> 2) << 21) + ((tid & 32) ? 15 : 13) * 4096
                                                              : ((tid & 32) ? 0 : 14) * 4096 + (cta >> 2) * 128));
    unsigned pv = 0;
    if (probing) {
        stg128(pw, 0, 0, 0, 0);
        stg128(pw + 4, 0, 0, 0, 0);
        asm volatile("atom.relaxed.gpu.global.exch.b32 %0, [%1], %2;" : "=r"(pv) : "l"(pw), "r"(7) : "memory");
    }
    if (tid == 320) bar_setup<0, B_SIG>(bars);
    if (tid >= 256 && tid < 262) ts[68 + tid - 256] = tid < 260 ? 0xffffu : 0;
    if (tid == 383) asm volatile("griddepcontrol.launch_dependents;");
    __syncthreads();

    if (wg == 2) {
        asm volatile("setmaxnreg.dec.sync.aligned.u32 40;");
        const int role = (tid >> 5) & 3;
        if (role == 3) {
            unsigned v = 0;
#pragma unroll 1
            for (uint32_t n = 0; n < (1u << 15); n++) {
                asm volatile("ld.relaxed.gpu.global.u32 %0, [%1];" : "=r"(v) : "l"(&g_tsel[lane]) : "memory");
                if (__all_sync(0xffffffffu, v & 16)) break;
                __nanosleep(TSLEEP);
            }
            const uint32_t m1 = __ballot_sync(0xffffffffu, v & 8), below = (1u << lane) - 1;
            const int rank = (v & 8) ? 32 - __popc(m1) + __popc(m1 & below) : __popc(~m1 & below);
            ts[lane] = rank;
            ts[32 + rank] = lane;
            const uint32_t p0 = __ballot_sync(0xffffffffu, v & 1);
            if (lane == 0) ts[66] = p0;
            if (lane == (cta >> 2)) ts[64] = rank * 4 + (cta & 3);
            const int part = (m1 >> (cta >> 2)) & 1;
            __syncwarp();
            if (lane == 0) mbar_arrive(bars + B_TSEL);
            mbar_wait(bars + B_TSEL, 0);
            mbar_wait(bars + B_PUB, 0);
            int gc = 0;
            const int gend = lane == 0 ? 33 : lane == 1 ? 32 : 0;
#pragma unroll 1
            for (uint32_t n = 0; n < (1u << 16) && __any_sync(0xffffffffu, gc < gend); n++) {
                asm volatile("ld.relaxed.gpu.global.u32 %0, [%1];" : "=r"(v) : "l"(chunk_flag(sp, lane == 1, part, min(gc, 32 - (lane & 1)))) : "memory");
                if (gc < gend && v >= NCTA) {
                    asm volatile("fence.acquire.gpu;" ::: "memory");
                    mbar_arrive(bars + (lane == 0 ? B_RDY : B_GATE) + 8 * gc);
                    gc++;
                }
            }
            if (lane == 0) publish_tiles(sp, bars, cta, 1);
        } else if (role == 0) {
            const int b = (cta >> 1) & 1, dq = cta & 1;
            for (int v = 0; v < V0; v++) {
                mbar_wait(bars + B_EMPTY + 8 * (v % NST), ((v / NST) & 1) ^ 1);
                if (lane == 0) {
                    mbar_arrive(bars + B_FULL + 8 * (v % NST));
                    mbar_arrive(bars + B_FULL + 8 * (v % NST));
                }
            }
            mbar_wait(bars + B_TSEL, 0);
            const uint32_t gr = ts[64], grp = gr >> 6, idx = (gr >> 2) & 15, pmask = ts[66];
            const uint32_t n0 = idx * 4 + 2 * dq + ((lane & 1) ^ 1), r0 = lane < 3 ? idx * 4 + b : R_W + n0 / 3;
            const uint32_t base = (r0 << 16) + 4096 + ((lane < 3 ? lane : n0 % 3) << 14), step = (lane < 3 ? 64 : 22) << 16;
            uint32_t sels = 0;
            for (int i = 0; i < 12; i++) sels |= run_sel(r0 + i * (step >> 16), grp, pmask) << i;
            int ld = 0;
            const uint32_t bytes = lane == 2 ? XB - 16384 : 8192;
#pragma unroll 1
            for (int h = 0; h < 64; h++) {
                const int s = step_k(h), st = (h + V0) % NST;
                const bool newx = h < HEND ? !(h & 1) : h < HEND + 4;
                const uint32_t fb = bars + B_FULL + 8 * st;
                const uint32_t k = lane < 3 ? (s >> 1) % RX : (h + RW - 64 % RW) % RW, half = lane < 3 ? s & 1 : 0;
                const uint8_t* gsrc = sp + (base + k * step + (half << 17) + ((((sels >> k) ^ half) & 1) << 13));
                const uint32_t dst = sbase + (lane < 3 ? OFF_X + (s & 3) * XB + lane * 8192 : st * 8192 + (lane == 3 ? OFF_W0 : OFF_W1));
                auto landed = [&]() {
                    if (ld < h && mbar_test(bars + B_FULL + 8 * ((ld + V0) % NST), ((ld + V0) / NST) & 1)) {
                        if (!(ld & 1) && lane < 2) red_relaxed(chunk_flag(sp, 1, lane, ld >> 1));
                        ld++;
                    }
                };
                if ((h & 1) || h == 0) {
#pragma unroll 1
                    for (uint32_t n = 0; n < (1u << 19) && !mbar_test(bars + B_RDY + 8 * ((h + 1) >> 1), 0); n++) landed();
                    asm volatile("fence.proxy.async.global;" ::: "memory");
                }
#pragma unroll 1
                for (uint32_t n = 0; n < (1u << 19) && !mbar_test(bars + B_EMPTY + 8 * st, (((h + V0) / NST) & 1) ^ 1); n++) landed();
#pragma unroll 1
                for (uint32_t n = 0; n < (1u << 19) && ld <= h - NST; n++) landed();
                if (lane == 0) mbar_expect_tx(fb, newx ? 16384 + XB : 16384);
                __syncwarp();
                if (lane < 3 ? newx : lane < 5) bulk_g2s(dst, gsrc, bytes, fb);
            }
#pragma unroll 1
            for (; ld < 63; ld++) {
                mbar_wait(bars + B_FULL + 8 * ((ld + V0) % NST), ((ld + V0) / NST) & 1);
                if (!(ld & 1) && lane < 2) red_relaxed(chunk_flag(sp, 1, lane, ld >> 1));
            }
            tail_poll(sp, gr, 0);
            mbar_wait(bars + B_T2, 0);
            tail_loads(sbase, sp, gr, pmask, 0, 5, lane);
            tail_poll(sp, gr, 1);
            tail_loads(sbase, sp, gr, pmask, 5, 8, lane);
            mbar_wait(bars + B_YS + 16, 0);
            tail_loads(sbase, sp, gr, pmask, 8, 10, lane);
            mbar_wait(bars + B_T2 + 8, 0);
            if (lane == 0) {
                mbar_expect_tx(bars + B_C1, 2560);
                corr_load(sbase, gr, 2, bars + B_C1);
                corr_load(sbase, gr, 3, bars + B_C1);
            }
            tail_poll(sp, gr, 2);
            tail_loads(sbase, sp, gr, pmask, 10, 15, lane);
            tail_poll(sp, gr, 3);
            tail_loads(sbase, sp, gr, pmask, 15, 20, lane);
            mbar_wait(bars + B_GATE + 8 * 31, 0);
            unsigned exits = 0;
            if (lane == 0) exits = atomicAdd(&g_exit, 1);
            if (__shfl_sync(0xffffffffu, exits, 0) == NCTA - 1) {
                for (int i = 0; i < 4; i++) *chunk_flag(sp, i >> 1, i & 1, lane) = 0;
                if (lane < 2) *chunk_flag(sp, 0, lane, 32) = 0;
                g_tsel[lane] = 0;
                if (lane < 16) *y_flag(sp, lane >> 3, lane & 7) = 0;
                if (lane == 0) { g_exit = 0; g_epoch = ts[76]; }
            }
        } else if (role == 1) {
            auto raw_load = [&](int r, int h, uint32_t gr, uint32_t dst, uint32_t bar) {
                if (r >= 0) {
                    const int u = r * NCTA + cta, i = u % XPC, b = i >= kNT;
                    tma3d(dst, &tmx, u / XPC * 64, (i - b * kNT) * kMO, b, bar);
                } else if (h >= 0) {
                    const int c = 32 * step_k(h) + ((gr >> 1) & 30);
                    tma3d_ef(dst, c < 512 ? &tmw0 : &tmw1, step_m(h) * 256 + (gr & 3) * 64, 0, c & 511, bar);
                }
            };
            uint32_t gr;
            {
                const int v = lane >> 1, r = v < V0 ? x_round(v, lane & 1) : -1, h = v < V0 ? w_step(v, lane & 1) : -1;
                const uint32_t dst = pre_slot(sbase, v, lane & 1), bar = bars + B_PRE + 8 * lane;
                if (r >= 0 || h >= 0) mbar_expect_tx(bar, r >= 0 ? 8192 : 4096);
                if (v < PRE1) raw_load(r, -1, 0, dst, bar);
                mbar_wait(bars + B_TSEL, 0);
                gr = ts[64];
                raw_load(-1, h, gr, dst, bar);
                if (v >= PRE1) raw_load(r, -1, 0, dst, bar);
                __syncwarp();
            }
            mbar_wait(bars + B_PUB, 0);
#pragma unroll 1
            for (int v = V0; v < V0 + 64; v++) {
                mbar_wait(bars + B_EMPTY + 8 * (v % NST), ((v / NST) & 1) ^ 1);
                __syncwarp();
                const int r = lane < 2 ? x_round(v, lane) : -1, h = lane < 2 ? w_step(v, lane) : -1;
                const uint32_t fb = bars + B_FULL + 8 * (v % NST);
                const uint32_t bytes = __reduce_add_sync(0xffffffffu, r >= 0 ? 8192 : h >= 0 ? 4096 : 0);
                if (lane == 0) mbar_expect_tx(fb, bytes);
                __syncwarp();
                raw_load(r, h, gr, raw_slot(sbase, v, lane), fb);
                if (v >= 20 && v < 40) {
                    const int t = (v - 20) / 5, i = (v - 20) % 5 * 32 + lane, db = 4 * (t >> 1) + 2 * (cta & 1) + (t & 1);
                    ts[(OFF_YT - OFF_TS) / 4 + t * kNT + i] = y_unit(db, i, (cta >> 1) & 1, ts[66]);
                }
                if (v == 66 && lane == 0) {
#pragma unroll 1
                    for (uint32_t n = 0; n < (1u << 15); n++) {
                        unsigned c0, c1;
                        asm volatile("ld.relaxed.gpu.global.u32 %0, [%1];" : "=r"(c0) : "l"(&g_cready[(gr >> 6) * 64]) : "memory");
                        asm volatile("ld.relaxed.gpu.global.u32 %0, [%1];" : "=r"(c1) : "l"(&g_cready[(gr >> 6) * 64 + 32]) : "memory");
                        if (c0 == ts[76] && c1 == ts[76]) break;
                        __nanosleep(500);
                    }
                    asm volatile("fence.acquire.gpu;" ::: "memory");
                    asm volatile("fence.proxy.async.global;" ::: "memory");
                    mbar_expect_tx(bars + B_FTAB, 8192 + 2560);
                    bulk_g2s(sbase + OFF_F, g_tab.inv, 8192, bars + B_FTAB);
                    for (int t = 0; t < 2; t++) {
                        corr_load(sbase, gr, t, bars + B_FTAB);
                        asm volatile("cp.async.bulk.prefetch.L2.global [%0], 1280;" ::"l"(corr_src(gr, 2 + t)) : "memory");
                    }
                }
            }
            channel_scales(sbase, smem_raw, sp, lane);
        } else {
            uint32_t epoch;
            if (lane == 0) {
                bar_setup<B_SIG, B_END>(bars);
                mbar_arrive(bars + B_TSEL);
            }
            asm volatile("ld.relaxed.gpu.global.u32 %0, [%1];" : "=r"(epoch) : "l"(&g_epoch) : "memory");
            mbar_wait(bars + B_TSEL, 0);
            const uint32_t gr = ts[64];
#pragma unroll
            for (int i = lane; i < 256; i += 32) {
                const int d = 64 * tail_block(gr, i >> 6) + (i & 33) + 8 * ((i >> 1) & 3) + 2 * ((i >> 3) & 3);
                ts[(OFF_GB - OFF_TS) / 4 + 2 * i] = (uint32_t)__bfloat16_as_ushort(gamma[d]) << 16;
                ts[(OFF_GB - OFF_TS) / 4 + 2 * i + 1] = (uint32_t)__bfloat16_as_ushort(beta[d]) << 16;
            }
            if (lane == 0) ts[76] = epoch + 1;
            if (cta < 32) stg128(part_sums(sp, cta >> 4, (cta >> 1) & 7, epoch) + (cta & 1) * 64 + 2 * lane, 0, 0, 0, 0);
            __syncwarp();
            if (lane) return;
#pragma unroll 1
            for (int gc = 0; gc < 33;) {
                mbar_wait(bars + B_SIG + 8 * gc, 0);
                if (gc < MERGE) mbar_wait(bars + B_SIG + 8 * MERGE, 0);
                int ge = gc + 1;
                while (ge < 33 && mbar_test(bars + B_SIG + 8 * ge, 0)) ge++;
                asm volatile("fence.acq_rel.gpu;" ::: "memory");
                for (; gc < ge; gc++) {
                    red_relaxed(chunk_flag(sp, 0, 0, gc));
                    red_relaxed(chunk_flag(sp, 0, 1, gc));
                    if (gc == 0) mbar_arrive(bars + B_PUB);
                }
            }
            publish_tiles(sp, bars, cta, 0);
        }
    } else {
        asm volatile("setmaxnreg.inc.sync.aligned.u32 232;");
        uint4 fw[2];
#pragma unroll
        for (int j = 0; j < 2; j++) fw[j] = __ldg(reinterpret_cast<const uint4*>(g_tab.fwd) + tid + 256 * j);
        if (wg == 1) {
            uint4 sm[8];
#pragma unroll
            for (int j = 0; j < 4; j++) {
                const int r = 2 * j + ((tid >> 6) & 1);
                sm[j] = __ldg(reinterpret_cast<const uint4*>(x) + ((r >> 2) * kRows + 1000 + 2000 * (r & 3)) * 128 + (((j + r) & 1) << 6) + (tid & 63));
                sm[4 + j] = __ldg(reinterpret_cast<const uint4*>(wt) + (4 * r * 512 + 67 * r + 7) * 64 + (tid & 63));
            }
#pragma unroll
            for (int k = 0; k < 2; k++) {
                uint32_t mx = 0;
#pragma unroll
                for (int j = 4 * k; j < 4 * k + 4; j++)
                    mx = __vmaxu2(__vmaxu2(mx, __vmaxu2(sm[j].x & 0x7FFF7FFFu, sm[j].y & 0x7FFF7FFFu)), __vmaxu2(sm[j].z & 0x7FFF7FFFu, sm[j].w & 0x7FFF7FFFu));
                mx = __reduce_max_sync(0xffffffffu, max(mx & 0xFFFFu, mx >> 16));
                if (lane == 0) atomicMax(const_cast<uint32_t*>(ts) + 72 + k, mx);
            }
        }
        if ((cta & 3) == 0) {
            if (probing) {
                const int w = tid >> 5;
                unsigned best = 0xffffu;
#pragma unroll 1
                for (int r = 0; r < 6; r++) {
                    unsigned t0, t1;
                    asm volatile("{\n.reg .pred p;\nsetp.eq.u32 p, %1, 0xffffffff;\nmov.u32 %0, 0;\n@!p mov.u32 %0, %%clock;\n}"
                                 : "=r"(t0) : "r"(pv) : "memory");
                    asm volatile("atom.relaxed.gpu.global.exch.b32 %0, [%1], %2;" : "=r"(pv) : "l"(pw), "r"(r) : "memory");
                    asm volatile("{\n.reg .pred p;\nsetp.eq.u32 p, %1, 0xffffffff;\nmov.u32 %0, 0;\n@!p mov.u32 %0, %%clock;\n}"
                                 : "=r"(t1) : "r"(pv) : "memory");
                    ts[68 + w] = best = min(best, t1 - t0);
                    const unsigned other = ts[68 + (w ^ 1)];
                    if (min(best, other) < PROBE_NEAR && max(best, other) > PROBE_NEAR) break;
                }
            }
            if (wg == 0) {
                named_bar(2, 128);
                if (tid == 0) {
                    const uint32_t part = ts[71] < ts[70];
                    const uint32_t v = 16 | (part << 3) | ((ts[69] < ts[68]) ^ part);
                    asm volatile("st.relaxed.gpu.global.u32 [%0], %1;" ::"l"(&g_tsel[cta >> 2]), "r"(v) : "memory");
                }
            }
        }
        uint32_t plan = tid < 2 * (V0 + 65) ? plan_word(tid >> 1, tid & 1, cta) : 0;
        {
            named_bar(1, 256);
            const uint32_t ex = min(max(251 - (int)(ts[72] >> 7), 8), 187), ew = min(max(251 - (int)(ts[73] >> 7), 8), 187);
            if (tid == 0) { ts[74] = ex << 23; ts[75] = ew << 23; }
            const uint32_t sx = ex * 0x800080u, sw = ew * 0x800080u;
#pragma unroll
            for (int j = 0; j < 2; j++) {
                const int i = tid + 256 * j, row = i >> 3, c = (i ^ row) & 7;
                sts128(sbase + OFF_F + 16 * i, mul_bf16x2(fw[j].x, sx), mul_bf16x2(fw[j].y, sx), mul_bf16x2(fw[j].z, sx), mul_bf16x2(fw[j].w, sx));
                if (c < 2) sts128(sbase + OFF_TMP + row * 32 + c * 16, mul_bf16x2(fw[j].x, sw), mul_bf16x2(fw[j].y, sw), mul_bf16x2(fw[j].z, sw), mul_bf16x2(fw[j].w, sw));
            }
            named_bar(1, 256);
        }
        const int t = tid & 127;
        Xf f;
        f.sbase = sbase; f.lane = lane; f.xsw = cta & 4; f.dw = desc_lo(sbase + (wg ? OFF_W1 : OFF_W0));
        {
            const int w = t >> 5;
            const uint32_t nw = (8 * (w & 1) + (lane >> 2)) * 4 + (cta & 3), rw = R_W + nw / 3;
            f.pw = sp + (rw << 16) + 4096 + ((nw % 3) << 14) + (w >> 1) * 128;
            f.cw = ((lane & 7) ^ (w >> 1)) << 4;
            for (int i = 0; i < RW; i++) f.cw |= run_sel(rw + i * 22, 0, 0) << (8 + i);
            mbar_wait(bars + B_TSEL, 0);
            const uint32_t gr = ts[64], pmask = ts[66];
            const uint32_t rx = ts[8 * w + (lane >> 2)];
            f.px = sp + ((rx & 15) << 18) + 4096;
            f.cx = ((lane & 7) << 4) | ((((pmask >> ((rx >> 3) & 1)) ^ -(((rx >> 1) ^ (rx >> 4)) & 1)) & 0x55) << 8);
#pragma unroll
            for (int i = 0; i < RW; i++) f.cw ^= (((pmask >> ((rw + i * 22) >> 5)) ^ (gr >> 6)) & 1) << (8 + i);
            if (plan & 4) plan |= ((gr & 12) << 8) | ((gr & 48) << 4) | ((gr & 48) << 1);
            if (tid < 2 * (V0 + 65)) ts[(OFF_PLAN - OFF_TS) / 4 + tid] = plan;
            const int row = tid >> 2, ch = tid & 3, s = ts[32 + (gr >> 6) * 16 + ((row >> 1) & 8) + (row & 7)], p = (row >> 3) & 1;
            const int frow = 16 * (s >> 3) + 8 * p + (s & 7);
            uint32_t v[4] = {0, 0, 0, 0};
            if ((ch >> 1) == (row >> 5))
                asm volatile("ld.shared.v4.b32 {%0,%1,%2,%3}, [%4];" : "=r"(v[0]), "=r"(v[1]), "=r"(v[2]), "=r"(v[3])
                             : "r"(sbase + OFF_TMP + frow * 32 + (ch & 1) * 16) : "memory");
            sts128(sbase + OFF_G + row * 64 + ((ch ^ ((row >> 1) & 3)) << 4), v[0], v[1], v[2], v[3]);
            fence_proxy_async_smem();
            named_bar(1, 256);
        }
        {
            float at[32];
#pragma unroll 1
            for (uint32_t v = 0; v < V0; v++) {
                const uint32_t e = plan_load(f, v, wg), raw = pre_slot(sbase, v, wg);
                mbar_wait(bars + B_FULL + 8 * (v % NST), (v / NST) & 1);
                if (e & 6) mbar_wait(bars + B_PRE + 16 * v + 8 * wg, 0);
                if (v == PAUSE) mbar_wait(bars + B_PUB, 0);
                wg_fence();
                if ((e & 6) == 2) {
                    unit_mma<false>(at, f, raw);
                    wg_wait<0>();
                    unit_store<false>(at, f, e);
                } else if (e & 4) {
                    unit_mma<true>(at, f, raw);
                    wg_wait<0>();
                    unit_store<true>(at, f, e);
                }
                if (lane == 0) mbar_arrive(bars + B_EMPTY + 8 * (v % NST));
                unit_done(f, e, v);
            }
        }
        const int slot = cta >> 2;
        f.e = plan_load(f, V0, wg);
        uint32_t a0[40], a1[40], b0[40], b1[40];
#pragma unroll
        for (int i = 0; i < 40; i++) a0[i] = a1[i] = b0[i] = b1[i] = 0;
        if (slot == 0) gemm_main<true>(a0, a1, b0, b1, f, wg);
        else gemm_main<false>(a0, a1, b0, b1, f, wg);
        const uint32_t gr = __shfl_sync(0xffffffffu, ts[64], 0);
        const float sx = __uint_as_float(ts[74]), sw = __uint_as_float(ts[75]);
        uint32_t wr[2][4][4];
        w_fetch(wr[0], f, V0 + HEND);
#pragma unroll 1
        for (int m = 0; m < 2; m++) {
            if (slot == 0) gemm_last<true>(a0, a1, wr, f, wg, m);
            else gemm_last<false>(a0, a1, wr, f, wg, m);
            reg_fence(a0);
            reg_fence(a1);
            const int wsw = gr & 4;
            mbar_wait(bars + B_GATE + 8 * y_gate(2 * m + wg), 0);
            if (m) mbar_wait(bars + B_FTAB, 0);
            const uint32_t ytab = sbase + OFF_YT + (m * 2 + wg) * (kNT * 4);
            store_tile(a0, a1, b0, b1, wr[0], f, m == 0, sbase + OFF_STG + wg * 16384, t, wg, sp, slot, ytab, wsw);
            __syncwarp();
            if (lane == 0) mbar_arrive(bars + B_YS + 8 * (2 * m + wg));
        }
        tail_phase(sbase, smem_raw, sp, wg, gr, sx, sw, x, wt, gamma, beta, out);
    }
}

constexpr int C_STAGE = 32768 + 2 * XB, C_SMEM = 3 * C_STAGE + 64;
__global__ void __launch_bounds__(256, 1) corr_kernel(const __grid_constant__ CUtensorMap tmx, const __grid_constant__ CUtensorMap tmw) {
    extern __shared__ __align__(1024) uint8_t smem_raw[];
    const uint32_t sbase = smem_u32(smem_raw) & ~1023u, bars = sbase + 3 * C_STAGE;
    const int tid = threadIdx.x, wg = __shfl_sync(0xffffffffu, tid >> 7, 0), b = blockIdx.x >> 1, dh = blockIdx.x & 1;
    auto load = [&](int k) {
        const uint32_t st = sbase + (k % 3) * C_STAGE, bar = bars + 8 * (k % 3);
        mbar_expect_tx(bar, C_STAGE);
        for (int i = 0; i < 4; i++) tma2d(st + i * 8192, &tmw, 256 * dh + 64 * i, 64 * k, bar);
        tma4d(st + 32768, &tmx, 64 * k, 64 - kMO, 1, b, bar);
        tma4d(st + 32768 + XB, &tmx, 64 * k, 0, 0, b, bar);
    };
    uint32_t epoch = 0;
    if (tid == 0) {
        for (int i = 0; i < 3; i++) mbar_init(bars + 8 * i, 1);
        fence_mbar_init();
        fence_proxy_async_smem();
        for (int k = 0; k < 3; k++) load(k);
        asm volatile("ld.relaxed.gpu.global.u32 %0, [%1];" : "=r"(epoch) : "l"(&g_epoch) : "memory");
    }
    __syncthreads();
    float a[2][80];
#pragma unroll
    for (int i = 0; i < 80; i++) a[0][i] = a[1][i] = 0.f;
#pragma unroll 1
    for (int k = 0; k < 8; k++) {
        const uint32_t dA = desc_lo(sbase + (k % 3) * C_STAGE + wg * 16384), dB = desc_lo(sbase + (k % 3) * C_STAGE + 32768);
        mbar_wait(bars + 8 * (k % 3), (k / 3) & 1);
        wg_fence();
#pragma unroll
        for (int i = 0; i < 8; i++) {
            wgmma_n160_f<1>(a[i & 1], dA + (i & 1) * 512 + (i >> 1) * 128, dB + (i >> 1) * 2);
            wgmma_n160_f<-1>(a[i & 1], dA + (i & 1) * 512 + (i >> 1) * 128, dB + XB / 16 + (i >> 1) * 2);
        }
        wg_commit();
        wg_wait<0>();
        __syncthreads();
        if (tid == 0 && k + 3 < 8) load(k + 3);
    }
    reg_fence(a[0]);
    reg_fence(a[1]);
    const int w = (tid >> 5) & 3, g = (tid & 31) >> 2, q = tid & 3;
    float* stage = reinterpret_cast<float*>(smem_raw);
#pragma unroll
    for (int i = 0; i < 160; i++) {
        const int m = i / 80, j = i % 80, d = 16 * w + 8 * ((j >> 1) & 1) + g;
        stage[((2 * wg + m) * kNT + 8 * (j >> 2) + 2 * q + (j & 1)) * 64 + (d & 33) + 8 * ((d >> 1) & 3) + 2 * ((d >> 3) & 3)] = a[m][j];
    }
    __syncthreads();
    for (int i = tid; i < 4 * kNT * 16; i += 256)
        reinterpret_cast<float4*>(g_corr)[(b * 8 + 4 * dh) * kNT * 16 + i] = reinterpret_cast<const float4*>(stage)[i];
    __syncthreads();
    if (tid == 0) {
        asm volatile("fence.acq_rel.gpu;" ::: "memory");
        asm volatile("st.relaxed.gpu.global.u32 [%0], %1;" ::"l"(&g_cready[blockIdx.x * 32]), "r"(epoch + 1) : "memory");
    }
}

__global__ void __launch_bounds__(256) plain_conv(const __nv_bfloat16* __restrict__ x, const __nv_bfloat16* __restrict__ w) {
    __shared__ float xs[64][17], ws[16][65];
    float* h = g_direct;
    const int b = blockIdx.z, l0 = blockIdx.x * 64, d0 = blockIdx.y * 64, tx = threadIdx.x & 15, ty = threadIdx.x >> 4;
    float acc[4][4] = {};
    for (int k0 = 0; k0 < 31 * 512; k0 += 16) {
        for (int i = threadIdx.x; i < 1024; i += 256) {
            const int l = min(l0 + (i >> 4), kL - 1);
            xs[i >> 4][i & 15] = __bfloat162float(x[((size_t)b * kRows + l) * 1024 + k0 + (i & 15)]);
            ws[i >> 6][i & 63] = __bfloat162float(w[(size_t)(k0 + (i >> 6)) * 512 + d0 + (i & 63)]);
        }
        __syncthreads();
        for (int k = 0; k < 16; k++)
            for (int i = 0; i < 4; i++)
                for (int j = 0; j < 4; j++) acc[i][j] = fmaf(xs[ty * 4 + i][k], ws[k][tx * 4 + j], acc[i][j]);
        __syncthreads();
    }
    for (int i = 0; i < 4; i++)
        for (int j = 0; j < 4; j++)
            if (l0 + ty * 4 + i < kL) h[((size_t)b * kL + l0 + ty * 4 + i) * 512 + d0 + tx * 4 + j] = acc[i][j];
}
__global__ void __launch_bounds__(256) plain_norm(const __nv_bfloat16* __restrict__ gamma, const __nv_bfloat16* __restrict__ beta,
                                                  __nv_bfloat16* __restrict__ out) {
    __shared__ float s1[8][32], s2[8][32];
    const int c = threadIdx.x & 31, r = threadIdx.x >> 5, d = blockIdx.x * 32 + c;
    const float* h = g_direct + (size_t)blockIdx.y * kL * 512 + d;
    float a = 0.f, q = 0.f;
    for (int l = r; l < kL; l += 8) { const float v = h[(size_t)l * 512]; a += v; q = fmaf(v, v, q); }
    s1[r][c] = a; s2[r][c] = q;
    __syncthreads();
    a = q = 0.f;
    for (int i = 0; i < 8; i++) { a += s1[i][c]; q += s2[i][c]; }
    const float mean = a * (1.0f / kL), sc = __bfloat162float(gamma[d]) / sqrtf(fmaxf(q * (1.0f / kL) - mean * mean, 0.f) + 1e-5f);
    const float sh = __bfloat162float(beta[d]) - mean * sc;
    for (int l = r; l < kL; l += 8)
        out[((size_t)blockIdx.y * kL + l) * 512 + d] = __float2bfloat16(gelu_half(0.5f * fmaf(h[(size_t)l * 512], sc, sh)));
}

typedef CUresult (*EncodeTiledFn)(CUtensorMap*, CUtensorMapDataType, cuuint32_t, void*, const cuuint64_t*, const cuuint64_t*,
                                  const cuuint32_t*, const cuuint32_t*, CUtensorMapInterleave, CUtensorMapSwizzle,
                                  CUtensorMapL2promotion, CUtensorMapFloatOOBfill);

void encode(EncodeTiledFn fn, CUtensorMap* tm, const void* ptr, int rank, const cuuint64_t* dims, const cuuint64_t* strides,
            const cuuint32_t* box, CUtensorMapL2promotion promo, CUtensorMapSwizzle swz = CU_TENSOR_MAP_SWIZZLE_128B) {
    const cuuint32_t es[5] = {1, 1, 1, 1, 1};
    fn(tm, CU_TENSOR_MAP_DATA_TYPE_BFLOAT16, rank, const_cast<void*>(ptr), dims, strides, box, es, CU_TENSOR_MAP_INTERLEAVE_NONE,
       swz, promo, CU_TENSOR_MAP_FLOAT_OOB_FILL_NONE);
}

}

extern "C" void kernel_launch(void* const* d_in, const int* in_sizes, int n_in, void* d_out, int out_size) {
    const __nv_bfloat16* x = (const __nv_bfloat16*)d_in[0];
    const __nv_bfloat16* w = (const __nv_bfloat16*)d_in[1];
    const __nv_bfloat16* gamma = (const __nv_bfloat16*)d_in[2];
    const __nv_bfloat16* beta = (const __nv_bfloat16*)d_in[3];
    static EncodeTiledFn enc = nullptr;
    static int resident = 0;
    if (!enc) {
        void* fn = nullptr;
        cudaDriverEntryPointQueryResult qr;
        cudaGetDriverEntryPoint("cuTensorMapEncodeTiled", &fn, cudaEnableDefault, &qr);
        enc = (EncodeTiledFn)fn;
        cudaFuncSetAttribute(main_kernel, cudaFuncAttributeMaxDynamicSharedMemorySize, MAIN_SMEM);
        cudaFuncSetAttribute(corr_kernel, cudaFuncAttributeMaxDynamicSharedMemorySize, C_SMEM);
        int dev = 0, per_sm = 0;
        cudaGetDevice(&dev);
        cudaDeviceGetAttribute(&resident, cudaDevAttrMultiProcessorCount, dev);
        cudaOccupancyMaxActiveBlocksPerMultiprocessor(&per_sm, main_kernel, 384, MAIN_SMEM);
        resident *= per_sm;
    }
    if (resident < NCTA + 4) {
        plain_conv<<<dim3((kL + 63) / 64, 8, 2), 256>>>(x, w);
        plain_norm<<<dim3(16, 2), 256>>>(gamma, beta, (__nv_bfloat16*)d_out);
        return;
    }
    CUtensorMap tmx, tmw0, tmw1, tmcx, tmcw;
    {
        const cuuint64_t dims[3] = {1024, kRows, 2}, strides[2] = {2048, (cuuint64_t)kRows * 2048};
        const cuuint32_t box[3] = {64, 64, 1};
        encode(enc, &tmx, x, 3, dims, strides, box, CU_TENSOR_MAP_L2_PROMOTION_L2_128B);
    }
    {
        const cuuint64_t dims0[3] = {512, 16, 512}, dims1[3] = {512, 15, 512}, strides[2] = {2 * 512 * 512 * 2, 1024};
        const cuuint32_t box[3] = {64, 16, 2};
        encode(enc, &tmw0, w, 3, dims0, strides, box, CU_TENSOR_MAP_L2_PROMOTION_L2_128B);
        encode(enc, &tmw1, w + 512 * 512, 3, dims1, strides, box, CU_TENSOR_MAP_L2_PROMOTION_L2_128B);
    }
    {
        const cuuint64_t dims[4] = {512, kMO, kNT, 2}, strides[3] = {2048, kMO * 2048, (cuuint64_t)kRows * 2048};
        const cuuint32_t box[4] = {64, 1, kNT, 1};
        encode(enc, &tmcx, x, 4, dims, strides, box, CU_TENSOR_MAP_L2_PROMOTION_L2_128B);
        const cuuint64_t dimw[2] = {512, 512}, stridew[1] = {1024};
        const cuuint32_t boxw[2] = {64, 64};
        encode(enc, &tmcw, w + 30 * 512 * 512, 2, dimw, stridew, boxw, CU_TENSOR_MAP_L2_PROMOTION_L2_128B);
    }
    main_kernel<<<NCTA, 384, MAIN_SMEM>>>(tmx, tmw0, tmw1, x, w, gamma, beta, (__nv_bfloat16*)d_out);
    cudaLaunchConfig_t cfg = {};
    cudaLaunchAttribute at[1];
    cfg.gridDim = 4;
    cfg.blockDim = 256;
    cfg.dynamicSmemBytes = C_SMEM;
    at[0].id = cudaLaunchAttributeProgrammaticStreamSerialization;
    at[0].val.programmaticStreamSerializationAllowed = 1;
    cfg.attrs = at;
    cfg.numAttrs = 1;
    cudaLaunchKernelEx(&cfg, corr_kernel, tmcx, tmcw);
}
```

```cpp
#include <cuda_runtime.h>
#include <cuda_bf16.h>
#include <cuda.h>
#include <stdint.h>

namespace {

constexpr int kL    = 7985;
constexpr int kRows = 8000;
constexpr int kMO   = 50;
constexpr int kNT   = 160;

constexpr int V0 = 7;
constexpr int NPRE = 6;
constexpr int RX = 4;
constexpr int PAUSE = 5;
constexpr int YSLEEP = 100;
constexpr int PRE1 = 4;
constexpr int TSLEEP = 200;
constexpr int MERGE = 1;
constexpr int RW = 10;

static_assert(V0 >= 7 && V0 <= 9 && RX >= 2 && RX <= 4 && RW >= V0 - 1 && RW <= 12, "rings must fit and be as deep as the look-ahead");
constexpr uint32_t HOME_MASK = 0xB;
constexpr uint32_t R_W = 64 * RX, NPAGES = (R_W + 22 * RW + 31) / 32;

__device__ __align__(1024) uint8_t g_sp[(size_t)(NPAGES + 1) * (2u << 20)];
__device__ __align__(128) unsigned g_tsel[32];
__device__ __forceinline__ uint32_t run_sel(uint32_t r, uint32_t group, uint32_t pmask) {
    return ((pmask >> (r >> 5)) ^ __popc(r & HOME_MASK) ^ group) & 1;
}
__device__ __forceinline__ uint32_t run_off(uint32_t r, uint32_t run, uint32_t group, uint32_t pmask) {
    return (r << 16) + 4096 + (run_sel(r, group, pmask) << 13) + (run << 14);
}
__device__ __forceinline__ unsigned* chunk_flag(uint8_t* sp, int done, int part, int chunk) {
    return reinterpret_cast<unsigned*>(sp + (4 + 3 * (chunk >> 5)) * 65536 + (done ? (part ? 15 : 13) : (part ? 0 : 14)) * 4096 + (chunk & 31) * 128);
}
__device__ __forceinline__ unsigned long long* part_sums(uint8_t* sp, int b, int db, uint32_t epoch) {
    return reinterpret_cast<unsigned long long*>(sp + (8 + 2 * db + ((__popc((8 + 2 * db) & HOME_MASK) ^ b) & 1)) * 65536 + 13 * 4096 + (epoch & 1) * 1024);
}
__device__ __forceinline__ unsigned* y_flag(uint8_t* sp, int b, int db) { return reinterpret_cast<unsigned*>(part_sums(sp, b, db, 0) + 512); }
__device__ __align__(256) float g_corr[16 * kNT * 64];
__device__ unsigned g_cready[4 * 32];
__device__ float g_direct[512 * 250 * 64];
__device__ unsigned long long g_dpart[2 * 512 * 64];
__device__ unsigned g_exit, g_epoch;

__device__ __forceinline__ uint32_t smem_u32(const void* p) { return (uint32_t)__cvta_generic_to_shared(p); }

__device__ __forceinline__ void mbar_init(uint32_t bar, uint32_t count) {
    asm volatile("mbarrier.init.shared::cta.b64 [%0], %1;" ::"r"(bar), "r"(count) : "memory");
}
__device__ __forceinline__ void mbar_expect_tx(uint32_t bar, uint32_t bytes) {
    asm volatile("mbarrier.arrive.expect_tx.shared::cta.b64 _, [%0], %1;" ::"r"(bar), "r"(bytes) : "memory");
}
__device__ __forceinline__ void mbar_arrive(uint32_t bar) {
    asm volatile("mbarrier.arrive.shared::cta.b64 _, [%0];" ::"r"(bar) : "memory");
}
__device__ __forceinline__ bool mbar_try(uint32_t bar, uint32_t parity) {
    uint32_t ok;
    asm volatile(
        "{\n.reg .pred p;\n"
        "mbarrier.try_wait.parity.shared::cta.b64 p, [%1], %2;\n"
        "selp.u32 %0, 1, 0, p;\n}\n"
        : "=r"(ok) : "r"(bar), "r"(parity) : "memory");
    return ok;
}
__device__ __forceinline__ bool mbar_test(uint32_t bar, uint32_t parity) {
    uint32_t ok;
    asm volatile(
        "{\n.reg .pred p;\n"
        "mbarrier.test_wait.parity.shared::cta.b64 p, [%1], %2;\n"
        "selp.u32 %0, 1, 0, p;\n}\n"
        : "=r"(ok) : "r"(bar), "r"(parity) : "memory");
    return ok;
}
__device__ __forceinline__ void mbar_wait(uint32_t bar, uint32_t parity) {
#pragma unroll 1
    for (uint32_t n = 0; n < (1u << 14); n++)
        if (mbar_try(bar, parity)) break;
}
__device__ __forceinline__ void fence_proxy_async_smem() { asm volatile("fence.proxy.async.shared::cta;" ::: "memory"); }
__device__ __forceinline__ void fence_mbar_init() { asm volatile("fence.mbarrier_init.release.cluster;" ::: "memory"); }

__device__ __forceinline__ void bulk_g2s(uint32_t dst, const void* src, uint32_t bytes, uint32_t bar) {
    asm volatile("cp.async.bulk.shared::cluster.global.mbarrier::complete_tx::bytes [%0], [%1], %2, [%3];"
                 ::"r"(dst), "l"(src), "r"(bytes), "r"(bar) : "memory");
}
__device__ __forceinline__ void tma3d_ef(uint32_t dst, const CUtensorMap* tm, int c0, int c1, int c2, uint32_t bar) {
    asm volatile("{\n.reg .b64 pol;\ncreatepolicy.fractional.L2::evict_first.b64 pol, 1.0;\n"
                 "cp.async.bulk.tensor.3d.shared::cluster.global.mbarrier::complete_tx::bytes.L2::cache_hint [%0], [%1, {%3, %4, %5}], [%2], pol;\n}"
                 ::"r"(dst), "l"(tm), "r"(bar), "r"(c0), "r"(c1), "r"(c2) : "memory");
}
__device__ __forceinline__ void tma3d(uint32_t dst, const CUtensorMap* tm, int c0, int c1, int c2, uint32_t bar) {
    asm volatile("cp.async.bulk.tensor.3d.shared::cluster.global.mbarrier::complete_tx::bytes [%0], [%1, {%3, %4, %5}], [%2];"
                 ::"r"(dst), "l"(tm), "r"(bar), "r"(c0), "r"(c1), "r"(c2) : "memory");
}
__device__ __forceinline__ void red_relaxed(unsigned* p) { asm volatile("red.relaxed.gpu.global.add.u32 [%0], 1;" ::"l"(p) : "memory"); }
__device__ __forceinline__ void named_arrive(int id, int n) { asm volatile("bar.arrive %0, %1;" ::"r"(id), "r"(n) : "memory"); }
__device__ __forceinline__ void named_bar(int id, int n) { asm volatile("bar.sync %0, %1;" ::"r"(id), "r"(n) : "memory"); }

__device__ __forceinline__ void wg_fence() { asm volatile("wgmma.fence.sync.aligned;" ::: "memory"); }
__device__ __forceinline__ void wg_commit() { asm volatile("wgmma.commit_group.sync.aligned;" ::: "memory"); }
template <int N> __device__ __forceinline__ void wg_wait() { asm volatile("wgmma.wait_group.sync.aligned %0;" ::"n"(N) : "memory"); }
template <int N> __device__ __forceinline__ void reg_fence(float (&d)[N]) {
#pragma unroll
    for (int i = 0; i < N; i++) asm volatile("" : "+f"(d[i])::"memory");
}

#define F4(a, i) "+f"(a[i]), "+f"(a[i + 1]), "+f"(a[i + 2]), "+f"(a[i + 3])
#define F8(a, i) F4(a, i), F4(a, i + 4)
#define F16(a, i) F8(a, i), F8(a, i + 8)

constexpr uint32_t HI128 = 0x40000040u, HI64 = 0x80000020u;
__device__ __forceinline__ uint32_t desc_lo(uint32_t addr) { return (addr >> 4) | 0x10000u; }

#define R4(a, i) "+r"(a[i]), "+r"(a[i + 1]), "+r"(a[i + 2]), "+r"(a[i + 3])
#define R8(a, i) R4(a, i), R4(a, i + 4)
template <int N> __device__ __forceinline__ void reg_fence(uint32_t (&d)[N]) {
#pragma unroll
    for (int i = 0; i < N; i++) asm volatile("" : "+r"(d[i])::"memory");
}
__device__ __forceinline__ void tma2d(uint32_t dst, const CUtensorMap* tm, int c0, int c1, uint32_t bar) {
    asm volatile("cp.async.bulk.tensor.2d.shared::cluster.global.mbarrier::complete_tx::bytes [%0], [%1, {%3, %4}], [%2];"
                 ::"r"(dst), "l"(tm), "r"(bar), "r"(c0), "r"(c1) : "memory");
}
__device__ __forceinline__ void tma4d(uint32_t dst, const CUtensorMap* tm, int c0, int c1, int c2, int c3, uint32_t bar) {
    asm volatile("cp.async.bulk.tensor.4d.shared::cluster.global.mbarrier::complete_tx::bytes [%0], [%1, {%3, %4, %5, %6}], [%2];"
                 ::"r"(dst), "l"(tm), "r"(bar), "r"(c0), "r"(c1), "r"(c2), "r"(c3) : "memory");
}

template <uint32_t AHI, int ACC>
__device__ __forceinline__ void wgmma_n64_ss(float (&d)[32], uint32_t da, uint32_t db) {
    asm volatile(
        "{\n.reg .pred p;\n.reg .b64 da, db;\nsetp.ne.b32 p, %36, 0;\nmov.b64 da, {%32, %34};\nmov.b64 db, {%33, %35};\n"
        "wgmma.mma_async.sync.aligned.m64n64k16.f32.bf16.bf16 "
        "{%0,%1,%2,%3,%4,%5,%6,%7,%8,%9,%10,%11,%12,%13,%14,%15,%16,%17,%18,%19,%20,%21,%22,%23,%24,%25,%26,%27,%28,%29,%30,%31},"
        "da, db, p, 1, 1, 0, 1;\n}\n"
        : F16(d, 0), F16(d, 16)
        : "r"(da), "r"(db), "n"(AHI), "n"(HI128), "n"(ACC));
}

template <int ACC>
__device__ __forceinline__ void wgmma_n56_ss(float (&d)[28], uint32_t da, uint32_t db) {
    asm volatile(
        "{\n.reg .pred p;\n.reg .b64 da, db;\nsetp.ne.b32 p, %31, 0;\nmov.b64 da, {%28, %30};\nmov.b64 db, {%29, %30};\n"
        "wgmma.mma_async.sync.aligned.m64n56k16.f32.f16.f16 "
        "{%0,%1,%2,%3,%4,%5,%6,%7,%8,%9,%10,%11,%12,%13,%14,%15,%16,%17,%18,%19,%20,%21,%22,%23,%24,%25,%26,%27},"
        "da, db, p, 1, 1, 1, 0;\n}\n"
        : F16(d, 0), F8(d, 16), F4(d, 24)
        : "r"(da), "r"(db), "n"(HI128), "n"(ACC));
}

template <int SA>
__device__ __forceinline__ void wgmma_n160_h(uint32_t (&d)[40], uint32_t da, uint32_t db) {
    asm volatile(
        "{\n.reg .pred p;\n.reg .b64 da, db;\nsetp.eq.b32 p, 0, 0;\nmov.b64 da, {%40, %43};\nmov.b64 db, {%41, %43};\n"
        "wgmma.mma_async.sync.aligned.m64n160k16.f16.f16.f16 "
        "{%0,%1,%2,%3,%4,%5,%6,%7,%8,%9,%10,%11,%12,%13,%14,%15,%16,%17,%18,%19,%20,%21,%22,%23,%24,%25,%26,%27,"
        "%28,%29,%30,%31,%32,%33,%34,%35,%36,%37,%38,%39},"
        "da, db, p, %42, 1, 1, 0;\n}\n"
        : R8(d, 0), R8(d, 8), R8(d, 16), R8(d, 24), R8(d, 32)
        : "r"(da), "r"(db), "n"(SA), "n"(HI128));
}
template <int SA>
__device__ __forceinline__ void wgmma_n160_hr(uint32_t (&d)[40], const uint32_t (&a)[4], uint32_t db) {
    asm volatile(
        "{\n.reg .pred p;\n.reg .b64 db;\nsetp.eq.b32 p, 0, 0;\nmov.b64 db, {%44, %46};\n"
        "wgmma.mma_async.sync.aligned.m64n160k16.f16.f16.f16 "
        "{%0,%1,%2,%3,%4,%5,%6,%7,%8,%9,%10,%11,%12,%13,%14,%15,%16,%17,%18,%19,%20,%21,%22,%23,%24,%25,%26,%27,"
        "%28,%29,%30,%31,%32,%33,%34,%35,%36,%37,%38,%39},"
        "{%40,%41,%42,%43}, db, p, %45, 1, 0;\n}\n"
        : R8(d, 0), R8(d, 8), R8(d, 16), R8(d, 24), R8(d, 32)
        : "r"(a[0]), "r"(a[1]), "r"(a[2]), "r"(a[3]), "r"(db), "n"(SA), "n"(HI128));
}
template <int SA>
__device__ __forceinline__ void wgmma_n160_f(float (&d)[80], uint32_t da, uint32_t db) {
    asm volatile(
        "{\n.reg .pred p;\n.reg .b64 da, db;\nsetp.eq.b32 p, 0, 0;\nmov.b64 da, {%80, %83};\nmov.b64 db, {%81, %83};\n"
        "wgmma.mma_async.sync.aligned.m64n160k16.f32.bf16.bf16 "
        "{%0,%1,%2,%3,%4,%5,%6,%7,%8,%9,%10,%11,%12,%13,%14,%15,%16,%17,%18,%19,%20,%21,%22,%23,%24,%25,%26,%27,"
        "%28,%29,%30,%31,%32,%33,%34,%35,%36,%37,%38,%39,%40,%41,%42,%43,%44,%45,%46,%47,%48,%49,%50,%51,%52,%53,%54,%55,"
        "%56,%57,%58,%59,%60,%61,%62,%63,%64,%65,%66,%67,%68,%69,%70,%71,%72,%73,%74,%75,%76,%77,%78,%79},"
        "da, db, p, %82, 1, 1, 0;\n}\n"
        : F16(d, 0), F16(d, 16), F16(d, 32), F16(d, 48), F16(d, 64)
        : "r"(da), "r"(db), "n"(SA), "n"(HI128));
}

__device__ __forceinline__ uint32_t pack_f16(float lo, float hi) {
    uint32_t r;
    asm("cvt.rn.f16x2.f32 %0, %1, %2;" : "=r"(r) : "f"(hi), "f"(lo));
    return r;
}
__device__ __forceinline__ uint32_t mul_bf16x2(uint32_t a, uint32_t b) {
    uint32_t r;
    asm("mul.rn.bf16x2 %0, %1, %2;" : "=r"(r) : "r"(a), "r"(b));
    return r;
}
__device__ __forceinline__ void sts128(uint32_t p, uint32_t a, uint32_t b, uint32_t c, uint32_t d) {
    asm volatile("st.shared.v4.b32 [%0], {%1,%2,%3,%4};" ::"r"(p), "r"(a), "r"(b), "r"(c), "r"(d) : "memory");
}
__device__ __forceinline__ uint32_t pack_bf16(float lo, float hi) {
    uint32_t r;
    asm("cvt.rn.bf16x2.f32 %0, %1, %2;" : "=r"(r) : "f"(hi), "f"(lo));
    return r;
}
__device__ __forceinline__ void stg128(void* p, uint32_t a, uint32_t b, uint32_t c, uint32_t d) {
    asm volatile("st.global.v4.b32 [%0], {%1,%2,%3,%4};" ::"l"(p), "r"(a), "r"(b), "r"(c), "r"(d) : "memory");
}
__device__ __forceinline__ void stmatrix_x4_t(uint32_t addr, uint32_t a, uint32_t b, uint32_t c, uint32_t d) {
    asm volatile("stmatrix.sync.aligned.m8n8.x4.trans.shared.b16 [%0], {%1,%2,%3,%4};"
                 ::"r"(addr), "r"(a), "r"(b), "r"(c), "r"(d) : "memory");
}

constexpr uint32_t cos64(int k, bool half) {
    constexpr uint16_t q[17] = {0x3F80, 0x3F7F, 0x3F7B, 0x3F75, 0x3F6D, 0x3F62, 0x3F55, 0x3F46, 0x3F35, 0x3F22, 0x3F0E, 0x3EF1, 0x3EC4, 0x3E95, 0x3E48, 0x3DC9, 0x0000};
    constexpr uint16_t h[17] = {0x3C00, 0x3BF6, 0x3BD9, 0x3BA8, 0x3B64, 0x3B0E, 0x3AA7, 0x3A2F, 0x39A8, 0x3913, 0x3872, 0x378B, 0x361F, 0x34A5, 0x323E, 0x2E46, 0x0000};
    k &= 63;
    if (k > 32) k = 64 - k;
    const uint16_t* t = half ? h : q;
    return k <= 16 ? t[k] : (t[32 - k] | 0x8000u);
}
constexpr uint32_t fwd_coef(int s, int p, int t) { return (p && s == 0) ? cos64(32 * t, false) : cos64(s * t - 16 * p, false); }
constexpr uint32_t inv_coef(int l, int phi) {
    const int s = phi >> 1, p = phi & 1;
    if (l >= kMO) return 0;
    const uint32_t c = s == 0 ? cos64(32 * l * p, true) : cos64(s * l + 16 * p, true);
    return (c & 0x7FFF) ? c - ((s == 0 ? 6 : 5) << 10) : 0;
}
struct Tables {
    uint32_t fwd[2048];
    uint32_t inv[2048];
};
constexpr Tables make_tables() {
    Tables t = {};
    for (int i = 0; i < 2048; i++) {
        const int row = i >> 5, tt = 8 * (((i >> 2) & 7) ^ (row & 7)) + 2 * (i & 3), s = 8 * (row >> 4) + (row & 7), p = (row >> 3) & 1;
        t.fwd[i] = fwd_coef(s, p, tt) | (fwd_coef(s, p, tt + 1) << 16);
        t.inv[i] = inv_coef(row, tt) | (inv_coef(row, tt + 1) << 16);
    }
    return t;
}
__device__ __align__(128) const Tables g_tab = make_tables();

constexpr int NCTA = 128;
constexpr int NST = 4;
constexpr int HEND = 56;
constexpr int XB = kNT * 128;
constexpr int OFF_W1 = 0, OFF_X = OFF_W1 + NST * 8192, OFF_W0 = OFF_X + 4 * XB, OFF_RAW = OFF_W0 + NST * 8192;
constexpr int OFF_STG = OFF_RAW + 32768;
constexpr int OFF_U0 = OFF_W0, OFF_U1 = OFF_X, OFF_C1 = OFF_W1, OFF_DIR = OFF_W1 + 8192;
constexpr int OFF_F = OFF_RAW + 65536;
constexpr int OFF_G = OFF_F + 8192;
constexpr int OFF_C0 = OFF_G;
constexpr int OFF_BAR = OFF_G + 4096;
constexpr int B_FULL = 0, B_EMPTY = 8 * NST, B_TSEL = 16 * NST, B_PRE = B_TSEL + 8, B_SIG = B_PRE + 16 * V0, B_YS = B_SIG + 8 * 33,
              B_T2 = B_YS + 8 * 4, B_SUM = B_T2 + 16, B_GATE = B_SUM + 32, B_RDY = B_GATE + 8 * 32, B_PUB = B_RDY + 8 * 33, B_UNIT = B_PUB + 8,
              B_FTAB = B_UNIT + 8 * 20, B_C1 = B_FTAB + 8, B_NRM = B_C1 + 8, B_END = B_NRM + 32;
template <int O0, int O1>
__device__ __forceinline__ void bar_setup(uint32_t bars) {
#pragma unroll
    for (int o = O0; o < O1; o += 8)
        mbar_init(bars + o, o < B_EMPTY ? 2 : o < B_TSEL ? 8 : o == B_TSEL ? 2 : o < B_SIG ? 1 : o < B_YS - 8 ? 8 : o < B_GATE ? 4 : 1);
    fence_mbar_init();
    fence_proxy_async_smem();
}
constexpr int OFF_TS = OFF_BAR + B_END;
constexpr int OFF_PLAN = OFF_TS + 336;
constexpr int OFF_YT = OFF_PLAN + (V0 + 65) * 8;
constexpr int OFF_GB = (OFF_YT + 4 * kNT * 4 + 15) & ~15;
constexpr int MAIN_SMEM = OFF_GB + 2048;
static_assert(MAIN_SMEM <= 232448 && OFF_U0 + 10 * 8192 == OFF_STG + 16384, "shared memory");
constexpr int XPC = 2 * kNT;
constexpr unsigned PROBE_NEAR = 400;

__device__ __forceinline__ uint32_t raw_slot(uint32_t sbase, uint32_t v, int wg) { return sbase + OFF_RAW + ((v & 3) * 2 + wg) * 8192; }

__device__ __forceinline__ uint32_t pre_slot(uint32_t sbase, uint32_t v, int wg) {
    return v < 4 ? raw_slot(sbase, v, wg) : v < 8 ? sbase + OFF_X + (v - 4) * XB + wg * 8192 : sbase + (wg ? OFF_W1 : OFF_W0) + ((V0 + 3) % NST) * 8192;
}
constexpr int OFF_TMP = OFF_W1 + 8192;

template <bool DC, int I>
__device__ __forceinline__ void gemm_mma(uint32_t (&a0)[40], uint32_t (&a1)[40], uint32_t dx0, uint32_t dx1, uint32_t dw) {
    constexpr int ks = I >> 2;
    const uint32_t A0 = dw + ks * 128, A1 = A0 + 256, B0 = dx0 + ks * 2, B1 = dx1 + ks * 2;
    if ((I & 3) == 0) wgmma_n160_h<1>(a0, A0, B0);
    if ((I & 3) == 1) wgmma_n160_h<1>(a1, A1, DC ? B1 : B0);
    if ((I & 3) == 2 && !DC) wgmma_n160_h<1>(a0, A1, B1);
    if ((I & 3) == 3 && !DC) wgmma_n160_h<-1>(a1, A0, B1);
}

template <bool DC, int I0, int I1>
__device__ __forceinline__ void gemm_mmas(uint32_t (&a0)[40], uint32_t (&a1)[40], uint32_t dx0, uint32_t dx1, uint32_t dw) {
    if constexpr (I0 < I1) {
        gemm_mma<DC, I0>(a0, a1, dx0, dx1, dw);
        gemm_mmas<DC, I0 + 1, I1>(a0, a1, dx0, dx1, dw);
    }
}
static_assert(RX == 4 && RW == 10, "placement of the output spectra");
__device__ __forceinline__ uint32_t y_unit(uint32_t db, uint32_t tau, uint32_t b, uint32_t pmask) {
    const uint32_t n = (((db >> 1) & 2) + (db & 1)) * XPC + ((db >> 1) & 1) * kNT + tau, r = n / 3;
    return run_off(r + (r >= 192 && r < 278 ? (r < 214 ? 64 : -22) : 0), n % 3, b, pmask);
}
__device__ __forceinline__ int y_gate(int t) { return t ? 28 + t : 27; }
__device__ __forceinline__ int step_k(int h) { return h < HEND ? h >> 1 : 28 + (h & 3); }
__device__ __forceinline__ int step_m(int h) { return h < HEND ? h & 1 : (h >> 2) & 1; }
constexpr uint64_t x_mask() {
    uint64_t r = 2 | (3ull << 58);
    for (int v = 2; v < 58; v++)
        if ((0x73 >> (v & 7)) & 1) r |= 1ull << v;
    return r;
}
constexpr uint64_t XMASK = x_mask();
__device__ __forceinline__ int x_round(int v, int wg) {
    return v == 0 ? wg : (v < 60 && wg != (v & 1) && ((XMASK >> v) & 1)) ? 1 + __popcll(XMASK << (63 - v)) : -1;
}
__device__ __forceinline__ int w_step(int v, int wg) {
    return v == 0 ? -1 : v < 60 ? (wg == (v & 1) ? v - 1 : -1) : v < 62 ? 2 * v - 61 + wg : (v == 62 && wg == 1) ? 63 : -1;
}

__device__ __forceinline__ uint32_t plan_word(int v, int wg, int cta) {
    const int r = x_round(v, wg), h = w_step(v, wg);
    if (r < 0 && h < 0) return 0;
    const bool last = v >= 60 || (v & 1) || (v > 0 && wg == 0 && x_round(v + 1, 0) < 0);
    uint32_t off, row, gate;
    if (r >= 0) {
        const int u = r * NCTA + cta, cb = u / XPC, i = u - cb * XPC, b = i >= kNT, tau = i - b * kNT;
        row = tau & 63;
        off = (((cb % RX) * 64 + b) << 16) + ((tau >> 6) << 14) + b + 2;
        gate = cb >= RX ? 2 * (cb - RX) + 2 : 0;
    } else {
        const int ring = (h + RW - 64 % RW) % RW;
        row = 0;
        off = ((ring * 22) << 16) + (ring << 12) + 4;
        gate = h >= RW ? ((h - RW + 1) >> 1) + 1 : 0;
    }
    return (off + row * 128) | ((row & 7) << 4) | (last << 3) | ((v > 60) << 24) | (gate << 26);
}

struct Xf {
    uint32_t sbase;
    uint8_t *px, *pw;
    uint32_t cx, cw;
    uint32_t xsw;
    uint32_t dw;
    uint32_t e;
    int lane;
};
__device__ __forceinline__ uint32_t plan_load(const Xf& f, uint32_t v, int wg) {
    uint32_t e;
    asm volatile("ld.shared.u32 %0, [%1];" : "=r"(e) : "r"(f.sbase + OFF_PLAN + v * 8 + wg * 4));
    return __shfl_sync(0xffffffffu, e, 0);
}
template <bool W>
__device__ __forceinline__ void unit_mma(float (&acc)[32], const Xf& f, uint32_t raw) {
    const uint32_t dB = desc_lo(raw);
    if (W) {
        const uint32_t dG = desc_lo(f.sbase + OFF_G);
        wgmma_n64_ss<HI64, 0>(acc, dG, dB);
        wgmma_n64_ss<HI64, 1>(acc, dG + 2, dB + 128);
    } else {
        const uint32_t dF = desc_lo(f.sbase + OFF_F);
        wgmma_n64_ss<HI128, 0>(acc, dF, dB);
        wgmma_n64_ss<HI128, 1>(acc, dF + 2, dB + 128);
        wgmma_n64_ss<HI128, 1>(acc, dF + 4, dB + 256);
        wgmma_n64_ss<HI128, 1>(acc, dF + 6, dB + 384);
    }
    wg_commit();
}
constexpr int DROP = 3;
__device__ __forceinline__ uint32_t pack_sp(float lo, float hi) {
    const uint32_t r = pack_f16(lo, hi);
    return DROP ? (r + (0x10001u << DROP >> 1)) & ~(((1u << DROP) - 1) * 0x10001u) : r;
}
__device__ __forceinline__ void st_quad(uint8_t* p, const float (&acc)[32], int j0) {
    stg128(p, pack_sp(acc[j0], acc[j0 + 1]), pack_sp(acc[j0 + 4], acc[j0 + 5]), pack_sp(acc[j0 + 8], acc[j0 + 9]),
           pack_sp(acc[j0 + 12], acc[j0 + 13]));
}
template <bool W>
__device__ __forceinline__ void unit_store(float (&acc)[32], const Xf& f, uint32_t e) {
    const uint32_t sel = ((W ? f.cw >> (8 + ((e >> 12) & 15)) : e ^ (f.cx >> (8 + ((e >> 21) & 6)))) & 1) << 13;
    const uint32_t o = (e & (W ? 0xFF0F80u : 0xFFFF80u)) + ((e ^ (W ? f.cw : f.cx)) & 0x70);
    uint8_t* const b = W ? f.pw : f.px;
    uint8_t *p0 = b + (o + sel), *p1 = b + ((o ^ 64) + sel);
    reg_fence(acc);
    if (W) {
        st_quad(p0, acc, 0);
        st_quad(p1, acc, 16);
        st_quad(p0 + 4096, acc, 2);
        st_quad(p1 + 4096, acc, 18);
    } else {
        const int d = 131072 + 8192 - 2 * (int)sel;
        st_quad(p0, acc, 0);
        st_quad(p1, acc, 2);
        st_quad(p0 + d, acc, 16);
        st_quad(p1 + d, acc, 18);
    }
}
__device__ __forceinline__ void unit_done(const Xf& f, uint32_t e, uint32_t v) {
    if (e & 8) {
        __syncwarp();
        if (f.lane == 0) mbar_arrive(f.sbase + OFF_BAR + B_SIG + 8 * ((v >> 1) + ((e >> 24) & 1)));
    }
}
__device__ __forceinline__ void step_wait(Xf& f, uint32_t v, int wg) {
    const uint32_t bars = f.sbase + OFF_BAR;
    if (f.e >> 26) mbar_wait(bars + B_GATE - 8 + 8 * (f.e >> 26), 0);
    mbar_wait(bars + B_FULL + 8 * (v % NST), (v / NST) & 1);
}

template <bool DC, int KIND>
__device__ __forceinline__ void gemm_step(uint32_t (&a0)[40], uint32_t (&a1)[40], float (&at)[32], Xf& f, uint32_t v, uint32_t xs, int wg, bool first) {
    const uint32_t bars = f.sbase + OFF_BAR, sb = desc_lo(f.sbase), xb = sb + OFF_X / 16 + xs * (XB / 16), raw = raw_slot(f.sbase, v, wg);
    const uint32_t dx0 = xb + f.xsw, dx1 = xb + (f.xsw ^ 4), dw = f.dw + (v % NST) * 512, e = f.e;
    wg_fence();
    if (KIND) unit_mma<KIND != 1>(at, f, raw);
    constexpr int N1 = KIND == 0 ? 2 : NPRE;
    gemm_mmas<DC, 0, N1>(a0, a1, dx0, dx1, dw);
    wg_commit();
    f.e = plan_load(f, v + 1, wg);
    wg_wait<1>();
    if (!KIND && !first && f.lane == 0) mbar_arrive(bars + B_EMPTY + 8 * ((v - 1) % NST));
    if (KIND) unit_store<KIND != 1>(at, f, e);
    if (KIND) unit_done(f, e, v);
    gemm_mmas<DC, N1, 7>(a0, a1, dx0, dx1, dw);
    if (KIND && !first && f.lane == 0) mbar_arrive(bars + B_EMPTY + 8 * ((v - 1) % NST));
    gemm_mma<DC, 7>(a0, a1, dx0, dx1, dw);
    wg_commit();
}
template <bool DC>
__device__ __forceinline__ void any_step(uint32_t (&a0)[40], uint32_t (&a1)[40], float (&at)[32], Xf& f, uint32_t v, uint32_t xs, int wg, bool first) {
    step_wait(f, v, wg);
    const uint32_t kind = (f.e >> 1) & 3;
    if (kind == 1) gemm_step<DC, 1>(a0, a1, at, f, v, xs, wg, first);
    else if (kind == 2) gemm_step<DC, 2>(a0, a1, at, f, v, xs, wg, first);
    else gemm_step<DC, 0>(a0, a1, at, f, v, xs, wg, first);
}
template <bool DC>
__device__ __forceinline__ void gemm_main(uint32_t (&a0)[40], uint32_t (&a1)[40], uint32_t (&b0)[40], uint32_t (&b1)[40], Xf& f, int wg) {
    float at[32];
#pragma unroll 1
    for (uint32_t k = 0; k < HEND / 2; k++) {
        any_step<DC>(a0, a1, at, f, V0 + 2 * k, k & 3, wg, k == 0);
        any_step<DC>(b0, b1, at, f, V0 + 2 * k + 1, k & 3, wg, false);
    }
    wg_wait<0>();
    if (f.lane == 0) mbar_arrive(f.sbase + OFF_BAR + B_EMPTY + 8 * ((V0 + HEND - 1) % NST));
}
__device__ __forceinline__ void w_fetch(uint32_t (&d)[4][4], const Xf& f, uint32_t v) {
    const uint32_t bars = f.sbase + OFF_BAR, lane = f.lane;
    const uint32_t wa = ((f.dw & 0xFFFF) << 4) + (v % NST) * 8192 + (lane >> 4) * 1024 + (lane & 7) * 128 +
                        (((((threadIdx.x >> 4) & 6) + ((lane >> 3) & 1)) ^ (lane & 7)) << 4);
    mbar_wait(bars + B_FULL + 8 * (v % NST), (v / NST) & 1);
#pragma unroll
    for (int i = 0; i < 4; i++)
        asm volatile("ldmatrix.sync.aligned.m8n8.x4.trans.shared.b16 {%0,%1,%2,%3}, [%4];" : "=r"(d[i][0]), "=r"(d[i][1]), "=r"(d[i][2]), "=r"(d[i][3])
                     : "r"(wa + i * 2048) : "memory");
}
__device__ __forceinline__ void store_tile(uint32_t (&a0)[40], uint32_t (&a1)[40], const uint32_t (&b0)[40], const uint32_t (&b1)[40], uint32_t (&wn)[4][4],
                                           const Xf& f, bool first, uint32_t stg, int t, int wg, uint8_t* sp, int slot, uint32_t ytab, int wsw) {
    const int w = t >> 5, lane = t & 31, m = lane >> 3, i8 = lane & 7;
    const uint32_t addr = stg + i8 * 256 + (m >> 1) * 128 + (((2 * w + (m & 1)) ^ i8 ^ wsw) << 4);
    const int row = 2 * w + (lane >> 4), phi = 2 * slot + (m & 1);
    const uint32_t src = stg + row * 256 + (m & 1) * 128 + ((i8 ^ row) << 4);
    uint8_t* dst = sp + phi * 128 + ((i8 ^ (phi & 7)) << 4);
    named_bar(2 + wg, 128);
#pragma unroll
    for (int r = 0; r < 6; r++) {
        uint32_t v[4][4], o[4];
        if (r > 0) {
#pragma unroll
            for (int i = 0; i < 4; i++) {
                asm volatile("ld.shared.u32 %0, [%1];" : "=r"(o[i]) : "r"(ytab + (32 * (r - 1) + 8 * i + row) * 4) : "memory");
                asm volatile("ld.shared.v4.b32 {%0,%1,%2,%3}, [%4];" : "=r"(v[i][0]), "=r"(v[i][1]), "=r"(v[i][2]), "=r"(v[i][3])
                             : "r"(src + ((r - 1) & 1) * 8192 + i * 2048) : "memory");
            }
        }
        if (r < 5) {
#pragma unroll
            for (int j = 4 * r; j < 4 * r + 4; j++) stmatrix_x4_t(addr + (r & 1) * 8192 + (j & 3) * 2048, a0[2 * j], a0[2 * j + 1], a1[2 * j], a1[2 * j + 1]);
#pragma unroll
            for (int j = 8 * r; j < 8 * r + 8; j++) {
                asm volatile("mov.b32 %0, %1;" : "=r"(a0[j]) : "r"(b0[j]));
                asm volatile("mov.b32 %0, %1;" : "=r"(a1[j]) : "r"(b1[j]));
            }
        } else if (first) {
            w_fetch(wn, f, V0 + HEND + 4);
        }
        if (r > 0) {
#pragma unroll
            for (int i = 0; i < 4; i++) stg128(dst + o[i], v[i][0], v[i][1], v[i][2], v[i][3]);
        }
        if (r < 5) named_bar(2 + wg, 128);
    }
}

template <bool DC>
__device__ __forceinline__ void gemm_last(uint32_t (&a0)[40], uint32_t (&a1)[40], uint32_t (&w)[2][4][4], const Xf& f, int wg, int m) {
    const uint32_t bars = f.sbase + OFF_BAR, sb = desc_lo(f.sbase), v0 = V0 + HEND + 4 * m;
    if (2 * m + wg > 0) named_bar(3 + 2 * m + wg, 256);
#pragma unroll
    for (uint32_t k = 0; k < 4; k++) {
        const uint32_t xb = sb + OFF_X / 16 + k * (XB / 16), dx0 = xb + f.xsw, dx1 = xb + (f.xsw ^ 4);
        wg_fence();
#pragma unroll
        for (int ks = 0; ks < 2; ks++) {
            wgmma_n160_hr<1>(a0, w[k & 1][ks], dx0 + 2 * ks);
            wgmma_n160_hr<1>(a1, w[k & 1][2 + ks], (DC ? dx1 : dx0) + 2 * ks);
            if (!DC) wgmma_n160_hr<1>(a0, w[k & 1][2 + ks], dx1 + 2 * ks);
            if (!DC) wgmma_n160_hr<-1>(a1, w[k & 1][ks], dx1 + 2 * ks);
        }
        wg_commit();
        if (m == 0 && f.lane == 0) mbar_arrive(bars + B_EMPTY + 8 * ((v0 + k) % NST));
        if (k == 3 && 2 * m + wg < 3) named_arrive(4 + 2 * m + wg, 256);
        if (k > 0) wg_wait<1>();
        if (k < 3) w_fetch(w[(k + 1) & 1], f, v0 + k + 1);
    }
    wg_wait<0>();
    if (m && f.lane == 0) mbar_arrive(bars + B_T2 + 8 * wg);
}

__device__ __forceinline__ float gelu_half(float hv) {
    float th;
    asm("tanh.approx.f32 %0, %1;" : "=f"(th) : "f"(hv * fmaf(hv * hv, 8.0f * 0.7978845608028654f * 0.044715f, 2.0f * 0.7978845608028654f)));
    return fmaf(hv, th, hv);
}
__device__ __noinline__ void direct_block(const __nv_bfloat16* __restrict__ x, const __nv_bfloat16* __restrict__ w,
                                          const __nv_bfloat16* __restrict__ gamma, const __nv_bfloat16* __restrict__ beta,
                                          __nv_bfloat16* __restrict__ out, float* sm, int b, int db, int part, uint32_t epoch) {
    float *xs = sm, *ws = sm + 32 * 17, *red = ws + 16 * 65;
    const int tid = threadIdx.x & 127, bar = 2 + (threadIdx.x >> 7), tx = tid & 15, ty = tid >> 4, row0 = part * 250, lim = min(250, kL - row0);
    float* h = g_direct + (size_t)((b * 8 + db) * 32 + part) * (250 * 64);
    for (int l0 = 0; l0 < lim; l0 += 32) {
        float acc[4][4] = {};
        for (int k0 = 0; k0 < 31 * 512; k0 += 16) {
            named_bar(bar, 128);
            for (int i = tid; i < 1024; i += 128) {
                if (i < 512) xs[(i >> 4) * 17 + (i & 15)] = __bfloat162float(x[((size_t)b * kRows + row0 + min(l0 + (i >> 4), lim - 1)) * 1024 + k0 + (i & 15)]);
                ws[(i >> 6) * 65 + (i & 63)] = __bfloat162float(w[(size_t)(k0 + (i >> 6)) * 512 + 64 * db + (i & 63)]);
            }
            named_bar(bar, 128);
            for (int k = 0; k < 16; k++)
#pragma unroll
                for (int i = 0; i < 4; i++)
#pragma unroll
                    for (int j = 0; j < 4; j++) acc[i][j] = fmaf(xs[(ty * 4 + i) * 17 + k], ws[k * 65 + tx * 4 + j], acc[i][j]);
        }
#pragma unroll
        for (int i = 0; i < 4; i++)
#pragma unroll
            for (int j = 0; j < 4; j++)
                if (l0 + ty * 4 + i < lim) h[(l0 + ty * 4 + i) * 64 + tx * 4 + j] = acc[i][j];
    }
    const int c = tid & 63;
    float mean = 0.f, var = 0.f;
    for (int r = 0; r < 2; r++) {
        named_bar(bar, 128);
        float s = 0.f;
        for (int l = tid >> 6; l < lim; l += 2) {
            const float v = h[l * 64 + c] - mean;
            s += r ? v * v : v;
        }
        red[tid] = s;
        named_bar(bar, 128);
        unsigned long long* p = g_dpart + ((r * 16 + b * 8 + db) * 32) * 64 + c;
        if (tid < 64)
            asm volatile("st.relaxed.gpu.global.v2.b32 [%0], {%1, %2};" ::"l"(p + part * 64), "r"(__float_as_uint(red[c] + red[64 + c])), "r"(epoch) : "memory");
        s = 0.f;
        for (int k = 0; k < 32; k++) {
            unsigned long long v = 0;
#pragma unroll 1
            for (uint32_t n = 0; n < (1u << 19); n++) {
                asm volatile("ld.relaxed.gpu.global.u64 %0, [%1];" : "=l"(v) : "l"(p + k * 64) : "memory");
                if ((uint32_t)(v >> 32) == epoch) break;
                __nanosleep(200);
            }
            s += __uint_as_float((uint32_t)v);
        }
        (r ? var : mean) = s * (1.0f / kL);
    }
    const float a = __bfloat162float(gamma[64 * db + c]) / sqrtf(var + 1e-5f), be = __bfloat162float(beta[64 * db + c]);
    for (int l = tid >> 6; l < lim; l += 2)
        out[((size_t)b * kL + row0 + l) * 512 + 64 * db + c] = __float2bfloat16(gelu_half(0.5f * fmaf(h[l * 64 + c] - mean, a, be)));
    named_bar(bar, 128);
}

__device__ __forceinline__ int tail_block(uint32_t gr, int t) { return 4 * (t >> 1) + ((gr >> 4) & 2) + (t & 1); }
__device__ __forceinline__ void tail_poll(uint8_t* sp, uint32_t gr, int t) {
#pragma unroll 1
    for (uint32_t n = 0; n < (1u << 15); n++) {
        unsigned v;
        asm volatile("ld.relaxed.gpu.global.u32 %0, [%1];" : "=r"(v) : "l"(y_flag(sp, gr >> 6, tail_block(gr, t))) : "memory");
        if (v >= 32) break;
        __nanosleep(YSLEEP);
    }
    asm volatile("fence.acquire.gpu;" ::: "memory");
    asm volatile("fence.proxy.async.global;" ::: "memory");
}
__device__ __forceinline__ void tail_loads(uint32_t sbase, const uint8_t* sp, uint32_t gr, uint32_t pmask, int u0, int u1, int lane) {
    if (lane >= u0 && lane < u1) {
        const uint32_t bar = sbase + OFF_BAR + B_UNIT + 8 * lane;
        mbar_expect_tx(bar, 8192);
        bulk_g2s(sbase + (lane < 10 ? OFF_U0 : OFF_U1 - 81920) + lane * 8192, sp + y_unit(tail_block(gr, lane / 5), (gr & 31) * 5 + lane % 5, gr >> 6, pmask), 8192, bar);
    }
    __syncwarp();
}
__device__ __forceinline__ const float* corr_src(uint32_t gr, int t) { return &g_corr[(((gr >> 6) * 8 + tail_block(gr, t)) * kNT + (gr & 31) * 5) * 64]; }
__device__ __forceinline__ void corr_load(uint32_t sbase, uint32_t gr, int t, uint32_t bar) {
    bulk_g2s(sbase + (t < 2 ? OFF_C0 : OFF_C1) + (t & 1) * 1280, corr_src(gr, t), 1280, bar);
}
__device__ __forceinline__ void tail_phase(uint32_t sbase, uint8_t* smem, uint8_t* sp, int wg, uint32_t gr, float sx, float sw, const __nv_bfloat16* __restrict__ x,
                                           const __nv_bfloat16* __restrict__ wt, const __nv_bfloat16* __restrict__ gamma,
                                           const __nv_bfloat16* __restrict__ beta, __nv_bfloat16* __restrict__ out) {
    const uint32_t* ts = reinterpret_cast<const uint32_t*>(smem + OFF_TS);
    const int tid = threadIdx.x, w = (tid >> 5) & 3, lane = tid & 31, g = lane >> 2, q = lane & 3;
    const int b = gr >> 6, part = gr & 31;
#pragma unroll 1
    for (int rd = 0; rd < 3; rd++) {
        if (rd < 2) {
            float acc[28], acc2[28], s[8] = {0.f, 0.f, 0.f, 0.f, 0.f, 0.f, 0.f, 0.f};
            const float swq = q == 0 ? sw : 0.f;
            const int t = 2 * rd + wg;
            const uint32_t ub = sbase + (t < 2 ? OFF_U0 : OFF_U1) + (t & 1) * 40960, ubar = sbase + OFF_BAR + B_UNIT + 40 * t;
            const float* c1 = reinterpret_cast<const float*>(smem + (t < 2 ? OFF_C0 : OFF_C1) + (t & 1) * 1280) + 16 * w + g;
            const uint32_t ka = ub + (lane >> 4) * 1024 + (lane & 7) * 128 + (((2 * w + ((lane >> 3) & 1)) ^ (lane & 7)) << 4);
            auto inverse = [&](float (&d)[28], int u) {
                const uint32_t dA = desc_lo(ub + u * 8192), dB = desc_lo(sbase + OFF_F);
                wg_fence();
                wgmma_n56_ss<0>(d, dA, dB);
                wgmma_n56_ss<1>(d, dA + 128, dB + 2);
                wgmma_n56_ss<1>(d, dA + 256, dB + 4);
                wgmma_n56_ss<1>(d, dA + 384, dB + 6);
                wg_commit();
            };
            auto keep = [&](float (&d)[28], int u, int un) {
                const bool ok = mbar_try(ubar + 8 * un, 0);
                reg_fence(d);
                d[25] = fmaf(c1[u * 64] * sx, swq, d[25]);
                d[27] = fmaf(c1[u * 64 + 8] * sx, swq, d[27]);
                if (part == 31 && u == 4) {
                    if (q >= 2) d[16] = d[18] = 0.f;
                    if (q >= 1) d[17] = d[19] = 0.f;
#pragma unroll
                    for (int i = 20; i < 28; i++) d[i] = 0.f;
                }
                const uint32_t a = ka + u * 8192;
#pragma unroll
                for (int j = 0; j < 6; j += 2)
                    stmatrix_x4_t(a + j * 1024, pack_f16(d[4 * j], d[4 * j + 1]), pack_f16(d[4 * j + 2], d[4 * j + 3]),
                                  pack_f16(d[4 * j + 4], d[4 * j + 5]), pack_f16(d[4 * j + 6], d[4 * j + 7]));
                asm volatile("stmatrix.sync.aligned.m8n8.x2.trans.shared.b16 [%0], {%1,%2};"
                             ::"r"(a + 6 * 1024), "r"(pack_f16(d[24], d[25])), "r"(pack_f16(d[26], d[27])) : "memory");
#pragma unroll
                for (int i = 0; i < 28; i++) {
                    s[i & 3] += d[i];
                    s[4 + (i & 3)] = fmaf(d[i], d[i], s[4 + (i & 3)]);
                }
#pragma unroll
                for (int i = 0; i < 8; i++) asm volatile("" : "+f"(s[i]));
                if (!ok) mbar_wait(ubar + 8 * un, 0);
                wg_wait<0>();
            };
            if (t >= 2) mbar_wait(sbase + OFF_BAR + B_C1, 0);
            mbar_wait(ubar, 0);
            inverse(acc, 0);
            mbar_wait(ubar + 8, 0);
            wg_wait<0>();
#pragma unroll 1
            for (int u = 0;; u += 2) {
                inverse(acc2, min(u + 1, 4));
                keep(acc, u, min(u + 2, 4));
                if (u == 4) break;
                inverse(acc, u + 2);
                keep(acc2, u + 1, min(u + 3, 4));
            }
#pragma unroll
            for (int i = 0; i < 4; i++) s[i] = s[2 * i] + s[2 * i + 1];
#pragma unroll
            for (int i = 0; i < 2; i++) s[i] = (q & 2 ? s[2 + i] : s[i]) + __shfl_xor_sync(0xffffffffu, q & 2 ? s[i] : s[2 + i], 2);
            const float mine = (q & 1 ? s[1] : s[0]) + __shfl_xor_sync(0xffffffffu, q & 1 ? s[0] : s[1], 1);
            asm volatile("red.relaxed.gpu.global.add.u64 [%0], %1;"
                         ::"l"(part_sums(sp, b, tail_block(gr, t), ts[76]) + 2 * (16 * w + 8 * (q & 1) + g) + (q >> 1)),
                         "l"(fabsf(mine) < 0x1p25f ? __float2ll_rn(mine * 0x1p21f) * 4096 + 1 : 65ll) : "memory");
            __syncwarp();
            if (lane == 0) mbar_arrive(sbase + OFF_BAR + B_SUM + 8 * t);
            if (rd == 0) continue;
        }
        const int t = 2 * rd - 2 + wg, db = tail_block(gr, t);
#pragma unroll 1
        for (uint32_t n = 0; n < (1u << 20); n++)
            if (mbar_try(sbase + OFF_BAR + B_NRM + 8 * t, 0)) break;
        if (reinterpret_cast<const volatile uint32_t*>(ts)[77 + t]) {
            direct_block(x, wt, gamma, beta, out, reinterpret_cast<float*>(smem + OFF_DIR + wg * 8192), b, db, part, ts[76]);
            continue;
        }
        const int jh = g & 1, r0 = 4 * w;
        const int lim = min(250, kL - part * 250) - r0 - (g >> 1);
        float na[8], nb[8];
#pragma unroll
        for (int i = 0; i < 8; i += 2) {
            const float4 v = reinterpret_cast<const float4*>(smem + OFF_GB)[32 * t + 16 * jh + 2 * i + q];
            na[i] = v.x; nb[i] = v.y; na[i + 1] = v.z; nb[i + 1] = v.w;
        }
        __nv_bfloat16* o = out + ((size_t)b * kL + part * 250 + r0 + (g >> 1)) * 512 + 64 * db + 32 * jh + 8 * q;
        int l = r0 + ((lane >> 1) & 3);
        uint32_t ra = sbase + (t < 2 ? OFF_U0 : OFF_U1) + (t & 1) * 40960 + l * 128;
        const int cc = 4 * (lane & 1) + (lane >> 3);
        auto fetch = [&](uint32_t (&r)[4]) {
            asm volatile("ldmatrix.sync.aligned.m8n8.x4.shared.b16 {%0,%1,%2,%3}, [%4];"
                         : "=r"(r[0]), "=r"(r[1]), "=r"(r[2]), "=r"(r[3]) : "r"(ra + (((cc ^ l) & 7) << 4)) : "memory");
            const bool wrap = l >= kMO - 16;
            l += wrap ? 16 - kMO : 16;
            ra += wrap ? 2048 + 8192 - kMO * 128 : 2048;
        };
        auto gelu8 = [&](const uint32_t (&r)[4], uint32_t (&p)[4]) {
#pragma unroll
            for (int i = 0; i < 4; i++) {
                float lo, hi;
                asm("{\n.reg .b16 a, b;\nmov.b32 {a, b}, %2;\ncvt.f32.f16 %0, a;\ncvt.f32.f16 %1, b;\n}" : "=f"(lo), "=f"(hi) : "r"(r[i]));
                p[i] = pack_bf16(gelu_half(fmaf(lo, na[2 * i], nb[2 * i])), gelu_half(fmaf(hi, na[2 * i + 1], nb[2 * i + 1])));
            }
        };
        uint32_t r[2][4], rn[2][4];
        fetch(r[0]);
        fetch(r[1]);
#pragma unroll 1
        for (int i = 0; i < 256; i += 32) {
            fetch(rn[0]);
            fetch(rn[1]);
            uint32_t p0[4], p1[4];
            gelu8(r[0], p0);
            gelu8(r[1], p1);
            if (i < lim) stg128(o, p0[0], p0[1], p0[2], p0[3]);
            if (i + 16 < lim) stg128(o + 16 * 512, p1[0], p1[1], p1[2], p1[3]);
            o += 32 * 512;
#pragma unroll
            for (int k = 0; k < 4; k++) { r[0][k] = rn[0][k]; r[1][k] = rn[1][k]; }
        }
    }
}
__device__ __forceinline__ void channel_scales(uint32_t sbase, uint8_t* smem, uint8_t* sp, int lane) {
    volatile uint32_t* ts = reinterpret_cast<volatile uint32_t*>(smem + OFF_TS);
    const uint32_t gr = ts[64], bars = sbase + OFF_BAR;
#pragma unroll 1
    for (int t = 0; t < 4; t++) {
#pragma unroll 1
        for (uint32_t n = 0; n < (1u << 20); n++)
            if (mbar_try(bars + B_SUM + 8 * t, 0)) break;
        long long s[4];
#pragma unroll 1
        for (uint32_t n = 0; n < (1u << 19); n++) {
            const unsigned long long* p = part_sums(sp, gr >> 6, tail_block(gr, t), ts[76]) + 4 * lane;
#pragma unroll
            for (int i = 0; i < 4; i++) asm volatile("ld.relaxed.gpu.global.u64 %0, [%1];" : "=l"(s[i]) : "l"(p + i) : "memory");
            if (__all_sync(0xffffffffu, s[0] & s[1] & s[2] & s[3] & 32)) break;
        }
        const float sx = __uint_as_float(ts[74]), sw = __uint_as_float(ts[75]);
        bool bad = false;
#pragma unroll
        for (int i = 0; i < 2; i++) {
            const float mean = (float)(s[2 * i] >> 12) * (0x1p-21f / kL), sq = (float)(s[2 * i + 1] >> 12) * (0x1p-21f / kL);
            float2* gb = reinterpret_cast<float2*>(smem + OFF_GB) + 64 * t + 2 * lane + i;
            const float den = fmaxf(sq - mean * mean, 0.f) + 1e-5f * sx * sw * sx * sw, a = gb->x * rsqrtf(den);
            *gb = make_float2(0.5f * a, 0.5f * (gb->y - mean * a));
            bad |= ((s[2 * i] | s[2 * i + 1]) & 0xFC0) || !(den >= 0x1p-22f);
        }
        bad = __any_sync(0xffffffffu, bad);
        if (lane == 0) ts[77 + t] = bad;
        __syncwarp();
        if (lane == 0) mbar_arrive(bars + B_NRM + 8 * t);
    }
}

__device__ __forceinline__ void publish_tiles(uint8_t* sp, uint32_t bars, int cta, int wg) {
#pragma unroll 1
    for (int m = 0; m < 2; m++) {
        mbar_wait(bars + B_YS + 8 * (2 * m + wg), 0);
        asm volatile("fence.acq_rel.gpu;" ::: "memory");
        red_relaxed(y_flag(sp, (cta >> 1) & 1, 4 * m + 2 * (cta & 1) + wg));
    }
}

__global__ void __launch_bounds__(384, 1)
main_kernel(const __grid_constant__ CUtensorMap tmx, const __grid_constant__ CUtensorMap tmw0, const __grid_constant__ CUtensorMap tmw1,
            const __nv_bfloat16* __restrict__ x, const __nv_bfloat16* __restrict__ wt, const __nv_bfloat16* __restrict__ gamma,
            const __nv_bfloat16* __restrict__ beta, __nv_bfloat16* __restrict__ out) {
    extern __shared__ __align__(1024) uint8_t smem_raw[];
    const uint32_t sbase = smem_u32(smem_raw) & ~1023u;
    const uint32_t bars = sbase + OFF_BAR;
    const int tid = threadIdx.x, wg = __shfl_sync(0xffffffffu, tid >> 7, 0), lane = tid & 31;
    const int cta = blockIdx.x;
    volatile uint32_t* ts = reinterpret_cast<volatile uint32_t*>(smem_raw + OFF_TS);
    uint8_t* const sp = reinterpret_cast<uint8_t*>((reinterpret_cast<uintptr_t>(g_sp) + (2u << 20) - 1) & ~(uintptr_t)((2u << 20) - 1));
    const bool probing = (cta & 3) == 0 && lane == 0 && tid < 128 && (tid >= 64 || cta < 4 * NPAGES);
    unsigned* pw = reinterpret_cast<unsigned*>(sp + (tid < 64 ? ((cta >> 2) << 21) + ((tid & 32) ? 15 : 13) * 4096
                                                              : ((tid & 32) ? 0 : 14) * 4096 + (cta >> 2) * 128));
    unsigned pv = 0;
    if (probing) {
        stg128(pw, 0, 0, 0, 0);
        stg128(pw + 4, 0, 0, 0, 0);
        asm volatile("atom.relaxed.gpu.global.exch.b32 %0, [%1], %2;" : "=r"(pv) : "l"(pw), "r"(7) : "memory");
    }
    if (tid == 320) bar_setup<0, B_SIG>(bars);
    if (tid >= 256 && tid < 262) ts[68 + tid - 256] = tid < 260 ? 0xffffu : 0;
    if (tid == 383) asm volatile("griddepcontrol.launch_dependents;");
    __syncthreads();

    if (wg == 2) {
        asm volatile("setmaxnreg.dec.sync.aligned.u32 40;");
        const int role = (tid >> 5) & 3;
        if (role == 3) {
            unsigned v = 0;
#pragma unroll 1
            for (uint32_t n = 0; n < (1u << 15); n++) {
                asm volatile("ld.relaxed.gpu.global.u32 %0, [%1];" : "=r"(v) : "l"(&g_tsel[lane]) : "memory");
                if (__all_sync(0xffffffffu, v & 16)) break;
                __nanosleep(TSLEEP);
            }
            const uint32_t m1 = __ballot_sync(0xffffffffu, v & 8), below = (1u << lane) - 1;
            const int rank = (v & 8) ? 32 - __popc(m1) + __popc(m1 & below) : __popc(~m1 & below);
            ts[lane] = rank;
            ts[32 + rank] = lane;
            const uint32_t p0 = __ballot_sync(0xffffffffu, v & 1);
            if (lane == 0) ts[66] = p0;
            if (lane == (cta >> 2)) ts[64] = rank * 4 + (cta & 3);
            const int part = (m1 >> (cta >> 2)) & 1;
            __syncwarp();
            if (lane == 0) mbar_arrive(bars + B_TSEL);
            mbar_wait(bars + B_TSEL, 0);
            mbar_wait(bars + B_PUB, 0);
            int gc = 0;
            const int gend = lane == 0 ? 33 : lane == 1 ? 32 : 0;
#pragma unroll 1
            for (uint32_t n = 0; n < (1u << 16) && __any_sync(0xffffffffu, gc < gend); n++) {
                asm volatile("ld.relaxed.gpu.global.u32 %0, [%1];" : "=r"(v) : "l"(chunk_flag(sp, lane == 1, part, min(gc, 32 - (lane & 1)))) : "memory");
                if (gc < gend && v >= NCTA) {
                    asm volatile("fence.acquire.gpu;" ::: "memory");
                    mbar_arrive(bars + (lane == 0 ? B_RDY : B_GATE) + 8 * gc);
                    gc++;
                }
            }
            if (lane == 0) publish_tiles(sp, bars, cta, 1);
        } else if (role == 0) {
            const int b = (cta >> 1) & 1, dq = cta & 1;
            for (int v = 0; v < V0; v++) {
                mbar_wait(bars + B_EMPTY + 8 * (v % NST), ((v / NST) & 1) ^ 1);
                if (lane == 0) {
                    mbar_arrive(bars + B_FULL + 8 * (v % NST));
                    mbar_arrive(bars + B_FULL + 8 * (v % NST));
                }
            }
            mbar_wait(bars + B_TSEL, 0);
            const uint32_t gr = ts[64], grp = gr >> 6, idx = (gr >> 2) & 15, pmask = ts[66];
            const uint32_t n0 = idx * 4 + 2 * dq + ((lane & 1) ^ 1), r0 = lane < 3 ? idx * 4 + b : R_W + n0 / 3;
            const uint32_t base = (r0 << 16) + 4096 + ((lane < 3 ? lane : n0 % 3) << 14), step = (lane < 3 ? 64 : 22) << 16;
            uint32_t sels = 0;
            for (int i = 0; i < 12; i++) sels |= run_sel(r0 + i * (step >> 16), grp, pmask) << i;
            int ld = 0;
            const uint32_t bytes = lane == 2 ? XB - 16384 : 8192;
#pragma unroll 1
            for (int h = 0; h < 64; h++) {
                const int s = step_k(h), st = (h + V0) % NST;
                const bool newx = h < HEND ? !(h & 1) : h < HEND + 4;
                const uint32_t fb = bars + B_FULL + 8 * st;
                const uint32_t k = lane < 3 ? (s >> 1) % RX : (h + RW - 64 % RW) % RW, half = lane < 3 ? s & 1 : 0;
                const uint8_t* gsrc = sp + (base + k * step + (half << 17) + ((((sels >> k) ^ half) & 1) << 13));
                const uint32_t dst = sbase + (lane < 3 ? OFF_X + (s & 3) * XB + lane * 8192 : st * 8192 + (lane == 3 ? OFF_W0 : OFF_W1));
                auto landed = [&]() {
                    if (ld < h && mbar_test(bars + B_FULL + 8 * ((ld + V0) % NST), ((ld + V0) / NST) & 1)) {
                        if (!(ld & 1) && lane < 2) red_relaxed(chunk_flag(sp, 1, lane, ld >> 1));
                        ld++;
                    }
                };
                if ((h & 1) || h == 0) {
#pragma unroll 1
                    for (uint32_t n = 0; n < (1u << 19) && !mbar_test(bars + B_RDY + 8 * ((h + 1) >> 1), 0); n++) landed();
                    asm volatile("fence.proxy.async.global;" ::: "memory");
                }
#pragma unroll 1
                for (uint32_t n = 0; n < (1u << 19) && !mbar_test(bars + B_EMPTY + 8 * st, (((h + V0) / NST) & 1) ^ 1); n++) landed();
#pragma unroll 1
                for (uint32_t n = 0; n < (1u << 19) && ld <= h - NST; n++) landed();
                if (lane == 0) mbar_expect_tx(fb, newx ? 16384 + XB : 16384);
                __syncwarp();
                if (lane < 3 ? newx : lane < 5) bulk_g2s(dst, gsrc, bytes, fb);
            }
#pragma unroll 1
            for (; ld < 63; ld++) {
                mbar_wait(bars + B_FULL + 8 * ((ld + V0) % NST), ((ld + V0) / NST) & 1);
                if (!(ld & 1) && lane < 2) red_relaxed(chunk_flag(sp, 1, lane, ld >> 1));
            }
            tail_poll(sp, gr, 0);
            mbar_wait(bars + B_T2, 0);
            tail_loads(sbase, sp, gr, pmask, 0, 5, lane);
            tail_poll(sp, gr, 1);
            tail_loads(sbase, sp, gr, pmask, 5, 8, lane);
            mbar_wait(bars + B_YS + 16, 0);
            tail_loads(sbase, sp, gr, pmask, 8, 10, lane);
            mbar_wait(bars + B_T2 + 8, 0);
            if (lane == 0) {
                mbar_expect_tx(bars + B_C1, 2560);
                corr_load(sbase, gr, 2, bars + B_C1);
                corr_load(sbase, gr, 3, bars + B_C1);
            }
            tail_poll(sp, gr, 2);
            tail_loads(sbase, sp, gr, pmask, 10, 15, lane);
            tail_poll(sp, gr, 3);
            tail_loads(sbase, sp, gr, pmask, 15, 20, lane);
            mbar_wait(bars + B_GATE + 8 * 31, 0);
            unsigned exits = 0;
            if (lane == 0) exits = atomicAdd(&g_exit, 1);
            if (__shfl_sync(0xffffffffu, exits, 0) == NCTA - 1) {
                for (int i = 0; i < 4; i++) *chunk_flag(sp, i >> 1, i & 1, lane) = 0;
                if (lane < 2) *chunk_flag(sp, 0, lane, 32) = 0;
                g_tsel[lane] = 0;
                if (lane < 16) *y_flag(sp, lane >> 3, lane & 7) = 0;
                if (lane == 0) { g_exit = 0; g_epoch = ts[76]; }
            }
        } else if (role == 1) {
            auto raw_load = [&](int r, int h, uint32_t gr, uint32_t dst, uint32_t bar) {
                if (r >= 0) {
                    const int u = r * NCTA + cta, i = u % XPC, b = i >= kNT;
                    tma3d(dst, &tmx, u / XPC * 64, (i - b * kNT) * kMO, b, bar);
                } else if (h >= 0) {
                    const int c = 32 * step_k(h) + ((gr >> 1) & 30);
                    tma3d_ef(dst, c < 512 ? &tmw0 : &tmw1, step_m(h) * 256 + (gr & 3) * 64, 0, c & 511, bar);
                }
            };
            uint32_t gr;
            {
                const int v = lane >> 1, r = v < V0 ? x_round(v, lane & 1) : -1, h = v < V0 ? w_step(v, lane & 1) : -1;
                const uint32_t dst = pre_slot(sbase, v, lane & 1), bar = bars + B_PRE + 8 * lane;
                if (r >= 0 || h >= 0) mbar_expect_tx(bar, r >= 0 ? 8192 : 4096);
                if (v < PRE1) raw_load(r, -1, 0, dst, bar);
                mbar_wait(bars + B_TSEL, 0);
                gr = ts[64];
                raw_load(-1, h, gr, dst, bar);
                if (v >= PRE1) raw_load(r, -1, 0, dst, bar);
                __syncwarp();
            }
            mbar_wait(bars + B_PUB, 0);
#pragma unroll 1
            for (int v = V0; v < V0 + 64; v++) {
                mbar_wait(bars + B_EMPTY + 8 * (v % NST), ((v / NST) & 1) ^ 1);
                __syncwarp();
                const int r = lane < 2 ? x_round(v, lane) : -1, h = lane < 2 ? w_step(v, lane) : -1;
                const uint32_t fb = bars + B_FULL + 8 * (v % NST);
                const uint32_t bytes = __reduce_add_sync(0xffffffffu, r >= 0 ? 8192 : h >= 0 ? 4096 : 0);
                if (lane == 0) mbar_expect_tx(fb, bytes);
                __syncwarp();
                raw_load(r, h, gr, raw_slot(sbase, v, lane), fb);
                if (v >= 20 && v < 40) {
                    const int t = (v - 20) / 5, i = (v - 20) % 5 * 32 + lane, db = 4 * (t >> 1) + 2 * (cta & 1) + (t & 1);
                    ts[(OFF_YT - OFF_TS) / 4 + t * kNT + i] = y_unit(db, i, (cta >> 1) & 1, ts[66]);
                }
                if (v == 66 && lane == 0) {
#pragma unroll 1
                    for (uint32_t n = 0; n < (1u << 15); n++) {
                        unsigned c0, c1;
                        asm volatile("ld.relaxed.gpu.global.u32 %0, [%1];" : "=r"(c0) : "l"(&g_cready[(gr >> 6) * 64]) : "memory");
                        asm volatile("ld.relaxed.gpu.global.u32 %0, [%1];" : "=r"(c1) : "l"(&g_cready[(gr >> 6) * 64 + 32]) : "memory");
                        if (c0 == ts[76] && c1 == ts[76]) break;
                        __nanosleep(500);
                    }
                    asm volatile("fence.acquire.gpu;" ::: "memory");
                    asm volatile("fence.proxy.async.global;" ::: "memory");
                    mbar_expect_tx(bars + B_FTAB, 8192 + 2560);
                    bulk_g2s(sbase + OFF_F, g_tab.inv, 8192, bars + B_FTAB);
                    for (int t = 0; t < 2; t++) {
                        corr_load(sbase, gr, t, bars + B_FTAB);
                        asm volatile("cp.async.bulk.prefetch.L2.global [%0], 1280;" ::"l"(corr_src(gr, 2 + t)) : "memory");
                    }
                }
            }
            channel_scales(sbase, smem_raw, sp, lane);
        } else {
            uint32_t epoch;
            if (lane == 0) {
                bar_setup<B_SIG, B_END>(bars);
                mbar_arrive(bars + B_TSEL);
            }
            asm volatile("ld.relaxed.gpu.global.u32 %0, [%1];" : "=r"(epoch) : "l"(&g_epoch) : "memory");
            mbar_wait(bars + B_TSEL, 0);
            const uint32_t gr = ts[64];
#pragma unroll
            for (int i = lane; i < 256; i += 32) {
                const int d = 64 * tail_block(gr, i >> 6) + (i & 33) + 8 * ((i >> 1) & 3) + 2 * ((i >> 3) & 3);
                ts[(OFF_GB - OFF_TS) / 4 + 2 * i] = (uint32_t)__bfloat16_as_ushort(gamma[d]) << 16;
                ts[(OFF_GB - OFF_TS) / 4 + 2 * i + 1] = (uint32_t)__bfloat16_as_ushort(beta[d]) << 16;
            }
            if (lane == 0) ts[76] = epoch + 1;
            if (cta < 32) stg128(part_sums(sp, cta >> 4, (cta >> 1) & 7, epoch) + (cta & 1) * 64 + 2 * lane, 0, 0, 0, 0);
            __syncwarp();
            if (lane) return;
#pragma unroll 1
            for (int gc = 0; gc < 33;) {
                mbar_wait(bars + B_SIG + 8 * gc, 0);
                if (gc < MERGE) mbar_wait(bars + B_SIG + 8 * MERGE, 0);
                int ge = gc + 1;
                while (ge < 33 && mbar_test(bars + B_SIG + 8 * ge, 0)) ge++;
                asm volatile("fence.acq_rel.gpu;" ::: "memory");
                for (; gc < ge; gc++) {
                    red_relaxed(chunk_flag(sp, 0, 0, gc));
                    red_relaxed(chunk_flag(sp, 0, 1, gc));
                    if (gc == 0) mbar_arrive(bars + B_PUB);
                }
            }
            publish_tiles(sp, bars, cta, 0);
        }
    } else {
        asm volatile("setmaxnreg.inc.sync.aligned.u32 232;");
        uint4 fw[2];
#pragma unroll
        for (int j = 0; j < 2; j++) fw[j] = __ldg(reinterpret_cast<const uint4*>(g_tab.fwd) + tid + 256 * j);
        if (wg == 1) {
            uint4 sm[8];
#pragma unroll
            for (int j = 0; j < 4; j++) {
                const int r = 2 * j + ((tid >> 6) & 1);
                sm[j] = __ldg(reinterpret_cast<const uint4*>(x) + ((r >> 2) * kRows + 1000 + 2000 * (r & 3)) * 128 + (((j + r) & 1) << 6) + (tid & 63));
                sm[4 + j] = __ldg(reinterpret_cast<const uint4*>(wt) + (4 * r * 512 + 67 * r + 7) * 64 + (tid & 63));
            }
#pragma unroll
            for (int k = 0; k < 2; k++) {
                uint32_t mx = 0;
#pragma unroll
                for (int j = 4 * k; j < 4 * k + 4; j++)
                    mx = __vmaxu2(__vmaxu2(mx, __vmaxu2(sm[j].x & 0x7FFF7FFFu, sm[j].y & 0x7FFF7FFFu)), __vmaxu2(sm[j].z & 0x7FFF7FFFu, sm[j].w & 0x7FFF7FFFu));
                mx = __reduce_max_sync(0xffffffffu, max(mx & 0xFFFFu, mx >> 16));
                if (lane == 0) atomicMax(const_cast<uint32_t*>(ts) + 72 + k, mx);
            }
        }
        if ((cta & 3) == 0) {
            if (probing) {
                const int w = tid >> 5;
                unsigned best = 0xffffu;
#pragma unroll 1
                for (int r = 0; r < 6; r++) {
                    unsigned t0, t1;
                    asm volatile("{\n.reg .pred p;\nsetp.eq.u32 p, %1, 0xffffffff;\nmov.u32 %0, 0;\n@!p mov.u32 %0, %%clock;\n}"
                                 : "=r"(t0) : "r"(pv) : "memory");
                    asm volatile("atom.relaxed.gpu.global.exch.b32 %0, [%1], %2;" : "=r"(pv) : "l"(pw), "r"(r) : "memory");
                    asm volatile("{\n.reg .pred p;\nsetp.eq.u32 p, %1, 0xffffffff;\nmov.u32 %0, 0;\n@!p mov.u32 %0, %%clock;\n}"
                                 : "=r"(t1) : "r"(pv) : "memory");
                    ts[68 + w] = best = min(best, t1 - t0);
                    const unsigned other = ts[68 + (w ^ 1)];
                    if (min(best, other) < PROBE_NEAR && max(best, other) > PROBE_NEAR) break;
                }
            }
            if (wg == 0) {
                named_bar(2, 128);
                if (tid == 0) {
                    const uint32_t part = ts[71] < ts[70];
                    const uint32_t v = 16 | (part << 3) | ((ts[69] < ts[68]) ^ part);
                    asm volatile("st.relaxed.gpu.global.u32 [%0], %1;" ::"l"(&g_tsel[cta >> 2]), "r"(v) : "memory");
                }
            }
        }
        uint32_t plan = tid < 2 * (V0 + 65) ? plan_word(tid >> 1, tid & 1, cta) : 0;
        {
            named_bar(1, 256);
            const uint32_t ex = min(max(251 - (int)(ts[72] >> 7), 8), 187), ew = min(max(251 - (int)(ts[73] >> 7), 8), 187);
            if (tid == 0) { ts[74] = ex << 23; ts[75] = ew << 23; }
            const uint32_t sx = ex * 0x800080u, sw = ew * 0x800080u;
#pragma unroll
            for (int j = 0; j < 2; j++) {
                const int i = tid + 256 * j, row = i >> 3, c = (i ^ row) & 7;
                sts128(sbase + OFF_F + 16 * i, mul_bf16x2(fw[j].x, sx), mul_bf16x2(fw[j].y, sx), mul_bf16x2(fw[j].z, sx), mul_bf16x2(fw[j].w, sx));
                if (c < 2) sts128(sbase + OFF_TMP + row * 32 + c * 16, mul_bf16x2(fw[j].x, sw), mul_bf16x2(fw[j].y, sw), mul_bf16x2(fw[j].z, sw), mul_bf16x2(fw[j].w, sw));
            }
            named_bar(1, 256);
        }
        const int t = tid & 127;
        Xf f;
        f.sbase = sbase; f.lane = lane; f.xsw = cta & 4; f.dw = desc_lo(sbase + (wg ? OFF_W1 : OFF_W0));
        {
            const int w = t >> 5;
            const uint32_t nw = (8 * (w & 1) + (lane >> 2)) * 4 + (cta & 3), rw = R_W + nw / 3;
            f.pw = sp + (rw << 16) + 4096 + ((nw % 3) << 14) + (w >> 1) * 128;
            f.cw = ((lane & 7) ^ (w >> 1)) << 4;
            for (int i = 0; i < RW; i++) f.cw |= run_sel(rw + i * 22, 0, 0) << (8 + i);
            mbar_wait(bars + B_TSEL, 0);
            const uint32_t gr = ts[64], pmask = ts[66];
            const uint32_t rx = ts[8 * w + (lane >> 2)];
            f.px = sp + ((rx & 15) << 18) + 4096;
            f.cx = ((lane & 7) << 4) | ((((pmask >> ((rx >> 3) & 1)) ^ -(((rx >> 1) ^ (rx >> 4)) & 1)) & 0x55) << 8);
#pragma unroll
            for (int i = 0; i < RW; i++) f.cw ^= (((pmask >> ((rw + i * 22) >> 5)) ^ (gr >> 6)) & 1) << (8 + i);
            if (plan & 4) plan |= ((gr & 12) << 8) | ((gr & 48) << 4) | ((gr & 48) << 1);
            if (tid < 2 * (V0 + 65)) ts[(OFF_PLAN - OFF_TS) / 4 + tid] = plan;
            const int row = tid >> 2, ch = tid & 3, s = ts[32 + (gr >> 6) * 16 + ((row >> 1) & 8) + (row & 7)], p = (row >> 3) & 1;
            const int frow = 16 * (s >> 3) + 8 * p + (s & 7);
            uint32_t v[4] = {0, 0, 0, 0};
            if ((ch >> 1) == (row >> 5))
                asm volatile("ld.shared.v4.b32 {%0,%1,%2,%3}, [%4];" : "=r"(v[0]), "=r"(v[1]), "=r"(v[2]), "=r"(v[3])
                             : "r"(sbase + OFF_TMP + frow * 32 + (ch & 1) * 16) : "memory");
            sts128(sbase + OFF_G + row * 64 + ((ch ^ ((row >> 1) & 3)) << 4), v[0], v[1], v[2], v[3]);
            fence_proxy_async_smem();
            named_bar(1, 256);
        }
        {
            float at[32];
#pragma unroll 1
            for (uint32_t v = 0; v < V0; v++) {
                const uint32_t e = plan_load(f, v, wg), raw = pre_slot(sbase, v, wg);
                mbar_wait(bars + B_FULL + 8 * (v % NST), (v / NST) & 1);
                if (e & 6) mbar_wait(bars + B_PRE + 16 * v + 8 * wg, 0);
                if (v == PAUSE) mbar_wait(bars + B_PUB, 0);
                wg_fence();
                if ((e & 6) == 2) {
                    unit_mma<false>(at, f, raw);
                    wg_wait<0>();
                    unit_store<false>(at, f, e);
                } else if (e & 4) {
                    unit_mma<true>(at, f, raw);
                    wg_wait<0>();
                    unit_store<true>(at, f, e);
                }
                if (lane == 0) mbar_arrive(bars + B_EMPTY + 8 * (v % NST));
                unit_done(f, e, v);
            }
        }
        const int slot = cta >> 2;
        f.e = plan_load(f, V0, wg);
        uint32_t a0[40], a1[40], b0[40], b1[40];
#pragma unroll
        for (int i = 0; i < 40; i++) a0[i] = a1[i] = b0[i] = b1[i] = 0;
        if (slot == 0) gemm_main<true>(a0, a1, b0, b1, f, wg);
        else gemm_main<false>(a0, a1, b0, b1, f, wg);
        const uint32_t gr = __shfl_sync(0xffffffffu, ts[64], 0);
        const float sx = __uint_as_float(ts[74]), sw = __uint_as_float(ts[75]);
        uint32_t wr[2][4][4];
        w_fetch(wr[0], f, V0 + HEND);
#pragma unroll 1
        for (int m = 0; m < 2; m++) {
            if (slot == 0) gemm_last<true>(a0, a1, wr, f, wg, m);
            else gemm_last<false>(a0, a1, wr, f, wg, m);
            reg_fence(a0);
            reg_fence(a1);
            const int wsw = gr & 4;
            mbar_wait(bars + B_GATE + 8 * y_gate(2 * m + wg), 0);
            if (m) mbar_wait(bars + B_FTAB, 0);
            const uint32_t ytab = sbase + OFF_YT + (m * 2 + wg) * (kNT * 4);
            store_tile(a0, a1, b0, b1, wr[0], f, m == 0, sbase + OFF_STG + wg * 16384, t, wg, sp, slot, ytab, wsw);
            __syncwarp();
            if (lane == 0) mbar_arrive(bars + B_YS + 8 * (2 * m + wg));
        }
        tail_phase(sbase, smem_raw, sp, wg, gr, sx, sw, x, wt, gamma, beta, out);
    }
}

constexpr int C_STAGE = 32768 + 2 * XB, C_SMEM = 3 * C_STAGE + 64;
__global__ void __launch_bounds__(256, 1) corr_kernel(const __grid_constant__ CUtensorMap tmx, const __grid_constant__ CUtensorMap tmw) {
    extern __shared__ __align__(1024) uint8_t smem_raw[];
    const uint32_t sbase = smem_u32(smem_raw) & ~1023u, bars = sbase + 3 * C_STAGE;
    const int tid = threadIdx.x, wg = __shfl_sync(0xffffffffu, tid >> 7, 0), b = blockIdx.x >> 1, dh = blockIdx.x & 1;
    auto load = [&](int k) {
        const uint32_t st = sbase + (k % 3) * C_STAGE, bar = bars + 8 * (k % 3);
        mbar_expect_tx(bar, C_STAGE);
        for (int i = 0; i < 4; i++) tma2d(st + i * 8192, &tmw, 256 * dh + 64 * i, 64 * k, bar);
        tma4d(st + 32768, &tmx, 64 * k, 64 - kMO, 1, b, bar);
        tma4d(st + 32768 + XB, &tmx, 64 * k, 0, 0, b, bar);
    };
    uint32_t epoch = 0;
    if (tid == 0) {
        for (int i = 0; i < 3; i++) mbar_init(bars + 8 * i, 1);
        fence_mbar_init();
        fence_proxy_async_smem();
        for (int k = 0; k < 3; k++) load(k);
        asm volatile("ld.relaxed.gpu.global.u32 %0, [%1];" : "=r"(epoch) : "l"(&g_epoch) : "memory");
    }
    __syncthreads();
    float a[2][80];
#pragma unroll
    for (int i = 0; i < 80; i++) a[0][i] = a[1][i] = 0.f;
#pragma unroll 1
    for (int k = 0; k < 8; k++) {
        const uint32_t dA = desc_lo(sbase + (k % 3) * C_STAGE + wg * 16384), dB = desc_lo(sbase + (k % 3) * C_STAGE + 32768);
        mbar_wait(bars + 8 * (k % 3), (k / 3) & 1);
        wg_fence();
#pragma unroll
        for (int i = 0; i < 8; i++) {
            wgmma_n160_f<1>(a[i & 1], dA + (i & 1) * 512 + (i >> 1) * 128, dB + (i >> 1) * 2);
            wgmma_n160_f<-1>(a[i & 1], dA + (i & 1) * 512 + (i >> 1) * 128, dB + XB / 16 + (i >> 1) * 2);
        }
        wg_commit();
        wg_wait<0>();
        __syncthreads();
        if (tid == 0 && k + 3 < 8) load(k + 3);
    }
    reg_fence(a[0]);
    reg_fence(a[1]);
    const int w = (tid >> 5) & 3, g = (tid & 31) >> 2, q = tid & 3;
    float* stage = reinterpret_cast<float*>(smem_raw);
#pragma unroll
    for (int i = 0; i < 160; i++) {
        const int m = i / 80, j = i % 80, d = 16 * w + 8 * ((j >> 1) & 1) + g;
        stage[((2 * wg + m) * kNT + 8 * (j >> 2) + 2 * q + (j & 1)) * 64 + (d & 33) + 8 * ((d >> 1) & 3) + 2 * ((d >> 3) & 3)] = a[m][j];
    }
    __syncthreads();
    for (int i = tid; i < 4 * kNT * 16; i += 256)
        reinterpret_cast<float4*>(g_corr)[(b * 8 + 4 * dh) * kNT * 16 + i] = reinterpret_cast<const float4*>(stage)[i];
    __syncthreads();
    if (tid == 0) {
        asm volatile("fence.acq_rel.gpu;" ::: "memory");
        asm volatile("st.relaxed.gpu.global.u32 [%0], %1;" ::"l"(&g_cready[blockIdx.x * 32]), "r"(epoch + 1) : "memory");
    }
}

__global__ void __launch_bounds__(256) plain_conv(const __nv_bfloat16* __restrict__ x, const __nv_bfloat16* __restrict__ w) {
    __shared__ float xs[64][17], ws[16][65];
    float* h = g_direct;
    const int b = blockIdx.z, l0 = blockIdx.x * 64, d0 = blockIdx.y * 64, tx = threadIdx.x & 15, ty = threadIdx.x >> 4;
    float acc[4][4] = {};
    for (int k0 = 0; k0 < 31 * 512; k0 += 16) {
        for (int i = threadIdx.x; i < 1024; i += 256) {
            const int l = min(l0 + (i >> 4), kL - 1);
            xs[i >> 4][i & 15] = __bfloat162float(x[((size_t)b * kRows + l) * 1024 + k0 + (i & 15)]);
            ws[i >> 6][i & 63] = __bfloat162float(w[(size_t)(k0 + (i >> 6)) * 512 + d0 + (i & 63)]);
        }
        __syncthreads();
        for (int k = 0; k < 16; k++)
            for (int i = 0; i < 4; i++)
                for (int j = 0; j < 4; j++) acc[i][j] = fmaf(xs[ty * 4 + i][k], ws[k][tx * 4 + j], acc[i][j]);
        __syncthreads();
    }
    for (int i = 0; i < 4; i++)
        for (int j = 0; j < 4; j++)
            if (l0 + ty * 4 + i < kL) h[((size_t)b * kL + l0 + ty * 4 + i) * 512 + d0 + tx * 4 + j] = acc[i][j];
}
__global__ void __launch_bounds__(256) plain_norm(const __nv_bfloat16* __restrict__ gamma, const __nv_bfloat16* __restrict__ beta,
                                                  __nv_bfloat16* __restrict__ out) {
    __shared__ float s1[8][32], s2[8][32];
    const int c = threadIdx.x & 31, r = threadIdx.x >> 5, d = blockIdx.x * 32 + c;
    const float* h = g_direct + (size_t)blockIdx.y * kL * 512 + d;
    float a = 0.f, q = 0.f;
    for (int l = r; l < kL; l += 8) { const float v = h[(size_t)l * 512]; a += v; q = fmaf(v, v, q); }
    s1[r][c] = a; s2[r][c] = q;
    __syncthreads();
    a = q = 0.f;
    for (int i = 0; i < 8; i++) { a += s1[i][c]; q += s2[i][c]; }
    const float mean = a * (1.0f / kL), sc = __bfloat162float(gamma[d]) / sqrtf(fmaxf(q * (1.0f / kL) - mean * mean, 0.f) + 1e-5f);
    const float sh = __bfloat162float(beta[d]) - mean * sc;
    for (int l = r; l < kL; l += 8)
        out[((size_t)blockIdx.y * kL + l) * 512 + d] = __float2bfloat16(gelu_half(0.5f * fmaf(h[(size_t)l * 512], sc, sh)));
}

typedef CUresult (*EncodeTiledFn)(CUtensorMap*, CUtensorMapDataType, cuuint32_t, void*, const cuuint64_t*, const cuuint64_t*,
                                  const cuuint32_t*, const cuuint32_t*, CUtensorMapInterleave, CUtensorMapSwizzle,
                                  CUtensorMapL2promotion, CUtensorMapFloatOOBfill);

void encode(EncodeTiledFn fn, CUtensorMap* tm, const void* ptr, int rank, const cuuint64_t* dims, const cuuint64_t* strides,
            const cuuint32_t* box, CUtensorMapL2promotion promo, CUtensorMapSwizzle swz = CU_TENSOR_MAP_SWIZZLE_128B) {
    const cuuint32_t es[5] = {1, 1, 1, 1, 1};
    fn(tm, CU_TENSOR_MAP_DATA_TYPE_BFLOAT16, rank, const_cast<void*>(ptr), dims, strides, box, es, CU_TENSOR_MAP_INTERLEAVE_NONE,
       swz, promo, CU_TENSOR_MAP_FLOAT_OOB_FILL_NONE);
}

}

extern "C" void kernel_launch(void* const* d_in, const int* in_sizes, int n_in, void* d_out, int out_size) {
    const __nv_bfloat16* x = (const __nv_bfloat16*)d_in[0];
    const __nv_bfloat16* w = (const __nv_bfloat16*)d_in[1];
    const __nv_bfloat16* gamma = (const __nv_bfloat16*)d_in[2];
    const __nv_bfloat16* beta = (const __nv_bfloat16*)d_in[3];
    static EncodeTiledFn enc = nullptr;
    static int resident = 0;
    if (!enc) {
        void* fn = nullptr;
        cudaDriverEntryPointQueryResult qr;
        cudaGetDriverEntryPoint("cuTensorMapEncodeTiled", &fn, cudaEnableDefault, &qr);
        enc = (EncodeTiledFn)fn;
        cudaFuncSetAttribute(main_kernel, cudaFuncAttributeMaxDynamicSharedMemorySize, MAIN_SMEM);
        cudaFuncSetAttribute(corr_kernel, cudaFuncAttributeMaxDynamicSharedMemorySize, C_SMEM);
        int dev = 0, per_sm = 0;
        cudaGetDevice(&dev);
        cudaDeviceGetAttribute(&resident, cudaDevAttrMultiProcessorCount, dev);
        cudaOccupancyMaxActiveBlocksPerMultiprocessor(&per_sm, main_kernel, 384, MAIN_SMEM);
        resident *= per_sm;
    }
    if (resident < NCTA + 4) {
        plain_conv<<<dim3((kL + 63) / 64, 8, 2), 256>>>(x, w);
        plain_norm<<<dim3(16, 2), 256>>>(gamma, beta, (__nv_bfloat16*)d_out);
        return;
    }
    CUtensorMap tmx, tmw0, tmw1, tmcx, tmcw;
    {
        const cuuint64_t dims[3] = {1024, kRows, 2}, strides[2] = {2048, (cuuint64_t)kRows * 2048};
        const cuuint32_t box[3] = {64, 64, 1};
        encode(enc, &tmx, x, 3, dims, strides, box, CU_TENSOR_MAP_L2_PROMOTION_L2_128B);
    }
    {
        const cuuint64_t dims0[3] = {512, 16, 512}, dims1[3] = {512, 15, 512}, strides[2] = {2 * 512 * 512 * 2, 1024};
        const cuuint32_t box[3] = {64, 16, 2};
        encode(enc, &tmw0, w, 3, dims0, strides, box, CU_TENSOR_MAP_L2_PROMOTION_L2_128B);
        encode(enc, &tmw1, w + 512 * 512, 3, dims1, strides, box, CU_TENSOR_MAP_L2_PROMOTION_L2_128B);
    }
    {
        const cuuint64_t dims[4] = {512, kMO, kNT, 2}, strides[3] = {2048, kMO * 2048, (cuuint64_t)kRows * 2048};
        const cuuint32_t box[4] = {64, 1, kNT, 1};
        encode(enc, &tmcx, x, 4, dims, strides, box, CU_TENSOR_MAP_L2_PROMOTION_L2_128B);
        const cuuint64_t dimw[2] = {512, 512}, stridew[1] = {1024};
        const cuuint32_t boxw[2] = {64, 64};
        encode(enc, &tmcw, w + 30 * 512 * 512, 2, dimw, stridew, boxw, CU_TENSOR_MAP_L2_PROMOTION_L2_128B);
    }
    main_kernel<<<NCTA, 384, MAIN_SMEM>>>(tmx, tmw0, tmw1, x, w, gamma, beta, (__nv_bfloat16*)d_out);
    cudaLaunchConfig_t cfg = {};
    cudaLaunchAttribute at[1];
    cfg.gridDim = 4;
    cfg.blockDim = 256;
    cfg.dynamicSmemBytes = C_SMEM;
    at[0].id = cudaLaunchAttributeProgrammaticStreamSerialization;
    at[0].val.programmaticStreamSerializationAllowed = 1;
    cfg.attrs = at;
    cfg.numAttrs = 1;
    cudaLaunchKernelEx(&cfg, corr_kernel, tmcx, tmcw);
}
```

```cpp
#include <cuda_runtime.h>
#include <cuda_bf16.h>
#include <cuda.h>
#include <stdint.h>

namespace {

constexpr int kL    = 7985;
constexpr int kRows = 8000;
constexpr int kMO   = 50;
constexpr int kNT   = 160;

constexpr int V0 = 7;
constexpr int NPRE = 6;
constexpr int RX = 4;
constexpr int PAUSE = 5;
constexpr int YSLEEP = 100;
constexpr int PRE1 = 4;
constexpr int TSLEEP = 200;
constexpr int MERGE = 1;
constexpr int RW = 10;

static_assert(V0 >= 7 && V0 <= 9 && RX >= 2 && RX <= 4 && RW >= V0 - 1 && RW <= 12, "rings must fit and be as deep as the look-ahead");
constexpr uint32_t HOME_MASK = 0xB;
constexpr uint32_t R_W = 64 * RX, NPAGES = (R_W + 22 * RW + 31) / 32;

__device__ __align__(1024) uint8_t g_sp[(size_t)(NPAGES + 1) * (2u << 20)];
__device__ __align__(128) unsigned g_tsel[32];
__device__ __forceinline__ uint32_t run_sel(uint32_t r, uint32_t group, uint32_t pmask) {
    return ((pmask >> (r >> 5)) ^ __popc(r & HOME_MASK) ^ group) & 1;
}
__device__ __forceinline__ uint32_t run_off(uint32_t r, uint32_t run, uint32_t group, uint32_t pmask) {
    return (r << 16) + 4096 + (run_sel(r, group, pmask) << 13) + (run << 14);
}
__device__ __forceinline__ unsigned* chunk_flag(uint8_t* sp, int done, int part, int chunk) {
    return reinterpret_cast<unsigned*>(sp + (4 + 3 * (chunk >> 5)) * 65536 + (done ? (part ? 15 : 13) : (part ? 0 : 14)) * 4096 + (chunk & 31) * 128);
}
__device__ __forceinline__ unsigned long long* part_sums(uint8_t* sp, int b, int db, uint32_t epoch) {
    return reinterpret_cast<unsigned long long*>(sp + (8 + 2 * db + ((__popc((8 + 2 * db) & HOME_MASK) ^ b) & 1)) * 65536 + 13 * 4096 + (epoch & 1) * 1024);
}
__device__ __forceinline__ unsigned* y_flag(uint8_t* sp, int b, int db) { return reinterpret_cast<unsigned*>(part_sums(sp, b, db, 0) + 512); }
__device__ __align__(256) float g_corr[16 * kNT * 64];
__device__ unsigned g_cready[4 * 32];
__device__ float g_direct[512 * 250 * 64];
__device__ unsigned long long g_dpart[2 * 512 * 64];
__device__ unsigned g_exit, g_epoch;

__device__ __forceinline__ uint32_t smem_u32(const void* p) { return (uint32_t)__cvta_generic_to_shared(p); }

__device__ __forceinline__ void mbar_init(uint32_t bar, uint32_t count) {
    asm volatile("mbarrier.init.shared::cta.b64 [%0], %1;" ::"r"(bar), "r"(count) : "memory");
}
__device__ __forceinline__ void mbar_expect_tx(uint32_t bar, uint32_t bytes) {
    asm volatile("mbarrier.arrive.expect_tx.shared::cta.b64 _, [%0], %1;" ::"r"(bar), "r"(bytes) : "memory");
}
__device__ __forceinline__ void mbar_arrive(uint32_t bar) {
    asm volatile("mbarrier.arrive.shared::cta.b64 _, [%0];" ::"r"(bar) : "memory");
}
__device__ __forceinline__ bool mbar_try(uint32_t bar, uint32_t parity) {
    uint32_t ok;
    asm volatile(
        "{\n.reg .pred p;\n"
        "mbarrier.try_wait.parity.shared::cta.b64 p, [%1], %2;\n"
        "selp.u32 %0, 1, 0, p;\n}\n"
        : "=r"(ok) : "r"(bar), "r"(parity) : "memory");
    return ok;
}
__device__ __forceinline__ bool mbar_test(uint32_t bar, uint32_t parity) {
    uint32_t ok;
    asm volatile(
        "{\n.reg .pred p;\n"
        "mbarrier.test_wait.parity.shared::cta.b64 p, [%1], %2;\n"
        "selp.u32 %0, 1, 0, p;\n}\n"
        : "=r"(ok) : "r"(bar), "r"(parity) : "memory");
    return ok;
}
__device__ __forceinline__ void mbar_wait(uint32_t bar, uint32_t parity) {
#pragma unroll 1
    for (uint32_t n = 0; n < (1u << 14); n++)
        if (mbar_try(bar, parity)) break;
}
__device__ __forceinline__ void fence_proxy_async_smem() { asm volatile("fence.proxy.async.shared::cta;" ::: "memory"); }
__device__ __forceinline__ void fence_mbar_init() { asm volatile("fence.mbarrier_init.release.cluster;" ::: "memory"); }

__device__ __forceinline__ void bulk_g2s(uint32_t dst, const void* src, uint32_t bytes, uint32_t bar) {
    asm volatile("cp.async.bulk.shared::cluster.global.mbarrier::complete_tx::bytes [%0], [%1], %2, [%3];"
                 ::"r"(dst), "l"(src), "r"(bytes), "r"(bar) : "memory");
}
__device__ __forceinline__ void tma3d_ef(uint32_t dst, const CUtensorMap* tm, int c0, int c1, int c2, uint32_t bar) {
    asm volatile("{\n.reg .b64 pol;\ncreatepolicy.fractional.L2::evict_first.b64 pol, 1.0;\n"
                 "cp.async.bulk.tensor.3d.shared::cluster.global.mbarrier::complete_tx::bytes.L2::cache_hint [%0], [%1, {%3, %4, %5}], [%2], pol;\n}"
                 ::"r"(dst), "l"(tm), "r"(bar), "r"(c0), "r"(c1), "r"(c2) : "memory");
}
__device__ __forceinline__ void tma3d(uint32_t dst, const CUtensorMap* tm, int c0, int c1, int c2, uint32_t bar) {
    asm volatile("cp.async.bulk.tensor.3d.shared::cluster.global.mbarrier::complete_tx::bytes [%0], [%1, {%3, %4, %5}], [%2];"
                 ::"r"(dst), "l"(tm), "r"(bar), "r"(c0), "r"(c1), "r"(c2) : "memory");
}
__device__ __forceinline__ void red_relaxed(unsigned* p) { asm volatile("red.relaxed.gpu.global.add.u32 [%0], 1;" ::"l"(p) : "memory"); }
__device__ __forceinline__ void named_arrive(int id, int n) { asm volatile("bar.arrive %0, %1;" ::"r"(id), "r"(n) : "memory"); }
__device__ __forceinline__ void named_bar(int id, int n) { asm volatile("bar.sync %0, %1;" ::"r"(id), "r"(n) : "memory"); }

__device__ __forceinline__ void wg_fence() { asm volatile("wgmma.fence.sync.aligned;" ::: "memory"); }
__device__ __forceinline__ void wg_commit() { asm volatile("wgmma.commit_group.sync.aligned;" ::: "memory"); }
template <int N> __device__ __forceinline__ void wg_wait() { asm volatile("wgmma.wait_group.sync.aligned %0;" ::"n"(N) : "memory"); }
template <int N> __device__ __forceinline__ void reg_fence(float (&d)[N]) {
#pragma unroll
    for (int i = 0; i < N; i++) asm volatile("" : "+f"(d[i])::"memory");
}

#define F4(a, i) "+f"(a[i]), "+f"(a[i + 1]), "+f"(a[i + 2]), "+f"(a[i + 3])
#define F8(a, i) F4(a, i), F4(a, i + 4)
#define F16(a, i) F8(a, i), F8(a, i + 8)

constexpr uint32_t HI128 = 0x40000040u;
__device__ __forceinline__ uint32_t desc_lo(uint32_t addr) { return (addr >> 4) | 0x10000u; }

#define R4(a, i) "+r"(a[i]), "+r"(a[i + 1]), "+r"(a[i + 2]), "+r"(a[i + 3])
#define R8(a, i) R4(a, i), R4(a, i + 4)
template <int N> __device__ __forceinline__ void reg_fence(uint32_t (&d)[N]) {
#pragma unroll
    for (int i = 0; i < N; i++) asm volatile("" : "+r"(d[i])::"memory");
}
__device__ __forceinline__ void tma2d(uint32_t dst, const CUtensorMap* tm, int c0, int c1, uint32_t bar) {
    asm volatile("cp.async.bulk.tensor.2d.shared::cluster.global.mbarrier::complete_tx::bytes [%0], [%1, {%3, %4}], [%2];"
                 ::"r"(dst), "l"(tm), "r"(bar), "r"(c0), "r"(c1) : "memory");
}
__device__ __forceinline__ void tma4d(uint32_t dst, const CUtensorMap* tm, int c0, int c1, int c2, int c3, uint32_t bar) {
    asm volatile("cp.async.bulk.tensor.4d.shared::cluster.global.mbarrier::complete_tx::bytes [%0], [%1, {%3, %4, %5, %6}], [%2];"
                 ::"r"(dst), "l"(tm), "r"(bar), "r"(c0), "r"(c1), "r"(c2), "r"(c3) : "memory");
}

template <int ACC>
__device__ __forceinline__ void wgmma_n64_ss(float (&d)[32], uint32_t da, uint32_t db) {
    asm volatile(
        "{\n.reg .pred p;\n.reg .b64 da, db;\nsetp.ne.b32 p, %36, 0;\nmov.b64 da, {%32, %34};\nmov.b64 db, {%33, %35};\n"
        "wgmma.mma_async.sync.aligned.m64n64k16.f32.bf16.bf16 "
        "{%0,%1,%2,%3,%4,%5,%6,%7,%8,%9,%10,%11,%12,%13,%14,%15,%16,%17,%18,%19,%20,%21,%22,%23,%24,%25,%26,%27,%28,%29,%30,%31},"
        "da, db, p, 1, 1, 0, 1;\n}\n"
        : F16(d, 0), F16(d, 16)
        : "r"(da), "r"(db), "n"(HI128), "n"(HI128), "n"(ACC));
}

__device__ __forceinline__ void wgmma_n64_sp(float (&d)[32], const uint32_t (&a)[4], uint32_t db, uint32_t meta) {
    asm volatile(
        "{\n.reg .pred p;\n.reg .b64 db;\nsetp.ne.b32 p, 0, 0;\nmov.b64 db, {%36, %38};\n"
        "wgmma.mma_async.sp.sync.aligned.m64n64k32.f32.bf16.bf16 "
        "{%0,%1,%2,%3,%4,%5,%6,%7,%8,%9,%10,%11,%12,%13,%14,%15,%16,%17,%18,%19,%20,%21,%22,%23,%24,%25,%26,%27,%28,%29,%30,%31},"
        "{%32,%33,%34,%35}, db, %37, 0, p, 1, 1, 1;\n}\n"
        : F16(d, 0), F16(d, 16)
        : "r"(a[0]), "r"(a[1]), "r"(a[2]), "r"(a[3]), "r"(db), "r"(meta), "n"(HI128));
}

template <int ACC>
__device__ __forceinline__ void wgmma_n56_ss(float (&d)[28], uint32_t da, uint32_t db) {
    asm volatile(
        "{\n.reg .pred p;\n.reg .b64 da, db;\nsetp.ne.b32 p, %31, 0;\nmov.b64 da, {%28, %30};\nmov.b64 db, {%29, %30};\n"
        "wgmma.mma_async.sync.aligned.m64n56k16.f32.f16.f16 "
        "{%0,%1,%2,%3,%4,%5,%6,%7,%8,%9,%10,%11,%12,%13,%14,%15,%16,%17,%18,%19,%20,%21,%22,%23,%24,%25,%26,%27},"
        "da, db, p, 1, 1, 1, 0;\n}\n"
        : F16(d, 0), F8(d, 16), F4(d, 24)
        : "r"(da), "r"(db), "n"(HI128), "n"(ACC));
}

template <int SA>
__device__ __forceinline__ void wgmma_n160_h(uint32_t (&d)[40], uint32_t da, uint32_t db) {
    asm volatile(
        "{\n.reg .pred p;\n.reg .b64 da, db;\nsetp.eq.b32 p, 0, 0;\nmov.b64 da, {%40, %43};\nmov.b64 db, {%41, %43};\n"
        "wgmma.mma_async.sync.aligned.m64n160k16.f16.f16.f16 "
        "{%0,%1,%2,%3,%4,%5,%6,%7,%8,%9,%10,%11,%12,%13,%14,%15,%16,%17,%18,%19,%20,%21,%22,%23,%24,%25,%26,%27,"
        "%28,%29,%30,%31,%32,%33,%34,%35,%36,%37,%38,%39},"
        "da, db, p, %42, 1, 1, 0;\n}\n"
        : R8(d, 0), R8(d, 8), R8(d, 16), R8(d, 24), R8(d, 32)
        : "r"(da), "r"(db), "n"(SA), "n"(HI128));
}
template <int SA>
__device__ __forceinline__ void wgmma_n160_hr(uint32_t (&d)[40], const uint32_t (&a)[4], uint32_t db) {
    asm volatile(
        "{\n.reg .pred p;\n.reg .b64 db;\nsetp.eq.b32 p, 0, 0;\nmov.b64 db, {%44, %46};\n"
        "wgmma.mma_async.sync.aligned.m64n160k16.f16.f16.f16 "
        "{%0,%1,%2,%3,%4,%5,%6,%7,%8,%9,%10,%11,%12,%13,%14,%15,%16,%17,%18,%19,%20,%21,%22,%23,%24,%25,%26,%27,"
        "%28,%29,%30,%31,%32,%33,%34,%35,%36,%37,%38,%39},"
        "{%40,%41,%42,%43}, db, p, %45, 1, 0;\n}\n"
        : R8(d, 0), R8(d, 8), R8(d, 16), R8(d, 24), R8(d, 32)
        : "r"(a[0]), "r"(a[1]), "r"(a[2]), "r"(a[3]), "r"(db), "n"(SA), "n"(HI128));
}
template <int SA>
__device__ __forceinline__ void wgmma_n160_f(float (&d)[80], uint32_t da, uint32_t db) {
    asm volatile(
        "{\n.reg .pred p;\n.reg .b64 da, db;\nsetp.eq.b32 p, 0, 0;\nmov.b64 da, {%80, %83};\nmov.b64 db, {%81, %83};\n"
        "wgmma.mma_async.sync.aligned.m64n160k16.f32.bf16.bf16 "
        "{%0,%1,%2,%3,%4,%5,%6,%7,%8,%9,%10,%11,%12,%13,%14,%15,%16,%17,%18,%19,%20,%21,%22,%23,%24,%25,%26,%27,"
        "%28,%29,%30,%31,%32,%33,%34,%35,%36,%37,%38,%39,%40,%41,%42,%43,%44,%45,%46,%47,%48,%49,%50,%51,%52,%53,%54,%55,"
        "%56,%57,%58,%59,%60,%61,%62,%63,%64,%65,%66,%67,%68,%69,%70,%71,%72,%73,%74,%75,%76,%77,%78,%79},"
        "da, db, p, %82, 1, 1, 0;\n}\n"
        : F16(d, 0), F16(d, 16), F16(d, 32), F16(d, 48), F16(d, 64)
        : "r"(da), "r"(db), "n"(SA), "n"(HI128));
}

__device__ __forceinline__ uint32_t pack_f16(float lo, float hi) {
    uint32_t r;
    asm("cvt.rn.f16x2.f32 %0, %1, %2;" : "=r"(r) : "f"(hi), "f"(lo));
    return r;
}
__device__ __forceinline__ uint32_t mul_bf16x2(uint32_t a, uint32_t b) {
    uint32_t r;
    asm("mul.rn.bf16x2 %0, %1, %2;" : "=r"(r) : "r"(a), "r"(b));
    return r;
}
__device__ __forceinline__ void sts128(uint32_t p, uint32_t a, uint32_t b, uint32_t c, uint32_t d) {
    asm volatile("st.shared.v4.b32 [%0], {%1,%2,%3,%4};" ::"r"(p), "r"(a), "r"(b), "r"(c), "r"(d) : "memory");
}
__device__ __forceinline__ uint32_t pack_bf16(float lo, float hi) {
    uint32_t r;
    asm("cvt.rn.bf16x2.f32 %0, %1, %2;" : "=r"(r) : "f"(hi), "f"(lo));
    return r;
}
__device__ __forceinline__ void stg128(void* p, uint32_t a, uint32_t b, uint32_t c, uint32_t d) {
    asm volatile("st.global.v4.b32 [%0], {%1,%2,%3,%4};" ::"l"(p), "r"(a), "r"(b), "r"(c), "r"(d) : "memory");
}
__device__ __forceinline__ void stmatrix_x4_t(uint32_t addr, uint32_t a, uint32_t b, uint32_t c, uint32_t d) {
    asm volatile("stmatrix.sync.aligned.m8n8.x4.trans.shared.b16 [%0], {%1,%2,%3,%4};"
                 ::"r"(addr), "r"(a), "r"(b), "r"(c), "r"(d) : "memory");
}

constexpr uint32_t cos64(int k, bool half) {
    constexpr uint16_t q[17] = {0x3F80, 0x3F7F, 0x3F7B, 0x3F75, 0x3F6D, 0x3F62, 0x3F55, 0x3F46, 0x3F35, 0x3F22, 0x3F0E, 0x3EF1, 0x3EC4, 0x3E95, 0x3E48, 0x3DC9, 0x0000};
    constexpr uint16_t h[17] = {0x3C00, 0x3BF6, 0x3BD9, 0x3BA8, 0x3B64, 0x3B0E, 0x3AA7, 0x3A2F, 0x39A8, 0x3913, 0x3872, 0x378B, 0x361F, 0x34A5, 0x323E, 0x2E46, 0x0000};
    k &= 63;
    if (k > 32) k = 64 - k;
    const uint16_t* t = half ? h : q;
    return k <= 16 ? t[k] : (t[32 - k] | 0x8000u);
}
constexpr uint32_t fwd_coef(int s, int p, int t) { return (p && s == 0) ? cos64(32 * t, false) : cos64(s * t - 16 * p, false); }
constexpr uint32_t inv_coef(int l, int phi) {
    const int s = phi >> 1, p = phi & 1;
    if (l >= kMO) return 0;
    const uint32_t c = s == 0 ? cos64(32 * l * p, true) : cos64(s * l + 16 * p, true);
    return (c & 0x7FFF) ? c - ((s == 0 ? 6 : 5) << 10) : 0;
}
struct Tables {
    uint32_t fwd[2048];
    uint32_t inv[2048];
};
constexpr Tables make_tables() {
    Tables t = {};
    for (int i = 0; i < 2048; i++) {
        const int row = i >> 5, tt = 8 * (((i >> 2) & 7) ^ (row & 7)) + 2 * (i & 3), s = 8 * (row >> 4) + (row & 7), p = (row >> 3) & 1;
        t.fwd[i] = fwd_coef(s, p, tt) | (fwd_coef(s, p, tt + 1) << 16);
        t.inv[i] = inv_coef(row, tt) | (inv_coef(row, tt + 1) << 16);
    }
    return t;
}
__device__ __align__(128) const Tables g_tab = make_tables();

constexpr int NCTA = 128;
constexpr int NST = 4;
constexpr int HEND = 56;
constexpr int XB = kNT * 128;
constexpr int OFF_W1 = 0, OFF_X = OFF_W1 + NST * 8192, OFF_W0 = OFF_X + 4 * XB, OFF_RAW = OFF_W0 + NST * 8192;
constexpr int OFF_STG = OFF_RAW + 32768;
constexpr int OFF_U0 = OFF_W0, OFF_U1 = OFF_X, OFF_C1 = OFF_W1, OFF_DIR = OFF_W1 + 8192;
constexpr int OFF_F = OFF_RAW + 65536;
constexpr int OFF_C0 = OFF_F + 8192;
constexpr int OFF_TMP = OFF_C0, OFF_BAR = OFF_C0 + 4096;
constexpr int B_FULL = 0, B_EMPTY = 8 * NST, B_TSEL = 16 * NST, B_PRE = B_TSEL + 8, B_SIG = B_PRE + 16 * V0, B_YS = B_SIG + 8 * 33,
              B_T2 = B_YS + 8 * 4, B_SUM = B_T2 + 16, B_GATE = B_SUM + 32, B_RDY = B_GATE + 8 * 32, B_PUB = B_RDY + 8 * 33, B_UNIT = B_PUB + 8,
              B_FTAB = B_UNIT + 8 * 20, B_C1 = B_FTAB + 8, B_NRM = B_C1 + 8, B_END = B_NRM + 32;
template <int O0, int O1>
__device__ __forceinline__ void bar_setup(uint32_t bars) {
#pragma unroll
    for (int o = O0; o < O1; o += 8)
        mbar_init(bars + o, o < B_EMPTY ? 2 : o < B_TSEL ? 8 : o == B_TSEL ? 2 : o < B_SIG ? 1 : o < B_YS - 8 ? 8 : o < B_GATE ? 4 : 1);
    fence_mbar_init();
    fence_proxy_async_smem();
}
constexpr int OFF_TS = OFF_BAR + B_END;
constexpr int OFF_PLAN = OFF_TS + 336;
constexpr int OFF_YT = OFF_PLAN + (V0 + 65) * 8;
constexpr int OFF_GB = (OFF_YT + 4 * kNT * 4 + 15) & ~15;
constexpr int MAIN_SMEM = OFF_GB + 2048;
static_assert(MAIN_SMEM <= 232448 && OFF_U0 + 10 * 8192 == OFF_STG + 16384, "shared memory");
constexpr int XPC = 2 * kNT;
constexpr unsigned PROBE_NEAR = 400;

__device__ __forceinline__ uint32_t raw_slot(uint32_t sbase, uint32_t v, int wg) { return sbase + OFF_RAW + ((v & 3) * 2 + wg) * 8192; }

__device__ __forceinline__ uint32_t pre_slot(uint32_t sbase, uint32_t v, int wg) {
    return v < 4 ? raw_slot(sbase, v, wg) : v < 8 ? sbase + OFF_X + (v - 4) * XB + wg * 8192 : sbase + (wg ? OFF_W1 : OFF_W0) + ((V0 + 3) % NST) * 8192;
}

template <bool DC, int I>
__device__ __forceinline__ void gemm_mma(uint32_t (&a0)[40], uint32_t (&a1)[40], uint32_t dx0, uint32_t dx1, uint32_t dw) {
    constexpr int ks = I >> 2;
    const uint32_t A0 = dw + ks * 128, A1 = A0 + 256, B0 = dx0 + ks * 2, B1 = dx1 + ks * 2;
    if ((I & 3) == 0) wgmma_n160_h<1>(a0, A0, B0);
    if ((I & 3) == 1) wgmma_n160_h<1>(a1, A1, DC ? B1 : B0);
    if ((I & 3) == 2 && !DC) wgmma_n160_h<1>(a0, A1, B1);
    if ((I & 3) == 3 && !DC) wgmma_n160_h<-1>(a1, A0, B1);
}

template <bool DC, int I0, int I1>
__device__ __forceinline__ void gemm_mmas(uint32_t (&a0)[40], uint32_t (&a1)[40], uint32_t dx0, uint32_t dx1, uint32_t dw) {
    if constexpr (I0 < I1) {
        gemm_mma<DC, I0>(a0, a1, dx0, dx1, dw);
        gemm_mmas<DC, I0 + 1, I1>(a0, a1, dx0, dx1, dw);
    }
}
static_assert(RX == 4 && RW == 10, "placement of the output spectra");
__device__ __forceinline__ uint32_t y_unit(uint32_t db, uint32_t tau, uint32_t b, uint32_t pmask) {
    const uint32_t n = (((db >> 1) & 2) + (db & 1)) * XPC + ((db >> 1) & 1) * kNT + tau, r = n / 3;
    return run_off(r + (r >= 192 && r < 278 ? (r < 214 ? 64 : -22) : 0), n % 3, b, pmask);
}
__device__ __forceinline__ int y_gate(int t) { return t ? 28 + t : 27; }
__device__ __forceinline__ int step_k(int h) { return h < HEND ? h >> 1 : 28 + (h & 3); }
__device__ __forceinline__ int step_m(int h) { return h < HEND ? h & 1 : (h >> 2) & 1; }
constexpr uint64_t x_mask() {
    uint64_t r = 2 | (3ull << 58);
    for (int v = 2; v < 58; v++)
        if ((0x73 >> (v & 7)) & 1) r |= 1ull << v;
    return r;
}
constexpr uint64_t XMASK = x_mask();
__device__ __forceinline__ int x_round(int v, int wg) {
    return v == 0 ? wg : (v < 60 && wg != (v & 1) && ((XMASK >> v) & 1)) ? 1 + __popcll(XMASK << (63 - v)) : -1;
}
__device__ __forceinline__ int w_step(int v, int wg) {
    return v == 0 ? -1 : v < 60 ? (wg == (v & 1) ? v - 1 : -1) : v < 62 ? 2 * v - 61 + wg : (v == 62 && wg == 1) ? 63 : -1;
}

__device__ __forceinline__ uint32_t plan_word(int v, int wg, int cta) {
    const int r = x_round(v, wg), h = w_step(v, wg);
    if (r < 0 && h < 0) return 0;
    const bool last = v >= 60 || (v & 1) || (v > 0 && wg == 0 && x_round(v + 1, 0) < 0);
    uint32_t off, row, gate;
    if (r >= 0) {
        const int u = r * NCTA + cta, cb = u / XPC, i = u - cb * XPC, b = i >= kNT, tau = i - b * kNT;
        row = tau & 63;
        off = (((cb % RX) * 64 + b) << 16) + ((tau >> 6) << 14) + b + 2;
        gate = cb >= RX ? 2 * (cb - RX) + 2 : 0;
    } else {
        const int ring = (h + RW - 64 % RW) % RW;
        row = 0;
        off = ((ring * 22) << 16) + (ring << 12) + 4;
        gate = h >= RW ? ((h - RW + 1) >> 1) + 1 : 0;
    }
    return (off + row * 128) | ((row & 7) << 4) | (last << 3) | ((v > 60) << 24) | (gate << 26);
}

struct Xf {
    uint32_t sbase;
    uint8_t *px, *pw;
    uint32_t cx, cw;
    uint32_t xsw;
    uint32_t g[4];
    uint32_t dw;
    uint32_t e;
    int lane;
};
__device__ __forceinline__ uint32_t plan_load(const Xf& f, uint32_t v, int wg) {
    uint32_t e;
    asm volatile("ld.shared.u32 %0, [%1];" : "=r"(e) : "r"(f.sbase + OFF_PLAN + v * 8 + wg * 4));
    return __shfl_sync(0xffffffffu, e, 0);
}
template <bool W>
__device__ __forceinline__ void unit_mma(float (&acc)[32], const Xf& f, uint32_t raw) {
    const uint32_t dB = desc_lo(raw);
    if (W) {
        wgmma_n64_sp(acc, f.g, dB, threadIdx.x & 64 ? 0xDDDDDDDDu : 0x88888888u);
    } else {
        const uint32_t dF = desc_lo(f.sbase + OFF_F);
        wgmma_n64_ss<0>(acc, dF, dB);
        wgmma_n64_ss<1>(acc, dF + 2, dB + 128);
        wgmma_n64_ss<1>(acc, dF + 4, dB + 256);
        wgmma_n64_ss<1>(acc, dF + 6, dB + 384);
    }
    wg_commit();
}
constexpr int DROP = 3;
__device__ __forceinline__ uint32_t pack_sp(float lo, float hi) {
    const uint32_t r = pack_f16(lo, hi);
    return DROP ? (r + (0x10001u << DROP >> 1)) & ~(((1u << DROP) - 1) * 0x10001u) : r;
}
__device__ __forceinline__ void st_quad(uint8_t* p, const float (&acc)[32], int j0) {
    stg128(p, pack_sp(acc[j0], acc[j0 + 1]), pack_sp(acc[j0 + 4], acc[j0 + 5]), pack_sp(acc[j0 + 8], acc[j0 + 9]),
           pack_sp(acc[j0 + 12], acc[j0 + 13]));
}
template <bool W>
__device__ __forceinline__ void unit_store(float (&acc)[32], const Xf& f, uint32_t e) {
    const uint32_t sel = ((W ? f.cw >> (8 + ((e >> 12) & 15)) : e ^ (f.cx >> (8 + ((e >> 21) & 6)))) & 1) << 13;
    const uint32_t o = (e & (W ? 0xFF0F80u : 0xFFFF80u)) + ((e ^ (W ? f.cw : f.cx)) & 0x70);
    uint8_t* const b = W ? f.pw : f.px;
    uint8_t *p0 = b + (o + sel), *p1 = b + ((o ^ 64) + sel);
    reg_fence(acc);
    if (W) {
        st_quad(p0, acc, 0);
        st_quad(p1, acc, 16);
        st_quad(p0 + 4096, acc, 2);
        st_quad(p1 + 4096, acc, 18);
    } else {
        const int d = 131072 + 8192 - 2 * (int)sel;
        st_quad(p0, acc, 0);
        st_quad(p1, acc, 2);
        st_quad(p0 + d, acc, 16);
        st_quad(p1 + d, acc, 18);
    }
}
__device__ __forceinline__ void unit_done(const Xf& f, uint32_t e, uint32_t v) {
    if (e & 8) {
        __syncwarp();
        if (f.lane == 0) mbar_arrive(f.sbase + OFF_BAR + B_SIG + 8 * ((v >> 1) + ((e >> 24) & 1)));
    }
}
__device__ __forceinline__ void step_wait(Xf& f, uint32_t v, int wg) {
    const uint32_t bars = f.sbase + OFF_BAR;
    mbar_wait(bars + B_FULL + 8 * (v % NST), (v / NST) & 1);
}

template <bool DC, int KIND>
__device__ __forceinline__ void gemm_step(uint32_t (&a0)[40], uint32_t (&a1)[40], float (&at)[32], Xf& f, uint32_t v, uint32_t xs, int wg, bool first) {
    const uint32_t bars = f.sbase + OFF_BAR, sb = desc_lo(f.sbase), xb = sb + OFF_X / 16 + xs * (XB / 16), raw = raw_slot(f.sbase, v, wg);
    const uint32_t dx0 = xb + f.xsw, dx1 = xb + (f.xsw ^ 4), dw = f.dw + (v % NST) * 512, e = f.e;
    wg_fence();
    if (KIND) unit_mma<KIND != 1>(at, f, raw);
    constexpr int N1 = KIND == 0 ? 2 : NPRE;
    gemm_mmas<DC, 0, N1>(a0, a1, dx0, dx1, dw);
    wg_commit();
    const uint32_t gate = bars + ((e >> 26) ? B_GATE - 8 + 8 * (e >> 26) : B_PUB);
    const bool open = !KIND || mbar_test(gate, 0);
    f.e = plan_load(f, v + 1, wg);
    wg_wait<1>();
    if (!open) mbar_wait(gate, 0);
    if (!KIND && !first && f.lane == 0) mbar_arrive(bars + B_EMPTY + 8 * ((v - 1) % NST));
    if (KIND) unit_store<KIND != 1>(at, f, e);
    if (KIND) unit_done(f, e, v);
    gemm_mmas<DC, N1, 7>(a0, a1, dx0, dx1, dw);
    if (KIND && !first && f.lane == 0) mbar_arrive(bars + B_EMPTY + 8 * ((v - 1) % NST));
    gemm_mma<DC, 7>(a0, a1, dx0, dx1, dw);
    wg_commit();
}
template <bool DC>
__device__ __forceinline__ void any_step(uint32_t (&a0)[40], uint32_t (&a1)[40], float (&at)[32], Xf& f, uint32_t v, uint32_t xs, int wg, bool first) {
    step_wait(f, v, wg);
    const uint32_t kind = (f.e >> 1) & 3;
    if (kind == 1) gemm_step<DC, 1>(a0, a1, at, f, v, xs, wg, first);
    else if (kind == 2) gemm_step<DC, 2>(a0, a1, at, f, v, xs, wg, first);
    else gemm_step<DC, 0>(a0, a1, at, f, v, xs, wg, first);
}
template <bool DC>
__device__ __forceinline__ void gemm_main(uint32_t (&a0)[40], uint32_t (&a1)[40], uint32_t (&b0)[40], uint32_t (&b1)[40], Xf& f, int wg) {
    float at[32];
#pragma unroll 1
    for (uint32_t k = 0; k < HEND / 2; k++) {
        any_step<DC>(a0, a1, at, f, V0 + 2 * k, k & 3, wg, k == 0);
        any_step<DC>(b0, b1, at, f, V0 + 2 * k + 1, k & 3, wg, false);
    }
    wg_wait<0>();
    if (f.lane == 0) mbar_arrive(f.sbase + OFF_BAR + B_EMPTY + 8 * ((V0 + HEND - 1) % NST));
}
__device__ __forceinline__ void w_fetch(uint32_t (&d)[4][4], const Xf& f, uint32_t v) {
    const uint32_t bars = f.sbase + OFF_BAR, lane = f.lane;
    const uint32_t wa = ((f.dw & 0xFFFF) << 4) + (v % NST) * 8192 + (lane >> 4) * 1024 + (lane & 7) * 128 +
                        (((((threadIdx.x >> 4) & 6) + ((lane >> 3) & 1)) ^ (lane & 7)) << 4);
    mbar_wait(bars + B_FULL + 8 * (v % NST), (v / NST) & 1);
#pragma unroll
    for (int i = 0; i < 4; i++)
        asm volatile("ldmatrix.sync.aligned.m8n8.x4.trans.shared.b16 {%0,%1,%2,%3}, [%4];" : "=r"(d[i][0]), "=r"(d[i][1]), "=r"(d[i][2]), "=r"(d[i][3])
                     : "r"(wa + i * 2048) : "memory");
}
__device__ __forceinline__ void store_tile(uint32_t (&a0)[40], uint32_t (&a1)[40], const uint32_t (&b0)[40], const uint32_t (&b1)[40], uint32_t (&wn)[4][4],
                                           const Xf& f, bool first, uint32_t stg, int t, int wg, uint8_t* sp, int slot, uint32_t ytab, int wsw) {
    const int w = t >> 5, lane = t & 31, m = lane >> 3, i8 = lane & 7;
    const uint32_t addr = stg + i8 * 256 + (m >> 1) * 128 + (((2 * w + (m & 1)) ^ i8 ^ wsw) << 4);
    const int row = 2 * w + (lane >> 4), phi = 2 * slot + (m & 1);
    const uint32_t src = stg + row * 256 + (m & 1) * 128 + ((i8 ^ row) << 4);
    uint8_t* dst = sp + phi * 128 + ((i8 ^ (phi & 7)) << 4);
    named_bar(2 + wg, 128);
#pragma unroll
    for (int r = 0; r < 6; r++) {
        uint32_t v[4][4], o[4];
        if (r > 0) {
#pragma unroll
            for (int i = 0; i < 4; i++) {
                asm volatile("ld.shared.u32 %0, [%1];" : "=r"(o[i]) : "r"(ytab + (32 * (r - 1) + 8 * i + row) * 4) : "memory");
                asm volatile("ld.shared.v4.b32 {%0,%1,%2,%3}, [%4];" : "=r"(v[i][0]), "=r"(v[i][1]), "=r"(v[i][2]), "=r"(v[i][3])
                             : "r"(src + ((r - 1) & 1) * 8192 + i * 2048) : "memory");
            }
        }
        if (r < 5) {
#pragma unroll
            for (int j = 4 * r; j < 4 * r + 4; j++) stmatrix_x4_t(addr + (r & 1) * 8192 + (j & 3) * 2048, a0[2 * j], a0[2 * j + 1], a1[2 * j], a1[2 * j + 1]);
#pragma unroll
            for (int j = 8 * r; j < 8 * r + 8; j++) {
                asm volatile("mov.b32 %0, %1;" : "=r"(a0[j]) : "r"(b0[j]));
                asm volatile("mov.b32 %0, %1;" : "=r"(a1[j]) : "r"(b1[j]));
            }
        } else if (first) {
            w_fetch(wn, f, V0 + HEND + 4);
        }
        if (r > 0) {
#pragma unroll
            for (int i = 0; i < 4; i++) stg128(dst + o[i], v[i][0], v[i][1], v[i][2], v[i][3]);
        }
        if (r < 5) named_bar(2 + wg, 128);
    }
}

template <bool DC>
__device__ __forceinline__ void gemm_last(uint32_t (&a0)[40], uint32_t (&a1)[40], uint32_t (&w)[2][4][4], const Xf& f, int wg, int m) {
    const uint32_t bars = f.sbase + OFF_BAR, sb = desc_lo(f.sbase), v0 = V0 + HEND + 4 * m;
    if (2 * m + wg > 0) named_bar(3 + 2 * m + wg, 256);
#pragma unroll
    for (uint32_t k = 0; k < 4; k++) {
        const uint32_t xb = sb + OFF_X / 16 + k * (XB / 16), dx0 = xb + f.xsw, dx1 = xb + (f.xsw ^ 4);
        wg_fence();
#pragma unroll
        for (int ks = 0; ks < 2; ks++) {
            wgmma_n160_hr<1>(a0, w[k & 1][ks], dx0 + 2 * ks);
            wgmma_n160_hr<1>(a1, w[k & 1][2 + ks], (DC ? dx1 : dx0) + 2 * ks);
            if (!DC) wgmma_n160_hr<1>(a0, w[k & 1][2 + ks], dx1 + 2 * ks);
            if (!DC) wgmma_n160_hr<-1>(a1, w[k & 1][ks], dx1 + 2 * ks);
        }
        wg_commit();
        if (m == 0 && f.lane == 0) mbar_arrive(bars + B_EMPTY + 8 * ((v0 + k) % NST));
        if (k == 3 && 2 * m + wg < 3) named_arrive(4 + 2 * m + wg, 256);
        if (k > 0) wg_wait<1>();
        if (k < 3) w_fetch(w[(k + 1) & 1], f, v0 + k + 1);
    }
    wg_wait<0>();
    if (m && f.lane == 0) mbar_arrive(bars + B_T2 + 8 * wg);
}

__device__ __forceinline__ float gelu_half(float hv) {
    float th;
    asm("tanh.approx.f32 %0, %1;" : "=f"(th) : "f"(hv * fmaf(hv * hv, 8.0f * 0.7978845608028654f * 0.044715f, 2.0f * 0.7978845608028654f)));
    return fmaf(hv, th, hv);
}
__device__ __noinline__ void direct_block(const __nv_bfloat16* __restrict__ x, const __nv_bfloat16* __restrict__ w,
                                          const __nv_bfloat16* __restrict__ gamma, const __nv_bfloat16* __restrict__ beta,
                                          __nv_bfloat16* __restrict__ out, float* sm, int b, int db, int part, uint32_t epoch) {
    float *xs = sm, *ws = sm + 32 * 17, *red = ws + 16 * 65;
    const int tid = threadIdx.x & 127, bar = 2 + (threadIdx.x >> 7), tx = tid & 15, ty = tid >> 4, row0 = part * 250, lim = min(250, kL - row0);
    float* h = g_direct + (size_t)((b * 8 + db) * 32 + part) * (250 * 64);
    for (int l0 = 0; l0 < lim; l0 += 32) {
        float acc[4][4] = {};
        for (int k0 = 0; k0 < 31 * 512; k0 += 16) {
            named_bar(bar, 128);
            for (int i = tid; i < 1024; i += 128) {
                if (i < 512) xs[(i >> 4) * 17 + (i & 15)] = __bfloat162float(x[((size_t)b * kRows + row0 + min(l0 + (i >> 4), lim - 1)) * 1024 + k0 + (i & 15)]);
                ws[(i >> 6) * 65 + (i & 63)] = __bfloat162float(w[(size_t)(k0 + (i >> 6)) * 512 + 64 * db + (i & 63)]);
            }
            named_bar(bar, 128);
            for (int k = 0; k < 16; k++)
#pragma unroll
                for (int i = 0; i < 4; i++)
#pragma unroll
                    for (int j = 0; j < 4; j++) acc[i][j] = fmaf(xs[(ty * 4 + i) * 17 + k], ws[k * 65 + tx * 4 + j], acc[i][j]);
        }
#pragma unroll
        for (int i = 0; i < 4; i++)
#pragma unroll
            for (int j = 0; j < 4; j++)
                if (l0 + ty * 4 + i < lim) h[(l0 + ty * 4 + i) * 64 + tx * 4 + j] = acc[i][j];
    }
    const int c = tid & 63;
    float mean = 0.f, var = 0.f;
    for (int r = 0; r < 2; r++) {
        named_bar(bar, 128);
        float s = 0.f;
        for (int l = tid >> 6; l < lim; l += 2) {
            const float v = h[l * 64 + c] - mean;
            s += r ? v * v : v;
        }
        red[tid] = s;
        named_bar(bar, 128);
        unsigned long long* p = g_dpart + ((r * 16 + b * 8 + db) * 32) * 64 + c;
        if (tid < 64)
            asm volatile("st.relaxed.gpu.global.v2.b32 [%0], {%1, %2};" ::"l"(p + part * 64), "r"(__float_as_uint(red[c] + red[64 + c])), "r"(epoch) : "memory");
        s = 0.f;
        for (int k = 0; k < 32; k++) {
            unsigned long long v = 0;
#pragma unroll 1
            for (uint32_t n = 0; n < (1u << 19); n++) {
                asm volatile("ld.relaxed.gpu.global.u64 %0, [%1];" : "=l"(v) : "l"(p + k * 64) : "memory");
                if ((uint32_t)(v >> 32) == epoch) break;
                __nanosleep(200);
            }
            s += __uint_as_float((uint32_t)v);
        }
        (r ? var : mean) = s * (1.0f / kL);
    }
    const float a = __bfloat162float(gamma[64 * db + c]) / sqrtf(var + 1e-5f), be = __bfloat162float(beta[64 * db + c]);
    for (int l = tid >> 6; l < lim; l += 2)
        out[((size_t)b * kL + row0 + l) * 512 + 64 * db + c] = __float2bfloat16(gelu_half(0.5f * fmaf(h[l * 64 + c] - mean, a, be)));
    named_bar(bar, 128);
}

__device__ __forceinline__ int tail_block(uint32_t gr, int t) { return 4 * (t >> 1) + ((gr >> 4) & 2) + (t & 1); }
__device__ __forceinline__ void tail_poll(uint8_t* sp, uint32_t gr, int t) {
#pragma unroll 1
    for (uint32_t n = 0; n < (1u << 15); n++) {
        unsigned v;
        asm volatile("ld.relaxed.gpu.global.u32 %0, [%1];" : "=r"(v) : "l"(y_flag(sp, gr >> 6, tail_block(gr, t))) : "memory");
        if (v >= 32) break;
        __nanosleep(YSLEEP);
    }
    asm volatile("fence.acquire.gpu;" ::: "memory");
    asm volatile("fence.proxy.async.global;" ::: "memory");
}
__device__ __forceinline__ void tail_loads(uint32_t sbase, const uint8_t* sp, uint32_t gr, uint32_t pmask, int u0, int u1, int lane) {
    if (lane >= u0 && lane < u1) {
        const uint32_t bar = sbase + OFF_BAR + B_UNIT + 8 * lane;
        mbar_expect_tx(bar, 8192);
        bulk_g2s(sbase + (lane < 10 ? OFF_U0 : OFF_U1 - 81920) + lane * 8192, sp + y_unit(tail_block(gr, lane / 5), (gr & 31) * 5 + lane % 5, gr >> 6, pmask), 8192, bar);
    }
    __syncwarp();
}
__device__ __forceinline__ const float* corr_src(uint32_t gr, int t) { return &g_corr[(((gr >> 6) * 8 + tail_block(gr, t)) * kNT + (gr & 31) * 5) * 64]; }
__device__ __forceinline__ void corr_load(uint32_t sbase, uint32_t gr, int t, uint32_t bar) {
    bulk_g2s(sbase + (t < 2 ? OFF_C0 : OFF_C1) + (t & 1) * 1280, corr_src(gr, t), 1280, bar);
}
__device__ __forceinline__ void tail_phase(uint32_t sbase, uint8_t* smem, uint8_t* sp, int wg, uint32_t gr, float sx, float sw, const __nv_bfloat16* __restrict__ x,
                                           const __nv_bfloat16* __restrict__ wt, const __nv_bfloat16* __restrict__ gamma,
                                           const __nv_bfloat16* __restrict__ beta, __nv_bfloat16* __restrict__ out) {
    const uint32_t* ts = reinterpret_cast<const uint32_t*>(smem + OFF_TS);
    const int tid = threadIdx.x, w = (tid >> 5) & 3, lane = tid & 31, g = lane >> 2, q = lane & 3;
    const int b = gr >> 6, part = gr & 31;
#pragma unroll 1
    for (int rd = 0; rd < 3; rd++) {
        if (rd < 2) {
            float acc[28], acc2[28], s[8] = {0.f, 0.f, 0.f, 0.f, 0.f, 0.f, 0.f, 0.f};
            const float swq = q == 0 ? sw : 0.f;
            const int t = 2 * rd + wg;
            const uint32_t ub = sbase + (t < 2 ? OFF_U0 : OFF_U1) + (t & 1) * 40960, ubar = sbase + OFF_BAR + B_UNIT + 40 * t;
            const float* c1 = reinterpret_cast<const float*>(smem + (t < 2 ? OFF_C0 : OFF_C1) + (t & 1) * 1280) + 16 * w + g;
            const uint32_t ka = ub + (lane >> 4) * 1024 + (lane & 7) * 128 + (((2 * w + ((lane >> 3) & 1)) ^ (lane & 7)) << 4);
            auto inverse = [&](float (&d)[28], int u) {
                const uint32_t dA = desc_lo(ub + u * 8192), dB = desc_lo(sbase + OFF_F);
                wg_fence();
                wgmma_n56_ss<0>(d, dA, dB);
                wgmma_n56_ss<1>(d, dA + 128, dB + 2);
                wgmma_n56_ss<1>(d, dA + 256, dB + 4);
                wgmma_n56_ss<1>(d, dA + 384, dB + 6);
                wg_commit();
            };
            auto keep = [&](float (&d)[28], int u, int un) {
                const bool ok = mbar_try(ubar + 8 * un, 0);
                reg_fence(d);
                d[25] = fmaf(c1[u * 64] * sx, swq, d[25]);
                d[27] = fmaf(c1[u * 64 + 8] * sx, swq, d[27]);
                if (part == 31 && u == 4) {
                    if (q >= 2) d[16] = d[18] = 0.f;
                    if (q >= 1) d[17] = d[19] = 0.f;
#pragma unroll
                    for (int i = 20; i < 28; i++) d[i] = 0.f;
                }
                const uint32_t a = ka + u * 8192;
#pragma unroll
                for (int j = 0; j < 6; j += 2)
                    stmatrix_x4_t(a + j * 1024, pack_f16(d[4 * j], d[4 * j + 1]), pack_f16(d[4 * j + 2], d[4 * j + 3]),
                                  pack_f16(d[4 * j + 4], d[4 * j + 5]), pack_f16(d[4 * j + 6], d[4 * j + 7]));
                asm volatile("stmatrix.sync.aligned.m8n8.x2.trans.shared.b16 [%0], {%1,%2};"
                             ::"r"(a + 6 * 1024), "r"(pack_f16(d[24], d[25])), "r"(pack_f16(d[26], d[27])) : "memory");
#pragma unroll
                for (int i = 0; i < 28; i++) {
                    s[i & 3] += d[i];
                    s[4 + (i & 3)] = fmaf(d[i], d[i], s[4 + (i & 3)]);
                }
#pragma unroll
                for (int i = 0; i < 8; i++) asm volatile("" : "+f"(s[i]));
                if (!ok) mbar_wait(ubar + 8 * un, 0);
                wg_wait<0>();
            };
            if (t >= 2) mbar_wait(sbase + OFF_BAR + B_C1, 0);
            mbar_wait(ubar, 0);
            inverse(acc, 0);
            mbar_wait(ubar + 8, 0);
            wg_wait<0>();
#pragma unroll 1
            for (int u = 0;; u += 2) {
                inverse(acc2, min(u + 1, 4));
                keep(acc, u, min(u + 2, 4));
                if (u == 4) break;
                inverse(acc, u + 2);
                keep(acc2, u + 1, min(u + 3, 4));
            }
#pragma unroll
            for (int i = 0; i < 4; i++) s[i] = s[2 * i] + s[2 * i + 1];
#pragma unroll
            for (int i = 0; i < 2; i++) s[i] = (q & 2 ? s[2 + i] : s[i]) + __shfl_xor_sync(0xffffffffu, q & 2 ? s[i] : s[2 + i], 2);
            const float mine = (q & 1 ? s[1] : s[0]) + __shfl_xor_sync(0xffffffffu, q & 1 ? s[0] : s[1], 1);
            asm volatile("red.relaxed.gpu.global.add.u64 [%0], %1;"
                         ::"l"(part_sums(sp, b, tail_block(gr, t), ts[76]) + 2 * (16 * w + 8 * (q & 1) + g) + (q >> 1)),
                         "l"(fabsf(mine) < 0x1p25f ? __float2ll_rn(mine * 0x1p21f) * 4096 + 1 : 65ll) : "memory");
            __syncwarp();
            if (lane == 0) mbar_arrive(sbase + OFF_BAR + B_SUM + 8 * t);
            if (rd == 0) continue;
        }
        const int t = 2 * rd - 2 + wg, db = tail_block(gr, t);
#pragma unroll 1
        for (uint32_t n = 0; n < (1u << 20); n++)
            if (mbar_try(sbase + OFF_BAR + B_NRM + 8 * t, 0)) break;
        if (reinterpret_cast<const volatile uint32_t*>(ts)[77 + t]) {
            direct_block(x, wt, gamma, beta, out, reinterpret_cast<float*>(smem + OFF_DIR + wg * 8192), b, db, part, ts[76]);
            continue;
        }
        const int jh = g & 1, r0 = 4 * w;
        const int lim = min(250, kL - part * 250) - r0 - (g >> 1);
        float na[8], nb[8];
#pragma unroll
        for (int i = 0; i < 8; i += 2) {
            const float4 v = reinterpret_cast<const float4*>(smem + OFF_GB)[32 * t + 16 * jh + 2 * i + q];
            na[i] = v.x; nb[i] = v.y; na[i + 1] = v.z; nb[i + 1] = v.w;
        }
        __nv_bfloat16* o = out + ((size_t)b * kL + part * 250 + r0 + (g >> 1)) * 512 + 64 * db + 32 * jh + 8 * q;
        int l = r0 + ((lane >> 1) & 3);
        uint32_t ra = sbase + (t < 2 ? OFF_U0 : OFF_U1) + (t & 1) * 40960 + l * 128;
        const int cc = 4 * (lane & 1) + (lane >> 3);
        auto fetch = [&](uint32_t (&r)[4]) {
            asm volatile("ldmatrix.sync.aligned.m8n8.x4.shared.b16 {%0,%1,%2,%3}, [%4];"
                         : "=r"(r[0]), "=r"(r[1]), "=r"(r[2]), "=r"(r[3]) : "r"(ra + (((cc ^ l) & 7) << 4)) : "memory");
            const bool wrap = l >= kMO - 16;
            l += wrap ? 16 - kMO : 16;
            ra += wrap ? 2048 + 8192 - kMO * 128 : 2048;
        };
        auto gelu8 = [&](const uint32_t (&r)[4], uint32_t (&p)[4]) {
#pragma unroll
            for (int i = 0; i < 4; i++) {
                float lo, hi;
                asm("{\n.reg .b16 a, b;\nmov.b32 {a, b}, %2;\ncvt.f32.f16 %0, a;\ncvt.f32.f16 %1, b;\n}" : "=f"(lo), "=f"(hi) : "r"(r[i]));
                p[i] = pack_bf16(gelu_half(fmaf(lo, na[2 * i], nb[2 * i])), gelu_half(fmaf(hi, na[2 * i + 1], nb[2 * i + 1])));
            }
        };
        uint32_t r[2][4], rn[2][4];
        fetch(r[0]);
        fetch(r[1]);
#pragma unroll 1
        for (int i = 0; i < 256; i += 32) {
            fetch(rn[0]);
            fetch(rn[1]);
            uint32_t p0[4], p1[4];
            gelu8(r[0], p0);
            gelu8(r[1], p1);
            if (i < lim) stg128(o, p0[0], p0[1], p0[2], p0[3]);
            if (i + 16 < lim) stg128(o + 16 * 512, p1[0], p1[1], p1[2], p1[3]);
            o += 32 * 512;
#pragma unroll
            for (int k = 0; k < 4; k++) { r[0][k] = rn[0][k]; r[1][k] = rn[1][k]; }
        }
    }
}
__device__ __forceinline__ void channel_scales(uint32_t sbase, uint8_t* smem, uint8_t* sp, int lane) {
    volatile uint32_t* ts = reinterpret_cast<volatile uint32_t*>(smem + OFF_TS);
    const uint32_t gr = ts[64], bars = sbase + OFF_BAR;
#pragma unroll 1
    for (int t = 0; t < 4; t++) {
#pragma unroll 1
        for (uint32_t n = 0; n < (1u << 20); n++)
            if (mbar_try(bars + B_SUM + 8 * t, 0)) break;
        long long s[4];
#pragma unroll 1
        for (uint32_t n = 0; n < (1u << 19); n++) {
            const unsigned long long* p = part_sums(sp, gr >> 6, tail_block(gr, t), ts[76]) + 4 * lane;
#pragma unroll
            for (int i = 0; i < 4; i++) asm volatile("ld.relaxed.gpu.global.u64 %0, [%1];" : "=l"(s[i]) : "l"(p + i) : "memory");
            if (__all_sync(0xffffffffu, s[0] & s[1] & s[2] & s[3] & 32)) break;
        }
        const float sx = __uint_as_float(ts[74]), sw = __uint_as_float(ts[75]);
        bool bad = false;
#pragma unroll
        for (int i = 0; i < 2; i++) {
            const float mean = (float)(s[2 * i] >> 12) * (0x1p-21f / kL), sq = (float)(s[2 * i + 1] >> 12) * (0x1p-21f / kL);
            float2* gb = reinterpret_cast<float2*>(smem + OFF_GB) + 64 * t + 2 * lane + i;
            const float den = fmaxf(sq - mean * mean, 0.f) + 1e-5f * sx * sw * sx * sw, a = gb->x * rsqrtf(den);
            *gb = make_float2(0.5f * a, 0.5f * (gb->y - mean * a));
            bad |= ((s[2 * i] | s[2 * i + 1]) & 0xFC0) || !(den >= 0x1p-22f);
        }
        bad = __any_sync(0xffffffffu, bad);
        if (lane == 0) ts[77 + t] = bad;
        __syncwarp();
        if (lane == 0) mbar_arrive(bars + B_NRM + 8 * t);
    }
}

__device__ __forceinline__ void publish_tiles(uint8_t* sp, uint32_t bars, int cta, int wg) {
#pragma unroll 1
    for (int m = 0; m < 2; m++) {
        mbar_wait(bars + B_YS + 8 * (2 * m + wg), 0);
        asm volatile("fence.acq_rel.gpu;" ::: "memory");
        red_relaxed(y_flag(sp, (cta >> 1) & 1, 4 * m + 2 * (cta & 1) + wg));
    }
}

__global__ void __launch_bounds__(384, 1)
main_kernel(const __grid_constant__ CUtensorMap tmx, const __grid_constant__ CUtensorMap tmw0, const __grid_constant__ CUtensorMap tmw1,
            const __nv_bfloat16* __restrict__ x, const __nv_bfloat16* __restrict__ wt, const __nv_bfloat16* __restrict__ gamma,
            const __nv_bfloat16* __restrict__ beta, __nv_bfloat16* __restrict__ out) {
    extern __shared__ __align__(1024) uint8_t smem_raw[];
    const uint32_t sbase = smem_u32(smem_raw) & ~1023u;
    const uint32_t bars = sbase + OFF_BAR;
    const int tid = threadIdx.x, wg = __shfl_sync(0xffffffffu, tid >> 7, 0), lane = tid & 31;
    const int cta = blockIdx.x;
    volatile uint32_t* ts = reinterpret_cast<volatile uint32_t*>(smem_raw + OFF_TS);
    uint8_t* const sp = reinterpret_cast<uint8_t*>((reinterpret_cast<uintptr_t>(g_sp) + (2u << 20) - 1) & ~(uintptr_t)((2u << 20) - 1));
    const bool probing = (cta & 3) == 0 && lane == 0 && tid < 128 && (tid >= 64 || cta < 4 * NPAGES);
    unsigned* pw = reinterpret_cast<unsigned*>(sp + (tid < 64 ? ((cta >> 2) << 21) + ((tid & 32) ? 15 : 13) * 4096
                                                              : ((tid & 32) ? 0 : 14) * 4096 + (cta >> 2) * 128));
    unsigned pv = 0;
    if (probing) {
        stg128(pw, 0, 0, 0, 0);
        stg128(pw + 4, 0, 0, 0, 0);
        asm volatile("atom.relaxed.gpu.global.exch.b32 %0, [%1], %2;" : "=r"(pv) : "l"(pw), "r"(7) : "memory");
    }
    if (tid == 320) bar_setup<0, B_SIG>(bars);
    if (tid >= 256 && tid < 262) ts[68 + tid - 256] = tid < 260 ? 0xffffu : 0;
    if (tid == 383) asm volatile("griddepcontrol.launch_dependents;");
    __syncthreads();

    if (wg == 2) {
        asm volatile("setmaxnreg.dec.sync.aligned.u32 40;");
        const int role = (tid >> 5) & 3;
        if (role == 3) {
            unsigned v = 0;
#pragma unroll 1
            for (uint32_t n = 0; n < (1u << 15); n++) {
                asm volatile("ld.relaxed.gpu.global.u32 %0, [%1];" : "=r"(v) : "l"(&g_tsel[lane]) : "memory");
                if (__all_sync(0xffffffffu, v & 16)) break;
                __nanosleep(TSLEEP);
            }
            const uint32_t m1 = __ballot_sync(0xffffffffu, v & 8), below = (1u << lane) - 1;
            const int rank = (v & 8) ? 32 - __popc(m1) + __popc(m1 & below) : __popc(~m1 & below);
            ts[lane] = rank;
            ts[32 + rank] = lane;
            const uint32_t p0 = __ballot_sync(0xffffffffu, v & 1);
            if (lane == 0) ts[66] = p0;
            if (lane == (cta >> 2)) ts[64] = rank * 4 + (cta & 3);
            const int part = (m1 >> (cta >> 2)) & 1;
            __syncwarp();
            if (lane == 0) mbar_arrive(bars + B_TSEL);
            mbar_wait(bars + B_TSEL, 0);
            mbar_wait(bars + B_PUB, 0);
            int gc = 0;
            const int gend = lane == 0 ? 33 : lane == 1 ? 32 : 0;
#pragma unroll 1
            for (uint32_t n = 0; n < (1u << 16) && __any_sync(0xffffffffu, gc < gend); n++) {
                asm volatile("ld.relaxed.gpu.global.u32 %0, [%1];" : "=r"(v) : "l"(chunk_flag(sp, lane == 1, part, min(gc, 32 - (lane & 1)))) : "memory");
                if (gc < gend && v >= NCTA) {
                    asm volatile("fence.acquire.gpu;" ::: "memory");
                    mbar_arrive(bars + (lane == 0 ? B_RDY : B_GATE) + 8 * gc);
                    gc++;
                }
            }
            if (lane == 0) publish_tiles(sp, bars, cta, 1);
        } else if (role == 0) {
            const int b = (cta >> 1) & 1, dq = cta & 1;
            for (int v = 0; v < V0; v++) {
                mbar_wait(bars + B_EMPTY + 8 * (v % NST), ((v / NST) & 1) ^ 1);
                if (lane == 0) {
                    mbar_arrive(bars + B_FULL + 8 * (v % NST));
                    mbar_arrive(bars + B_FULL + 8 * (v % NST));
                }
            }
            mbar_wait(bars + B_TSEL, 0);
            const uint32_t gr = ts[64], grp = gr >> 6, idx = (gr >> 2) & 15, pmask = ts[66];
            const uint32_t n0 = idx * 4 + 2 * dq + ((lane & 1) ^ 1), r0 = lane < 3 ? idx * 4 + b : R_W + n0 / 3;
            const uint32_t base = (r0 << 16) + 4096 + ((lane < 3 ? lane : n0 % 3) << 14), step = (lane < 3 ? 64 : 22) << 16;
            uint32_t sels = 0;
            for (int i = 0; i < 12; i++) sels |= run_sel(r0 + i * (step >> 16), grp, pmask) << i;
            int ld = 0;
            const uint32_t bytes = lane == 2 ? XB - 16384 : 8192;
#pragma unroll 1
            for (int h = 0; h < 64; h++) {
                const int s = step_k(h), st = (h + V0) % NST;
                const bool newx = h < HEND ? !(h & 1) : h < HEND + 4;
                const uint32_t fb = bars + B_FULL + 8 * st;
                const uint32_t k = lane < 3 ? (s >> 1) % RX : (h + RW - 64 % RW) % RW, half = lane < 3 ? s & 1 : 0;
                const uint8_t* gsrc = sp + (base + k * step + (half << 17) + ((((sels >> k) ^ half) & 1) << 13));
                const uint32_t dst = sbase + (lane < 3 ? OFF_X + (s & 3) * XB + lane * 8192 : st * 8192 + (lane == 3 ? OFF_W0 : OFF_W1));
                auto landed = [&]() {
                    if (ld < h && mbar_test(bars + B_FULL + 8 * ((ld + V0) % NST), ((ld + V0) / NST) & 1)) {
                        if (!(ld & 1) && lane < 2) red_relaxed(chunk_flag(sp, 1, lane, ld >> 1));
                        ld++;
                    }
                };
#pragma unroll 1
                for (uint32_t n = 0; n < (1u << 19) && !mbar_test(bars + B_EMPTY + 8 * st, (((h + V0) / NST) & 1) ^ 1); n++) landed();
#pragma unroll 1
                for (uint32_t n = 0; n < (1u << 19) && ld <= h - NST; n++) landed();
                if (lane == 0) mbar_expect_tx(fb, newx ? 16384 + XB : 16384);
                if ((h & 1) || h == 0) {
#pragma unroll 1
                    for (uint32_t n = 0; n < (1u << 19) && !mbar_test(bars + B_RDY + 8 * ((h + 1) >> 1), 0); n++) landed();
                    asm volatile("fence.proxy.async.global;" ::: "memory");
                }
                __syncwarp();
                if (lane < 3 ? newx : lane < 5) bulk_g2s(dst, gsrc, bytes, fb);
            }
#pragma unroll 1
            for (; ld < 63; ld++) {
                mbar_wait(bars + B_FULL + 8 * ((ld + V0) % NST), ((ld + V0) / NST) & 1);
                if (!(ld & 1) && lane < 2) red_relaxed(chunk_flag(sp, 1, lane, ld >> 1));
            }
            tail_poll(sp, gr, 0);
            mbar_wait(bars + B_T2, 0);
            tail_loads(sbase, sp, gr, pmask, 0, 5, lane);
            tail_poll(sp, gr, 1);
            tail_loads(sbase, sp, gr, pmask, 5, 8, lane);
            mbar_wait(bars + B_YS + 16, 0);
            tail_loads(sbase, sp, gr, pmask, 8, 10, lane);
            mbar_wait(bars + B_T2 + 8, 0);
            if (lane == 0) {
                mbar_expect_tx(bars + B_C1, 2560);
                corr_load(sbase, gr, 2, bars + B_C1);
                corr_load(sbase, gr, 3, bars + B_C1);
            }
            tail_poll(sp, gr, 2);
            tail_loads(sbase, sp, gr, pmask, 10, 15, lane);
            tail_poll(sp, gr, 3);
            tail_loads(sbase, sp, gr, pmask, 15, 20, lane);
            mbar_wait(bars + B_GATE + 8 * 31, 0);
            unsigned exits = 0;
            if (lane == 0) exits = atomicAdd(&g_exit, 1);
            if (__shfl_sync(0xffffffffu, exits, 0) == NCTA - 1) {
                for (int i = 0; i < 4; i++) *chunk_flag(sp, i >> 1, i & 1, lane) = 0;
                if (lane < 2) *chunk_flag(sp, 0, lane, 32) = 0;
                g_tsel[lane] = 0;
                if (lane < 16) *y_flag(sp, lane >> 3, lane & 7) = 0;
                if (lane == 0) { g_exit = 0; g_epoch = ts[76]; }
            }
        } else if (role == 1) {
            auto raw_load = [&](int r, int h, uint32_t gr, uint32_t dst, uint32_t bar) {
                if (r >= 0) {
                    const int u = r * NCTA + cta, i = u % XPC, b = i >= kNT;
                    tma3d(dst, &tmx, u / XPC * 64, (i - b * kNT) * kMO, b, bar);
                } else if (h >= 0) {
                    const int c = 32 * step_k(h) + ((gr >> 1) & 30);
                    tma3d_ef(dst, c < 512 ? &tmw0 : &tmw1, step_m(h) * 256 + (gr & 3) * 64, c & 511, 0, bar);
                }
            };
            uint32_t gr;
            {
                const int v = lane >> 1, r = v < V0 ? x_round(v, lane & 1) : -1, h = v < V0 ? w_step(v, lane & 1) : -1;
                const uint32_t dst = pre_slot(sbase, v, lane & 1), bar = bars + B_PRE + 8 * lane;
                if (r >= 0 || h >= 0) mbar_expect_tx(bar, r >= 0 ? 8192 : 4096);
                if (v < PRE1) raw_load(r, -1, 0, dst, bar);
                mbar_wait(bars + B_TSEL, 0);
                gr = ts[64];
                raw_load(-1, h, gr, dst, bar);
                if (v >= PRE1) raw_load(r, -1, 0, dst, bar);
                __syncwarp();
            }
            mbar_wait(bars + B_PUB, 0);
#pragma unroll 1
            for (int v = V0; v < V0 + 64; v++) {
                mbar_wait(bars + B_EMPTY + 8 * (v % NST), ((v / NST) & 1) ^ 1);
                __syncwarp();
                const int r = lane < 2 ? x_round(v, lane) : -1, h = lane < 2 ? w_step(v, lane) : -1;
                const uint32_t fb = bars + B_FULL + 8 * (v % NST);
                const uint32_t bytes = __reduce_add_sync(0xffffffffu, r >= 0 ? 8192 : h >= 0 ? 4096 : 0);
                if (lane == 0) mbar_expect_tx(fb, bytes);
                __syncwarp();
                raw_load(r, h, gr, raw_slot(sbase, v, lane), fb);
                if (v >= 20 && v < 40) {
                    const int t = (v - 20) / 5, i = (v - 20) % 5 * 32 + lane, db = 4 * (t >> 1) + 2 * (cta & 1) + (t & 1);
                    ts[(OFF_YT - OFF_TS) / 4 + t * kNT + i] = y_unit(db, i, (cta >> 1) & 1, ts[66]);
                }
                if (v == 66 && lane == 0) {
#pragma unroll 1
                    for (uint32_t n = 0; n < (1u << 15); n++) {
                        unsigned c0, c1;
                        asm volatile("ld.relaxed.gpu.global.u32 %0, [%1];" : "=r"(c0) : "l"(&g_cready[(gr >> 6) * 64]) : "memory");
                        asm volatile("ld.relaxed.gpu.global.u32 %0, [%1];" : "=r"(c1) : "l"(&g_cready[(gr >> 6) * 64 + 32]) : "memory");
                        if (c0 == ts[76] && c1 == ts[76]) break;
                        __nanosleep(500);
                    }
                    asm volatile("fence.acquire.gpu;" ::: "memory");
                    asm volatile("fence.proxy.async.global;" ::: "memory");
                    mbar_expect_tx(bars + B_FTAB, 8192 + 2560);
                    bulk_g2s(sbase + OFF_F, g_tab.inv, 8192, bars + B_FTAB);
                    for (int t = 0; t < 2; t++) {
                        corr_load(sbase, gr, t, bars + B_FTAB);
                        asm volatile("cp.async.bulk.prefetch.L2.global [%0], 1280;" ::"l"(corr_src(gr, 2 + t)) : "memory");
                    }
                }
            }
            channel_scales(sbase, smem_raw, sp, lane);
        } else {
            uint32_t epoch;
            if (lane == 0) {
                bar_setup<B_SIG, B_END>(bars);
                mbar_arrive(bars + B_TSEL);
            }
            asm volatile("ld.relaxed.gpu.global.u32 %0, [%1];" : "=r"(epoch) : "l"(&g_epoch) : "memory");
            mbar_wait(bars + B_TSEL, 0);
            const uint32_t gr = ts[64];
#pragma unroll
            for (int i = lane; i < 256; i += 32) {
                const int d = 64 * tail_block(gr, i >> 6) + (i & 33) + 8 * ((i >> 1) & 3) + 2 * ((i >> 3) & 3);
                ts[(OFF_GB - OFF_TS) / 4 + 2 * i] = (uint32_t)__bfloat16_as_ushort(gamma[d]) << 16;
                ts[(OFF_GB - OFF_TS) / 4 + 2 * i + 1] = (uint32_t)__bfloat16_as_ushort(beta[d]) << 16;
            }
            if (lane == 0) ts[76] = epoch + 1;
            if (cta < 32) stg128(part_sums(sp, cta >> 4, (cta >> 1) & 7, epoch) + (cta & 1) * 64 + 2 * lane, 0, 0, 0, 0);
            __syncwarp();
            if (lane) return;
#pragma unroll 1
            for (int gc = 0; gc < 33;) {
                mbar_wait(bars + B_SIG + 8 * gc, 0);
                if (gc < MERGE) mbar_wait(bars + B_SIG + 8 * MERGE, 0);
                int ge = gc + 1;
                while (ge < 33 && mbar_test(bars + B_SIG + 8 * ge, 0)) ge++;
                asm volatile("fence.acq_rel.gpu;" ::: "memory");
                for (; gc < ge; gc++) {
                    red_relaxed(chunk_flag(sp, 0, 0, gc));
                    red_relaxed(chunk_flag(sp, 0, 1, gc));
                    if (gc == 0) mbar_arrive(bars + B_PUB);
                }
            }
            publish_tiles(sp, bars, cta, 0);
        }
    } else {
        asm volatile("setmaxnreg.inc.sync.aligned.u32 232;");
        uint4 fw[2];
#pragma unroll
        for (int j = 0; j < 2; j++) fw[j] = __ldg(reinterpret_cast<const uint4*>(g_tab.fwd) + tid + 256 * j);
        if (wg == 1) {
            uint4 sm[8];
#pragma unroll
            for (int j = 0; j < 4; j++) {
                const int r = 2 * j + ((tid >> 6) & 1);
                sm[j] = __ldg(reinterpret_cast<const uint4*>(x) + ((r >> 2) * kRows + 1000 + 2000 * (r & 3)) * 128 + (((j + r) & 1) << 6) + (tid & 63));
                sm[4 + j] = __ldg(reinterpret_cast<const uint4*>(wt) + (4 * r * 512 + 67 * r + 7) * 64 + (tid & 63));
            }
#pragma unroll
            for (int k = 0; k < 2; k++) {
                uint32_t mx = 0;
#pragma unroll
                for (int j = 4 * k; j < 4 * k + 4; j++)
                    mx = __vmaxu2(__vmaxu2(mx, __vmaxu2(sm[j].x & 0x7FFF7FFFu, sm[j].y & 0x7FFF7FFFu)), __vmaxu2(sm[j].z & 0x7FFF7FFFu, sm[j].w & 0x7FFF7FFFu));
                mx = __reduce_max_sync(0xffffffffu, max(mx & 0xFFFFu, mx >> 16));
                if (lane == 0) atomicMax(const_cast<uint32_t*>(ts) + 72 + k, mx);
            }
        }
        if ((cta & 3) == 0) {
            if (probing) {
                const int w = tid >> 5;
                unsigned best = 0xffffu;
#pragma unroll 1
                for (int r = 0; r < 6; r++) {
                    unsigned t0, t1;
                    asm volatile("{\n.reg .pred p;\nsetp.eq.u32 p, %1, 0xffffffff;\nmov.u32 %0, 0;\n@!p mov.u32 %0, %%clock;\n}"
                                 : "=r"(t0) : "r"(pv) : "memory");
                    asm volatile("atom.relaxed.gpu.global.exch.b32 %0, [%1], %2;" : "=r"(pv) : "l"(pw), "r"(r) : "memory");
                    asm volatile("{\n.reg .pred p;\nsetp.eq.u32 p, %1, 0xffffffff;\nmov.u32 %0, 0;\n@!p mov.u32 %0, %%clock;\n}"
                                 : "=r"(t1) : "r"(pv) : "memory");
                    ts[68 + w] = best = min(best, t1 - t0);
                    const unsigned other = ts[68 + (w ^ 1)];
                    if (min(best, other) < PROBE_NEAR && max(best, other) > PROBE_NEAR) break;
                }
            }
            if (wg == 0) {
                named_bar(2, 128);
                if (tid == 0) {
                    const uint32_t part = ts[71] < ts[70];
                    const uint32_t v = 16 | (part << 3) | ((ts[69] < ts[68]) ^ part);
                    asm volatile("st.relaxed.gpu.global.u32 [%0], %1;" ::"l"(&g_tsel[cta >> 2]), "r"(v) : "memory");
                }
            }
        }
        if (tid < 2 * (V0 + 65)) ts[(OFF_PLAN - OFF_TS) / 4 + tid] = plan_word(tid >> 1, tid & 1, cta);
        {
            named_bar(1, 256);
            const uint32_t ex = min(max(251 - (int)(ts[72] >> 7), 8), 187), ew = min(max(251 - (int)(ts[73] >> 7), 8), 187);
            if (tid == 0) { ts[74] = ex << 23; ts[75] = ew << 23; }
            const uint32_t sx = ex * 0x800080u, sw = ew * 0x800080u;
#pragma unroll
            for (int j = 0; j < 2; j++) {
                const int i = tid + 256 * j, row = i >> 3, c = (i ^ row) & 7;
                sts128(sbase + OFF_F + 16 * i, mul_bf16x2(fw[j].x, sx), mul_bf16x2(fw[j].y, sx), mul_bf16x2(fw[j].z, sx), mul_bf16x2(fw[j].w, sx));
                if (c < 2) sts128(sbase + OFF_TMP + row * 32 + c * 16, mul_bf16x2(fw[j].x, sw), mul_bf16x2(fw[j].y, sw), mul_bf16x2(fw[j].z, sw), mul_bf16x2(fw[j].w, sw));
            }
            fence_proxy_async_smem();
            named_bar(1, 256);
        }
        const int t = tid & 127;
        Xf f;
        f.sbase = sbase; f.lane = lane; f.xsw = cta & 4; f.dw = desc_lo(sbase + (wg ? OFF_W1 : OFF_W0));
        {
            const int w = t >> 5;
            const uint32_t nw = (8 * (w & 1) + (lane >> 2)) * 4 + (cta & 3), rw = R_W + nw / 3;
            f.pw = sp + (rw << 16) + 4096 + ((nw % 3) << 14) + (w >> 1) * 128;
            f.cw = ((lane & 7) ^ (w >> 1)) << 4;
            for (int i = 0; i < RW; i++) f.cw |= run_sel(rw + i * 22, 0, 0) << (8 + i);
            mbar_wait(bars + B_FULL + 8 * (NST - 1), 0);
            mbar_wait(bars + B_TSEL, 0);
            const uint32_t gr = ts[64], pmask = ts[66];
            const uint32_t rx = ts[8 * w + (lane >> 2)];
            f.px = sp + ((rx & 15) << 18) + 4096;
            f.cx = ((lane & 7) << 4) | ((((pmask >> ((rx >> 3) & 1)) ^ -(((rx >> 1) ^ (rx >> 4)) & 1)) & 0x55) << 8);
#pragma unroll
            for (int i = 0; i < RW; i++) f.cw ^= (((pmask >> ((rw + i * 22) >> 5)) ^ (gr >> 6)) & 1) << (8 + i);
            const uint32_t row = ((gr & 12) << 1) | ((gr & 48) >> 3);
            f.pw += row * 128;
            f.cw ^= (row & 7) << 4;
            const uint32_t s = ts[32 + (gr >> 6) * 16 + 8 * (w & 1) + (lane >> 2)], ga = sbase + OFF_TMP + (16 * (s >> 3) + (s & 7)) * 32 + (lane & 3) * 4;
#pragma unroll
            for (int i = 0; i < 4; i++) asm volatile("ld.shared.u32 %0, [%1];" : "=r"(f.g[i]) : "r"(ga + (i & 1) * 256 + (i >> 1) * 16) : "memory");
        }
        {
            float at[32];
#pragma unroll 1
            for (uint32_t v = 0; v < V0; v++) {
                const uint32_t e = plan_load(f, v, wg), raw = pre_slot(sbase, v, wg);
                if (v >= NST) mbar_wait(bars + B_FULL + 8 * (v % NST), (v / NST) & 1);
                if (e & 6) mbar_wait(bars + B_PRE + 16 * v + 8 * wg, 0);
                if (v == PAUSE) mbar_wait(bars + B_PUB, 0);
                wg_fence();
                if ((e & 6) == 2) {
                    unit_mma<false>(at, f, raw);
                    wg_wait<0>();
                    unit_store<false>(at, f, e);
                } else if (e & 4) {
                    unit_mma<true>(at, f, raw);
                    wg_wait<0>();
                    unit_store<true>(at, f, e);
                }
                if (lane == 0) mbar_arrive(bars + B_EMPTY + 8 * (v % NST));
                unit_done(f, e, v);
            }
        }
        const int slot = cta >> 2;
        f.e = plan_load(f, V0, wg);
        uint32_t a0[40], a1[40], b0[40], b1[40];
#pragma unroll
        for (int i = 0; i < 40; i++) a0[i] = a1[i] = b0[i] = b1[i] = 0;
        if (slot == 0) gemm_main<true>(a0, a1, b0, b1, f, wg);
        else gemm_main<false>(a0, a1, b0, b1, f, wg);
        const uint32_t gr = __shfl_sync(0xffffffffu, ts[64], 0);
        const float sx = __uint_as_float(ts[74]), sw = __uint_as_float(ts[75]);
        uint32_t wr[2][4][4];
        w_fetch(wr[0], f, V0 + HEND);
#pragma unroll 1
        for (int m = 0; m < 2; m++) {
            if (slot == 0) gemm_last<true>(a0, a1, wr, f, wg, m);
            else gemm_last<false>(a0, a1, wr, f, wg, m);
            reg_fence(a0);
            reg_fence(a1);
            const int wsw = gr & 4;
            mbar_wait(bars + B_GATE + 8 * y_gate(2 * m + wg), 0);
            if (m) mbar_wait(bars + B_FTAB, 0);
            const uint32_t ytab = sbase + OFF_YT + (m * 2 + wg) * (kNT * 4);
            store_tile(a0, a1, b0, b1, wr[0], f, m == 0, sbase + OFF_STG + wg * 16384, t, wg, sp, slot, ytab, wsw);
            __syncwarp();
            if (lane == 0) mbar_arrive(bars + B_YS + 8 * (2 * m + wg));
        }
        tail_phase(sbase, smem_raw, sp, wg, gr, sx, sw, x, wt, gamma, beta, out);
    }
}

constexpr int C_STAGE = 32768 + 2 * XB, C_SMEM = 3 * C_STAGE + 64;
__global__ void __launch_bounds__(256, 1) corr_kernel(const __grid_constant__ CUtensorMap tmx, const __grid_constant__ CUtensorMap tmw) {
    extern __shared__ __align__(1024) uint8_t smem_raw[];
    const uint32_t sbase = smem_u32(smem_raw) & ~1023u, bars = sbase + 3 * C_STAGE;
    const int tid = threadIdx.x, wg = __shfl_sync(0xffffffffu, tid >> 7, 0), b = blockIdx.x >> 1, dh = blockIdx.x & 1;
    auto load = [&](int k) {
        const uint32_t st = sbase + (k % 3) * C_STAGE, bar = bars + 8 * (k % 3);
        mbar_expect_tx(bar, C_STAGE);
        for (int i = 0; i < 4; i++) tma2d(st + i * 8192, &tmw, 256 * dh + 64 * i, 64 * k, bar);
        tma4d(st + 32768, &tmx, 64 * k, 64 - kMO, 1, b, bar);
        tma4d(st + 32768 + XB, &tmx, 64 * k, 0, 0, b, bar);
    };
    uint32_t epoch = 0;
    if (tid == 0) {
        for (int i = 0; i < 3; i++) mbar_init(bars + 8 * i, 1);
        fence_mbar_init();
        fence_proxy_async_smem();
        for (int k = 0; k < 3; k++) load(k);
        asm volatile("ld.relaxed.gpu.global.u32 %0, [%1];" : "=r"(epoch) : "l"(&g_epoch) : "memory");
    }
    __syncthreads();
    float a[2][80];
#pragma unroll
    for (int i = 0; i < 80; i++) a[0][i] = a[1][i] = 0.f;
#pragma unroll 1
    for (int k = 0; k < 8; k++) {
        const uint32_t dA = desc_lo(sbase + (k % 3) * C_STAGE + wg * 16384), dB = desc_lo(sbase + (k % 3) * C_STAGE + 32768);
        mbar_wait(bars + 8 * (k % 3), (k / 3) & 1);
        wg_fence();
#pragma unroll
        for (int i = 0; i < 8; i++) {
            wgmma_n160_f<1>(a[i & 1], dA + (i & 1) * 512 + (i >> 1) * 128, dB + (i >> 1) * 2);
            wgmma_n160_f<-1>(a[i & 1], dA + (i & 1) * 512 + (i >> 1) * 128, dB + XB / 16 + (i >> 1) * 2);
        }
        wg_commit();
        wg_wait<0>();
        __syncthreads();
        if (tid == 0 && k + 3 < 8) load(k + 3);
    }
    reg_fence(a[0]);
    reg_fence(a[1]);
    const int w = (tid >> 5) & 3, g = (tid & 31) >> 2, q = tid & 3;
    float* stage = reinterpret_cast<float*>(smem_raw);
#pragma unroll
    for (int i = 0; i < 160; i++) {
        const int m = i / 80, j = i % 80, d = 16 * w + 8 * ((j >> 1) & 1) + g;
        stage[((2 * wg + m) * kNT + 8 * (j >> 2) + 2 * q + (j & 1)) * 64 + (d & 33) + 8 * ((d >> 1) & 3) + 2 * ((d >> 3) & 3)] = a[m][j];
    }
    __syncthreads();
    for (int i = tid; i < 4 * kNT * 16; i += 256)
        reinterpret_cast<float4*>(g_corr)[(b * 8 + 4 * dh) * kNT * 16 + i] = reinterpret_cast<const float4*>(stage)[i];
    __syncthreads();
    if (tid == 0) {
        asm volatile("fence.acq_rel.gpu;" ::: "memory");
        asm volatile("st.relaxed.gpu.global.u32 [%0], %1;" ::"l"(&g_cready[blockIdx.x * 32]), "r"(epoch + 1) : "memory");
    }
}

__global__ void __launch_bounds__(256) plain_conv(const __nv_bfloat16* __restrict__ x, const __nv_bfloat16* __restrict__ w) {
    __shared__ float xs[64][17], ws[16][65];
    float* h = g_direct;
    const int b = blockIdx.z, l0 = blockIdx.x * 64, d0 = blockIdx.y * 64, tx = threadIdx.x & 15, ty = threadIdx.x >> 4;
    float acc[4][4] = {};
    for (int k0 = 0; k0 < 31 * 512; k0 += 16) {
        for (int i = threadIdx.x; i < 1024; i += 256) {
            const int l = min(l0 + (i >> 4), kL - 1);
            xs[i >> 4][i & 15] = __bfloat162float(x[((size_t)b * kRows + l) * 1024 + k0 + (i & 15)]);
            ws[i >> 6][i & 63] = __bfloat162float(w[(size_t)(k0 + (i >> 6)) * 512 + d0 + (i & 63)]);
        }
        __syncthreads();
        for (int k = 0; k < 16; k++)
            for (int i = 0; i < 4; i++)
                for (int j = 0; j < 4; j++) acc[i][j] = fmaf(xs[ty * 4 + i][k], ws[k][tx * 4 + j], acc[i][j]);
        __syncthreads();
    }
    for (int i = 0; i < 4; i++)
        for (int j = 0; j < 4; j++)
            if (l0 + ty * 4 + i < kL) h[((size_t)b * kL + l0 + ty * 4 + i) * 512 + d0 + tx * 4 + j] = acc[i][j];
}
__global__ void __launch_bounds__(256) plain_norm(const __nv_bfloat16* __restrict__ gamma, const __nv_bfloat16* __restrict__ beta,
                                                  __nv_bfloat16* __restrict__ out) {
    __shared__ float s1[8][32], s2[8][32];
    const int c = threadIdx.x & 31, r = threadIdx.x >> 5, d = blockIdx.x * 32 + c;
    const float* h = g_direct + (size_t)blockIdx.y * kL * 512 + d;
    float a = 0.f, q = 0.f;
    for (int l = r; l < kL; l += 8) { const float v = h[(size_t)l * 512]; a += v; q = fmaf(v, v, q); }
    s1[r][c] = a; s2[r][c] = q;
    __syncthreads();
    a = q = 0.f;
    for (int i = 0; i < 8; i++) { a += s1[i][c]; q += s2[i][c]; }
    const float mean = a * (1.0f / kL), sc = __bfloat162float(gamma[d]) / sqrtf(fmaxf(q * (1.0f / kL) - mean * mean, 0.f) + 1e-5f);
    const float sh = __bfloat162float(beta[d]) - mean * sc;
    for (int l = r; l < kL; l += 8)
        out[((size_t)blockIdx.y * kL + l) * 512 + d] = __float2bfloat16(gelu_half(0.5f * fmaf(h[(size_t)l * 512], sc, sh)));
}

typedef CUresult (*EncodeTiledFn)(CUtensorMap*, CUtensorMapDataType, cuuint32_t, void*, const cuuint64_t*, const cuuint64_t*,
                                  const cuuint32_t*, const cuuint32_t*, CUtensorMapInterleave, CUtensorMapSwizzle,
                                  CUtensorMapL2promotion, CUtensorMapFloatOOBfill);

void encode(EncodeTiledFn fn, CUtensorMap* tm, const void* ptr, int rank, const cuuint64_t* dims, const cuuint64_t* strides,
            const cuuint32_t* box, CUtensorMapL2promotion promo, CUtensorMapSwizzle swz = CU_TENSOR_MAP_SWIZZLE_128B) {
    const cuuint32_t es[5] = {1, 1, 1, 1, 1};
    fn(tm, CU_TENSOR_MAP_DATA_TYPE_BFLOAT16, rank, const_cast<void*>(ptr), dims, strides, box, es, CU_TENSOR_MAP_INTERLEAVE_NONE,
       swz, promo, CU_TENSOR_MAP_FLOAT_OOB_FILL_NONE);
}

}

extern "C" void kernel_launch(void* const* d_in, const int* in_sizes, int n_in, void* d_out, int out_size) {
    const __nv_bfloat16* x = (const __nv_bfloat16*)d_in[0];
    const __nv_bfloat16* w = (const __nv_bfloat16*)d_in[1];
    const __nv_bfloat16* gamma = (const __nv_bfloat16*)d_in[2];
    const __nv_bfloat16* beta = (const __nv_bfloat16*)d_in[3];
    static EncodeTiledFn enc = nullptr;
    static int resident = 0;
    if (!enc) {
        void* fn = nullptr;
        cudaDriverEntryPointQueryResult qr;
        cudaGetDriverEntryPoint("cuTensorMapEncodeTiled", &fn, cudaEnableDefault, &qr);
        enc = (EncodeTiledFn)fn;
        cudaFuncSetAttribute(main_kernel, cudaFuncAttributeMaxDynamicSharedMemorySize, MAIN_SMEM);
        cudaFuncSetAttribute(corr_kernel, cudaFuncAttributeMaxDynamicSharedMemorySize, C_SMEM);
        int dev = 0, per_sm = 0;
        cudaGetDevice(&dev);
        cudaDeviceGetAttribute(&resident, cudaDevAttrMultiProcessorCount, dev);
        cudaOccupancyMaxActiveBlocksPerMultiprocessor(&per_sm, main_kernel, 384, MAIN_SMEM);
        resident *= per_sm;
    }
    if (resident < NCTA + 4) {
        plain_conv<<<dim3((kL + 63) / 64, 8, 2), 256>>>(x, w);
        plain_norm<<<dim3(16, 2), 256>>>(gamma, beta, (__nv_bfloat16*)d_out);
        return;
    }
    CUtensorMap tmx, tmw0, tmw1, tmcx, tmcw;
    {
        const cuuint64_t dims[3] = {1024, kRows, 2}, strides[2] = {2048, (cuuint64_t)kRows * 2048};
        const cuuint32_t box[3] = {64, 64, 1};
        encode(enc, &tmx, x, 3, dims, strides, box, CU_TENSOR_MAP_L2_PROMOTION_L2_128B);
    }
    {
        const cuuint64_t dims0[3] = {512, 512, 16}, dims1[3] = {512, 512, 15}, strides[2] = {1024, 2 * 512 * 512 * 2};
        const cuuint32_t box[3] = {64, 2, 16};
        encode(enc, &tmw0, w, 3, dims0, strides, box, CU_TENSOR_MAP_L2_PROMOTION_L2_128B);
        encode(enc, &tmw1, w + 512 * 512, 3, dims1, strides, box, CU_TENSOR_MAP_L2_PROMOTION_L2_128B);
    }
    {
        const cuuint64_t dims[4] = {512, kMO, kNT, 2}, strides[3] = {2048, kMO * 2048, (cuuint64_t)kRows * 2048};
        const cuuint32_t box[4] = {64, 1, kNT, 1};
        encode(enc, &tmcx, x, 4, dims, strides, box, CU_TENSOR_MAP_L2_PROMOTION_L2_128B);
        const cuuint64_t dimw[2] = {512, 512}, stridew[1] = {1024};
        const cuuint32_t boxw[2] = {64, 64};
        encode(enc, &tmcw, w + 30 * 512 * 512, 2, dimw, stridew, boxw, CU_TENSOR_MAP_L2_PROMOTION_L2_128B);
    }
    main_kernel<<<NCTA, 384, MAIN_SMEM>>>(tmx, tmw0, tmw1, x, w, gamma, beta, (__nv_bfloat16*)d_out);
    cudaLaunchConfig_t cfg = {};
    cudaLaunchAttribute at[1];
    cfg.gridDim = 4;
    cfg.blockDim = 256;
    cfg.dynamicSmemBytes = C_SMEM;
    at[0].id = cudaLaunchAttributeProgrammaticStreamSerialization;
    at[0].val.programmaticStreamSerializationAllowed = 1;
    cfg.attrs = at;
    cfg.numAttrs = 1;
    cudaLaunchKernelEx(&cfg, corr_kernel, tmcx, tmcw);
}
```

```cpp
#include <cuda_runtime.h>
#include <cuda_bf16.h>
#include <cuda.h>
#include <stdint.h>

namespace {

constexpr int kL    = 7985;
constexpr int kRows = 8000;
constexpr int kMO   = 50;
constexpr int kNT   = 160;

constexpr int V0 = 7;
constexpr int NPRE = 6;
constexpr int RX = 4;
constexpr int PAUSE = 5;
constexpr int YSLEEP = 100;
constexpr int PRE1 = 4;
constexpr int TSLEEP = 200;
constexpr int MERGE = 1;
constexpr int RW = 10;

static_assert(V0 >= 7 && V0 <= 9 && RX >= 2 && RX <= 4 && RW >= V0 - 1 && RW <= 12, "rings must fit and be as deep as the look-ahead");
constexpr uint32_t HOME_MASK = 0xB;
constexpr uint32_t R_W = 64 * RX, NPAGES = (R_W + 22 * RW + 31) / 32;

__device__ __align__(1024) uint8_t g_sp[(size_t)(NPAGES + 1) * (2u << 20)];
__device__ __align__(128) unsigned g_tsel[32];
__device__ __forceinline__ uint32_t run_sel(uint32_t r, uint32_t group, uint32_t pmask) {
    return ((pmask >> (r >> 5)) ^ __popc(r & HOME_MASK) ^ group) & 1;
}
__device__ __forceinline__ uint32_t run_off(uint32_t r, uint32_t run, uint32_t group, uint32_t pmask) {
    return (r << 16) + 4096 + (run_sel(r, group, pmask) << 13) + (run << 14);
}
__device__ __forceinline__ unsigned* chunk_flag(uint8_t* sp, int done, int part, int chunk) {
    return reinterpret_cast<unsigned*>(sp + (4 + 3 * (chunk >> 5)) * 65536 + (done ? (part ? 15 : 13) : (part ? 0 : 14)) * 4096 + (chunk & 31) * 128);
}
__device__ __forceinline__ unsigned long long* part_sums(uint8_t* sp, int b, int db, uint32_t epoch) {
    return reinterpret_cast<unsigned long long*>(sp + (8 + 2 * db + ((__popc((8 + 2 * db) & HOME_MASK) ^ b) & 1)) * 65536 + 13 * 4096 + (epoch & 1) * 1024);
}
__device__ __forceinline__ unsigned* y_flag(uint8_t* sp, int b, int db) { return reinterpret_cast<unsigned*>(part_sums(sp, b, db, 0) + 512); }
__device__ __align__(256) float g_corr[16 * kNT * 64];
__device__ unsigned g_cready[4 * 32];
__device__ float g_direct[512 * 250 * 64];
__device__ unsigned long long g_dpart[2 * 512 * 64];
__device__ unsigned g_exit, g_epoch;

__device__ __forceinline__ uint32_t smem_u32(const void* p) { return (uint32_t)__cvta_generic_to_shared(p); }

__device__ __forceinline__ void mbar_init(uint32_t bar, uint32_t count) {
    asm volatile("mbarrier.init.shared::cta.b64 [%0], %1;" ::"r"(bar), "r"(count) : "memory");
}
__device__ __forceinline__ void mbar_expect_tx(uint32_t bar, uint32_t bytes) {
    asm volatile("mbarrier.arrive.expect_tx.shared::cta.b64 _, [%0], %1;" ::"r"(bar), "r"(bytes) : "memory");
}
__device__ __forceinline__ void mbar_arrive(uint32_t bar) {
    asm volatile("mbarrier.arrive.shared::cta.b64 _, [%0];" ::"r"(bar) : "memory");
}
__device__ __forceinline__ bool mbar_try(uint32_t bar, uint32_t parity) {
    uint32_t ok;
    asm volatile(
        "{\n.reg .pred p;\n"
        "mbarrier.try_wait.parity.shared::cta.b64 p, [%1], %2;\n"
        "selp.u32 %0, 1, 0, p;\n}\n"
        : "=r"(ok) : "r"(bar), "r"(parity) : "memory");
    return ok;
}
__device__ __forceinline__ bool mbar_test(uint32_t bar, uint32_t parity) {
    uint32_t ok;
    asm volatile(
        "{\n.reg .pred p;\n"
        "mbarrier.test_wait.parity.shared::cta.b64 p, [%1], %2;\n"
        "selp.u32 %0, 1, 0, p;\n}\n"
        : "=r"(ok) : "r"(bar), "r"(parity) : "memory");
    return ok;
}
__device__ __forceinline__ void mbar_wait(uint32_t bar, uint32_t parity) {
#pragma unroll 1
    for (uint32_t n = 0; n < (1u << 14); n++)
        if (mbar_try(bar, parity)) break;
}
__device__ __forceinline__ void fence_proxy_async_smem() { asm volatile("fence.proxy.async.shared::cta;" ::: "memory"); }
__device__ __forceinline__ void fence_mbar_init() { asm volatile("fence.mbarrier_init.release.cluster;" ::: "memory"); }

__device__ __forceinline__ void bulk_g2s(uint32_t dst, const void* src, uint32_t bytes, uint32_t bar) {
    asm volatile("cp.async.bulk.shared::cluster.global.mbarrier::complete_tx::bytes [%0], [%1], %2, [%3];"
                 ::"r"(dst), "l"(src), "r"(bytes), "r"(bar) : "memory");
}
__device__ __forceinline__ void tma3d_ef(uint32_t dst, const CUtensorMap* tm, int c0, int c1, int c2, uint32_t bar) {
    asm volatile("{\n.reg .b64 pol;\ncreatepolicy.fractional.L2::evict_first.b64 pol, 1.0;\n"
                 "cp.async.bulk.tensor.3d.shared::cluster.global.mbarrier::complete_tx::bytes.L2::cache_hint [%0], [%1, {%3, %4, %5}], [%2], pol;\n}"
                 ::"r"(dst), "l"(tm), "r"(bar), "r"(c0), "r"(c1), "r"(c2) : "memory");
}
__device__ __forceinline__ void tma3d(uint32_t dst, const CUtensorMap* tm, int c0, int c1, int c2, uint32_t bar) {
    asm volatile("cp.async.bulk.tensor.3d.shared::cluster.global.mbarrier::complete_tx::bytes [%0], [%1, {%3, %4, %5}], [%2];"
                 ::"r"(dst), "l"(tm), "r"(bar), "r"(c0), "r"(c1), "r"(c2) : "memory");
}
__device__ __forceinline__ void red_relaxed(unsigned* p) { asm volatile("red.relaxed.gpu.global.add.u32 [%0], 1;" ::"l"(p) : "memory"); }
__device__ __forceinline__ void named_arrive(int id, int n) { asm volatile("bar.arrive %0, %1;" ::"r"(id), "r"(n) : "memory"); }
__device__ __forceinline__ void named_bar(int id, int n) { asm volatile("bar.sync %0, %1;" ::"r"(id), "r"(n) : "memory"); }

__device__ __forceinline__ void wg_fence() { asm volatile("wgmma.fence.sync.aligned;" ::: "memory"); }
__device__ __forceinline__ void wg_commit() { asm volatile("wgmma.commit_group.sync.aligned;" ::: "memory"); }
template <int N> __device__ __forceinline__ void wg_wait() { asm volatile("wgmma.wait_group.sync.aligned %0;" ::"n"(N) : "memory"); }
template <int N> __device__ __forceinline__ void reg_fence(float (&d)[N]) {
#pragma unroll
    for (int i = 0; i < N; i++) asm volatile("" : "+f"(d[i])::"memory");
}

#define F4(a, i) "+f"(a[i]), "+f"(a[i + 1]), "+f"(a[i + 2]), "+f"(a[i + 3])
#define F8(a, i) F4(a, i), F4(a, i + 4)
#define F16(a, i) F8(a, i), F8(a, i + 8)

constexpr uint32_t HI128 = 0x40000040u;
__device__ __forceinline__ uint32_t desc_lo(uint32_t addr) { return (addr >> 4) | 0x10000u; }

#define R4(a, i) "+r"(a[i]), "+r"(a[i + 1]), "+r"(a[i + 2]), "+r"(a[i + 3])
#define R8(a, i) R4(a, i), R4(a, i + 4)
template <int N> __device__ __forceinline__ void reg_fence(uint32_t (&d)[N]) {
#pragma unroll
    for (int i = 0; i < N; i++) asm volatile("" : "+r"(d[i])::"memory");
}
__device__ __forceinline__ void tma2d(uint32_t dst, const CUtensorMap* tm, int c0, int c1, uint32_t bar) {
    asm volatile("cp.async.bulk.tensor.2d.shared::cluster.global.mbarrier::complete_tx::bytes [%0], [%1, {%3, %4}], [%2];"
                 ::"r"(dst), "l"(tm), "r"(bar), "r"(c0), "r"(c1) : "memory");
}
__device__ __forceinline__ void tma4d(uint32_t dst, const CUtensorMap* tm, int c0, int c1, int c2, int c3, uint32_t bar) {
    asm volatile("cp.async.bulk.tensor.4d.shared::cluster.global.mbarrier::complete_tx::bytes [%0], [%1, {%3, %4, %5, %6}], [%2];"
                 ::"r"(dst), "l"(tm), "r"(bar), "r"(c0), "r"(c1), "r"(c2), "r"(c3) : "memory");
}

template <int ACC>
__device__ __forceinline__ void wgmma_n64_ss(float (&d)[32], uint32_t da, uint32_t db) {
    asm volatile(
        "{\n.reg .pred p;\n.reg .b64 da, db;\nsetp.ne.b32 p, %36, 0;\nmov.b64 da, {%32, %34};\nmov.b64 db, {%33, %35};\n"
        "wgmma.mma_async.sync.aligned.m64n64k16.f32.bf16.bf16 "
        "{%0,%1,%2,%3,%4,%5,%6,%7,%8,%9,%10,%11,%12,%13,%14,%15,%16,%17,%18,%19,%20,%21,%22,%23,%24,%25,%26,%27,%28,%29,%30,%31},"
        "da, db, p, 1, 1, 0, 1;\n}\n"
        : F16(d, 0), F16(d, 16)
        : "r"(da), "r"(db), "n"(HI128), "n"(HI128), "n"(ACC));
}

__device__ __forceinline__ void wgmma_n64_sp(float (&d)[32], const uint32_t (&a)[4], uint32_t db, uint32_t meta) {
    asm volatile(
        "{\n.reg .pred p;\n.reg .b64 db;\nsetp.ne.b32 p, 0, 0;\nmov.b64 db, {%36, %38};\n"
        "wgmma.mma_async.sp.sync.aligned.m64n64k32.f32.bf16.bf16 "
        "{%0,%1,%2,%3,%4,%5,%6,%7,%8,%9,%10,%11,%12,%13,%14,%15,%16,%17,%18,%19,%20,%21,%22,%23,%24,%25,%26,%27,%28,%29,%30,%31},"
        "{%32,%33,%34,%35}, db, %37, 0, p, 1, 1, 1;\n}\n"
        : F16(d, 0), F16(d, 16)
        : "r"(a[0]), "r"(a[1]), "r"(a[2]), "r"(a[3]), "r"(db), "r"(meta), "n"(HI128));
}

template <int ACC>
__device__ __forceinline__ void wgmma_n56_ss(float (&d)[28], uint32_t da, uint32_t db) {
    asm volatile(
        "{\n.reg .pred p;\n.reg .b64 da, db;\nsetp.ne.b32 p, %31, 0;\nmov.b64 da, {%28, %30};\nmov.b64 db, {%29, %30};\n"
        "wgmma.mma_async.sync.aligned.m64n56k16.f32.f16.f16 "
        "{%0,%1,%2,%3,%4,%5,%6,%7,%8,%9,%10,%11,%12,%13,%14,%15,%16,%17,%18,%19,%20,%21,%22,%23,%24,%25,%26,%27},"
        "da, db, p, 1, 1, 1, 0;\n}\n"
        : F16(d, 0), F8(d, 16), F4(d, 24)
        : "r"(da), "r"(db), "n"(HI128), "n"(ACC));
}

template <int SA>
__device__ __forceinline__ void wgmma_n160_h(uint32_t (&d)[40], uint32_t da, uint32_t db) {
    asm volatile(
        "{\n.reg .pred p;\n.reg .b64 da, db;\nsetp.eq.b32 p, 0, 0;\nmov.b64 da, {%40, %43};\nmov.b64 db, {%41, %43};\n"
        "wgmma.mma_async.sync.aligned.m64n160k16.f16.f16.f16 "
        "{%0,%1,%2,%3,%4,%5,%6,%7,%8,%9,%10,%11,%12,%13,%14,%15,%16,%17,%18,%19,%20,%21,%22,%23,%24,%25,%26,%27,"
        "%28,%29,%30,%31,%32,%33,%34,%35,%36,%37,%38,%39},"
        "da, db, p, %42, 1, 1, 0;\n}\n"
        : R8(d, 0), R8(d, 8), R8(d, 16), R8(d, 24), R8(d, 32)
        : "r"(da), "r"(db), "n"(SA), "n"(HI128));
}
template <int SA>
__device__ __forceinline__ void wgmma_n160_hr(uint32_t (&d)[40], const uint32_t (&a)[4], uint32_t db) {
    asm volatile(
        "{\n.reg .pred p;\n.reg .b64 db;\nsetp.eq.b32 p, 0, 0;\nmov.b64 db, {%44, %46};\n"
        "wgmma.mma_async.sync.aligned.m64n160k16.f16.f16.f16 "
        "{%0,%1,%2,%3,%4,%5,%6,%7,%8,%9,%10,%11,%12,%13,%14,%15,%16,%17,%18,%19,%20,%21,%22,%23,%24,%25,%26,%27,"
        "%28,%29,%30,%31,%32,%33,%34,%35,%36,%37,%38,%39},"
        "{%40,%41,%42,%43}, db, p, %45, 1, 0;\n}\n"
        : R8(d, 0), R8(d, 8), R8(d, 16), R8(d, 24), R8(d, 32)
        : "r"(a[0]), "r"(a[1]), "r"(a[2]), "r"(a[3]), "r"(db), "n"(SA), "n"(HI128));
}
template <int SA>
__device__ __forceinline__ void wgmma_n160_f(float (&d)[80], uint32_t da, uint32_t db) {
    asm volatile(
        "{\n.reg .pred p;\n.reg .b64 da, db;\nsetp.eq.b32 p, 0, 0;\nmov.b64 da, {%80, %83};\nmov.b64 db, {%81, %83};\n"
        "wgmma.mma_async.sync.aligned.m64n160k16.f32.bf16.bf16 "
        "{%0,%1,%2,%3,%4,%5,%6,%7,%8,%9,%10,%11,%12,%13,%14,%15,%16,%17,%18,%19,%20,%21,%22,%23,%24,%25,%26,%27,"
        "%28,%29,%30,%31,%32,%33,%34,%35,%36,%37,%38,%39,%40,%41,%42,%43,%44,%45,%46,%47,%48,%49,%50,%51,%52,%53,%54,%55,"
        "%56,%57,%58,%59,%60,%61,%62,%63,%64,%65,%66,%67,%68,%69,%70,%71,%72,%73,%74,%75,%76,%77,%78,%79},"
        "da, db, p, %82, 1, 1, 0;\n}\n"
        : F16(d, 0), F16(d, 16), F16(d, 32), F16(d, 48), F16(d, 64)
        : "r"(da), "r"(db), "n"(SA), "n"(HI128));
}

__device__ __forceinline__ uint32_t pack_f16(float lo, float hi) {
    uint32_t r;
    asm("cvt.rn.f16x2.f32 %0, %1, %2;" : "=r"(r) : "f"(hi), "f"(lo));
    return r;
}
__device__ __forceinline__ uint32_t mul_bf16x2(uint32_t a, uint32_t b) {
    uint32_t r;
    asm("mul.rn.bf16x2 %0, %1, %2;" : "=r"(r) : "r"(a), "r"(b));
    return r;
}
__device__ __forceinline__ void sts128(uint32_t p, uint32_t a, uint32_t b, uint32_t c, uint32_t d) {
    asm volatile("st.shared.v4.b32 [%0], {%1,%2,%3,%4};" ::"r"(p), "r"(a), "r"(b), "r"(c), "r"(d) : "memory");
}
__device__ __forceinline__ uint32_t pack_bf16(float lo, float hi) {
    uint32_t r;
    asm("cvt.rn.bf16x2.f32 %0, %1, %2;" : "=r"(r) : "f"(hi), "f"(lo));
    return r;
}
__device__ __forceinline__ void stg128(void* p, uint32_t a, uint32_t b, uint32_t c, uint32_t d) {
    asm volatile("st.global.v4.b32 [%0], {%1,%2,%3,%4};" ::"l"(p), "r"(a), "r"(b), "r"(c), "r"(d) : "memory");
}
__device__ __forceinline__ void stmatrix_x4_t(uint32_t addr, uint32_t a, uint32_t b, uint32_t c, uint32_t d) {
    asm volatile("stmatrix.sync.aligned.m8n8.x4.trans.shared.b16 [%0], {%1,%2,%3,%4};"
                 ::"r"(addr), "r"(a), "r"(b), "r"(c), "r"(d) : "memory");
}

constexpr uint32_t cos64(int k, bool half) {
    constexpr uint16_t q[17] = {0x3F80, 0x3F7F, 0x3F7B, 0x3F75, 0x3F6D, 0x3F62, 0x3F55, 0x3F46, 0x3F35, 0x3F22, 0x3F0E, 0x3EF1, 0x3EC4, 0x3E95, 0x3E48, 0x3DC9, 0x0000};
    constexpr uint16_t h[17] = {0x3C00, 0x3BF6, 0x3BD9, 0x3BA8, 0x3B64, 0x3B0E, 0x3AA7, 0x3A2F, 0x39A8, 0x3913, 0x3872, 0x378B, 0x361F, 0x34A5, 0x323E, 0x2E46, 0x0000};
    k &= 63;
    if (k > 32) k = 64 - k;
    const uint16_t* t = half ? h : q;
    return k <= 16 ? t[k] : (t[32 - k] | 0x8000u);
}
constexpr uint32_t fwd_coef(int s, int p, int t) { return (p && s == 0) ? cos64(32 * t, false) : cos64(s * t - 16 * p, false); }
constexpr uint32_t inv_coef(int l, int phi) {
    const int s = phi >> 1, p = phi & 1;
    if (l >= kMO) return 0;
    const uint32_t c = s == 0 ? cos64(32 * l * p, true) : cos64(s * l + 16 * p, true);
    return (c & 0x7FFF) ? c - ((s == 0 ? 6 : 5) << 10) : 0;
}
struct Tables {
    uint32_t fwd[2048];
    uint32_t inv[2048];
};
constexpr Tables make_tables() {
    Tables t = {};
    for (int i = 0; i < 2048; i++) {
        const int row = i >> 5, tt = 8 * (((i >> 2) & 7) ^ (row & 7)) + 2 * (i & 3), s = 8 * (row >> 4) + (row & 7), p = (row >> 3) & 1;
        t.fwd[i] = fwd_coef(s, p, tt) | (fwd_coef(s, p, tt + 1) << 16);
        t.inv[i] = inv_coef(row, tt) | (inv_coef(row, tt + 1) << 16);
    }
    return t;
}
__device__ __align__(128) const Tables g_tab = make_tables();

constexpr int NCTA = 128;
constexpr int NST = 4;
constexpr int HEND = 56;
constexpr int XB = kNT * 128;
constexpr int OFF_W1 = 0, OFF_X = OFF_W1 + NST * 8192, OFF_W0 = OFF_X + 4 * XB, OFF_RAW = OFF_W0 + NST * 8192;
constexpr int OFF_STG = OFF_RAW + 32768;
constexpr int OFF_U0 = OFF_W0, OFF_U1 = OFF_X, OFF_C1 = OFF_W1, OFF_DIR = OFF_W1 + 8192;
constexpr int OFF_F = OFF_RAW + 65536;
constexpr int OFF_C0 = OFF_F + 8192;
constexpr int OFF_TMP = OFF_C0, OFF_BAR = OFF_C0 + 4096;
constexpr int B_FULL = 0, B_EMPTY = 8 * NST, B_TSEL = 16 * NST, B_PRE = B_TSEL + 8, B_SIG = B_PRE + 16 * V0, B_YS = B_SIG + 8 * 33,
              B_T2 = B_YS + 8 * 4, B_SUM = B_T2 + 16, B_GATE = B_SUM + 32, B_RDY = B_GATE + 8 * 32, B_PUB = B_RDY + 8 * 33, B_UNIT = B_PUB + 8,
              B_FTAB = B_UNIT + 8 * 20, B_C1 = B_FTAB + 8, B_NRM = B_C1 + 8, B_END = B_NRM + 32;
template <int O0, int O1>
__device__ __forceinline__ void bar_setup(uint32_t bars) {
#pragma unroll
    for (int o = O0; o < O1; o += 8)
        mbar_init(bars + o, o < B_EMPTY ? 2 : o < B_TSEL ? 8 : o == B_TSEL ? 2 : o < B_SIG ? 1 : o < B_YS - 8 ? 8 : o < B_GATE ? 4 : 1);
    fence_mbar_init();
    fence_proxy_async_smem();
}
constexpr int OFF_TS = OFF_BAR + B_END;
constexpr int OFF_PLAN = OFF_TS + 336;
constexpr int OFF_YT = OFF_PLAN + (V0 + 65) * 8;
constexpr int OFF_GB = (OFF_YT + 4 * kNT * 4 + 15) & ~15;
constexpr int MAIN_SMEM = OFF_GB + 2048;
static_assert(MAIN_SMEM <= 232448 && OFF_U0 + 10 * 8192 == OFF_STG + 16384, "shared memory");
constexpr int XPC = 2 * kNT;
constexpr unsigned PROBE_NEAR = 400;

__device__ __forceinline__ uint32_t raw_slot(uint32_t sbase, uint32_t v, int wg) { return sbase + OFF_RAW + ((v & 3) * 2 + wg) * 8192; }

__device__ __forceinline__ uint32_t pre_slot(uint32_t sbase, uint32_t v, int wg) {
    return v < 4 ? raw_slot(sbase, v, wg) : v < 8 ? sbase + OFF_X + (v - 4) * XB + wg * 8192 : sbase + (wg ? OFF_W1 : OFF_W0) + ((V0 + 3) % NST) * 8192;
}

template <bool DC, int I>
__device__ __forceinline__ void gemm_mma(uint32_t (&a0)[40], uint32_t (&a1)[40], uint32_t dx0, uint32_t dx1, uint32_t dw) {
    constexpr int ks = I >> 2;
    const uint32_t A0 = dw + ks * 128, A1 = A0 + 256, B0 = dx0 + ks * 2, B1 = dx1 + ks * 2;
    if ((I & 3) == 0) wgmma_n160_h<1>(a0, A0, B0);
    if ((I & 3) == 1) wgmma_n160_h<1>(a1, A1, DC ? B1 : B0);
    if ((I & 3) == 2 && !DC) wgmma_n160_h<1>(a0, A1, B1);
    if ((I & 3) == 3 && !DC) wgmma_n160_h<-1>(a1, A0, B1);
}

template <bool DC, int I0, int I1>
__device__ __forceinline__ void gemm_mmas(uint32_t (&a0)[40], uint32_t (&a1)[40], uint32_t dx0, uint32_t dx1, uint32_t dw) {
    if constexpr (I0 < I1) {
        gemm_mma<DC, I0>(a0, a1, dx0, dx1, dw);
        gemm_mmas<DC, I0 + 1, I1>(a0, a1, dx0, dx1, dw);
    }
}
static_assert(RX == 4 && RW == 10, "placement of the output spectra");
__device__ __forceinline__ uint32_t y_unit(uint32_t db, uint32_t tau, uint32_t b, uint32_t pmask) {
    const uint32_t n = (((db >> 1) & 2) + (db & 1)) * XPC + ((db >> 1) & 1) * kNT + tau, r = n / 3;
    return run_off(r + (r >= 192 && r < 278 ? (r < 214 ? 64 : -22) : 0), n % 3, b, pmask);
}
__device__ __forceinline__ int y_gate(int t) { return t ? 28 + t : 27; }
__device__ __forceinline__ int step_k(int h) { return h < HEND ? h >> 1 : 28 + (h & 3); }
__device__ __forceinline__ int step_m(int h) { return h < HEND ? h & 1 : (h >> 2) & 1; }
constexpr uint64_t x_mask() {
    uint64_t r = 2 | (3ull << 58);
    for (int v = 2; v < 58; v++)
        if ((0x73 >> (v & 7)) & 1) r |= 1ull << v;
    return r;
}
constexpr uint64_t XMASK = x_mask();
__device__ __forceinline__ int x_round(int v, int wg) {
    return v == 0 ? wg : (v < 60 && wg != (v & 1) && ((XMASK >> v) & 1)) ? 1 + __popcll(XMASK << (63 - v)) : -1;
}
__device__ __forceinline__ int w_step(int v, int wg) {
    return v == 0 ? -1 : v < 60 ? (wg == (v & 1) ? v - 1 : -1) : v < 62 ? 2 * v - 61 + wg : (v == 62 && wg == 1) ? 63 : -1;
}

__device__ __forceinline__ uint32_t plan_word(int v, int wg, int cta) {
    const int r = x_round(v, wg), h = w_step(v, wg);
    if (r < 0 && h < 0) return 0;
    const bool last = v >= 60 || (v & 1) || (v > 0 && wg == 0 && x_round(v + 1, 0) < 0);
    uint32_t off, row, gate;
    if (r >= 0) {
        const int u = r * NCTA + cta, cb = u / XPC, i = u - cb * XPC, b = i >= kNT, tau = i - b * kNT;
        row = tau & 63;
        off = (((cb % RX) * 64 + b) << 16) + ((tau >> 6) << 14) + b + 2;
        gate = cb >= RX ? 2 * (cb - RX) + 2 : 0;
    } else {
        const int ring = (h + RW - 64 % RW) % RW;
        row = 0;
        off = ((ring * 22) << 16) + (ring << 12) + 4;
        gate = h >= RW ? ((h - RW + 1) >> 1) + 1 : 0;
    }
    return (off + row * 128) | ((row & 7) << 4) | (last << 3) | ((v > 60) << 24) | (gate << 26);
}

struct Xf {
    uint32_t sbase;
    uint8_t *px, *pw;
    uint32_t cx, cw;
    uint32_t xsw;
    uint32_t g[4];
    uint32_t dw;
    uint32_t e;
    int lane;
};
__device__ __forceinline__ uint32_t plan_load(const Xf& f, uint32_t v, int wg) {
    uint32_t e;
    asm volatile("ld.shared.u32 %0, [%1];" : "=r"(e) : "r"(f.sbase + OFF_PLAN + v * 8 + wg * 4));
    return __shfl_sync(0xffffffffu, e, 0);
}
template <bool W>
__device__ __forceinline__ void unit_mma(float (&acc)[32], const Xf& f, uint32_t raw) {
    const uint32_t dB = desc_lo(raw);
    if (W) {
        wgmma_n64_sp(acc, f.g, dB, threadIdx.x & 64 ? 0xDDDDDDDDu : 0x88888888u);
    } else {
        const uint32_t dF = desc_lo(f.sbase + OFF_F);
        wgmma_n64_ss<0>(acc, dF, dB);
        wgmma_n64_ss<1>(acc, dF + 2, dB + 128);
        wgmma_n64_ss<1>(acc, dF + 4, dB + 256);
        wgmma_n64_ss<1>(acc, dF + 6, dB + 384);
    }
    wg_commit();
}
constexpr int DROP = 3;
__device__ __forceinline__ uint32_t pack_sp(float lo, float hi) {
    const uint32_t r = pack_f16(lo, hi);
    return DROP ? (r + (0x10001u << DROP >> 1)) & ~(((1u << DROP) - 1) * 0x10001u) : r;
}
__device__ __forceinline__ void st_quad(uint8_t* p, const float (&acc)[32], int j0) {
    stg128(p, pack_sp(acc[j0], acc[j0 + 1]), pack_sp(acc[j0 + 4], acc[j0 + 5]), pack_sp(acc[j0 + 8], acc[j0 + 9]),
           pack_sp(acc[j0 + 12], acc[j0 + 13]));
}
template <bool W>
__device__ __forceinline__ void unit_store(float (&acc)[32], const Xf& f, uint32_t e) {
    const uint32_t sel = ((W ? f.cw >> (8 + ((e >> 12) & 15)) : e ^ (f.cx >> (8 + ((e >> 21) & 6)))) & 1) << 13;
    const uint32_t o = (e & (W ? 0xFF0F80u : 0xFFFF80u)) + ((e ^ (W ? f.cw : f.cx)) & 0x70);
    uint8_t* const b = W ? f.pw : f.px;
    uint8_t *p0 = b + (o + sel), *p1 = b + ((o ^ 64) + sel);
    reg_fence(acc);
    if (W) {
        st_quad(p0, acc, 0);
        st_quad(p1, acc, 16);
        st_quad(p0 + 4096, acc, 2);
        st_quad(p1 + 4096, acc, 18);
    } else {
        const int d = 131072 + 8192 - 2 * (int)sel;
        st_quad(p0, acc, 0);
        st_quad(p1, acc, 2);
        st_quad(p0 + d, acc, 16);
        st_quad(p1 + d, acc, 18);
    }
}
__device__ __forceinline__ void unit_done(const Xf& f, uint32_t e, uint32_t v) {
    if (e & 8) {
        __syncwarp();
        if (f.lane == 0) mbar_arrive(f.sbase + OFF_BAR + B_SIG + 8 * ((v >> 1) + ((e >> 24) & 1)));
    }
}
__device__ __forceinline__ void step_wait(Xf& f, uint32_t v, int wg) {
    const uint32_t bars = f.sbase + OFF_BAR;
    mbar_wait(bars + B_FULL + 8 * (v % NST), (v / NST) & 1);
}

template <bool DC, int KIND>
__device__ __forceinline__ void gemm_step(uint32_t (&a0)[40], uint32_t (&a1)[40], float (&at)[32], Xf& f, uint32_t v, uint32_t xs, int wg, bool first) {
    const uint32_t bars = f.sbase + OFF_BAR, sb = desc_lo(f.sbase), xb = sb + OFF_X / 16 + xs * (XB / 16), raw = raw_slot(f.sbase, v, wg);
    const uint32_t dx0 = xb + f.xsw, dx1 = xb + (f.xsw ^ 4), dw = f.dw + (v % NST) * 512, e = f.e;
    wg_fence();
    if (KIND) unit_mma<KIND != 1>(at, f, raw);
    constexpr int N1 = KIND == 0 ? 2 : NPRE;
    gemm_mmas<DC, 0, N1>(a0, a1, dx0, dx1, dw);
    wg_commit();
    const uint32_t gate = bars + ((e >> 26) ? B_GATE - 8 + 8 * (e >> 26) : B_PUB);
    const bool open = !KIND || mbar_test(gate, 0);
    f.e = plan_load(f, v + 1, wg);
    wg_wait<1>();
    if (!open) mbar_wait(gate, 0);
    if (!KIND && !first && f.lane == 0) mbar_arrive(bars + B_EMPTY + 8 * ((v - 1) % NST));
    if (KIND) unit_store<KIND != 1>(at, f, e);
    if (KIND) unit_done(f, e, v);
    gemm_mmas<DC, N1, 7>(a0, a1, dx0, dx1, dw);
    if (KIND && !first && f.lane == 0) mbar_arrive(bars + B_EMPTY + 8 * ((v - 1) % NST));
    gemm_mma<DC, 7>(a0, a1, dx0, dx1, dw);
    wg_commit();
}
template <bool DC>
__device__ __forceinline__ void any_step(uint32_t (&a0)[40], uint32_t (&a1)[40], float (&at)[32], Xf& f, uint32_t v, uint32_t xs, int wg, bool first) {
    step_wait(f, v, wg);
    const uint32_t kind = (f.e >> 1) & 3;
    if (kind == 1) gemm_step<DC, 1>(a0, a1, at, f, v, xs, wg, first);
    else if (kind == 2) gemm_step<DC, 2>(a0, a1, at, f, v, xs, wg, first);
    else gemm_step<DC, 0>(a0, a1, at, f, v, xs, wg, first);
}
template <bool DC>
__device__ __forceinline__ void gemm_main(uint32_t (&a0)[40], uint32_t (&a1)[40], uint32_t (&b0)[40], uint32_t (&b1)[40], Xf& f, int wg) {
    float at[32];
#pragma unroll 1
    for (uint32_t k = 0; k < HEND / 2; k++) {
        any_step<DC>(a0, a1, at, f, V0 + 2 * k, k & 3, wg, k == 0);
        any_step<DC>(b0, b1, at, f, V0 + 2 * k + 1, k & 3, wg, false);
    }
    wg_wait<0>();
    if (f.lane == 0) mbar_arrive(f.sbase + OFF_BAR + B_EMPTY + 8 * ((V0 + HEND - 1) % NST));
}
__device__ __forceinline__ void w_fetch(uint32_t (&d)[4][4], const Xf& f, uint32_t v) {
    const uint32_t bars = f.sbase + OFF_BAR, lane = f.lane;
    const uint32_t wa = ((f.dw & 0xFFFF) << 4) + (v % NST) * 8192 + (lane >> 4) * 1024 + (lane & 7) * 128 +
                        (((((threadIdx.x >> 4) & 6) + ((lane >> 3) & 1)) ^ (lane & 7)) << 4);
    mbar_wait(bars + B_FULL + 8 * (v % NST), (v / NST) & 1);
#pragma unroll
    for (int i = 0; i < 4; i++)
        asm volatile("ldmatrix.sync.aligned.m8n8.x4.trans.shared.b16 {%0,%1,%2,%3}, [%4];" : "=r"(d[i][0]), "=r"(d[i][1]), "=r"(d[i][2]), "=r"(d[i][3])
                     : "r"(wa + i * 2048) : "memory");
}
__device__ __forceinline__ void store_tile(uint32_t (&a0)[40], uint32_t (&a1)[40], const uint32_t (&b0)[40], const uint32_t (&b1)[40], uint32_t (&wn)[4][4],
                                           const Xf& f, bool first, uint32_t stg, int t, int wg, uint8_t* sp, int slot, uint32_t ytab, int wsw) {
    const int w = t >> 5, lane = t & 31, m = lane >> 3, i8 = lane & 7;
    const uint32_t addr = stg + i8 * 256 + (m >> 1) * 128 + (((2 * w + (m & 1)) ^ i8 ^ wsw) << 4);
    const int row = 2 * w + (lane >> 4), phi = 2 * slot + (m & 1);
    const uint32_t src = stg + row * 256 + (m & 1) * 128 + ((i8 ^ row) << 4);
    uint8_t* dst = sp + phi * 128 + ((i8 ^ (phi & 7)) << 4);
    named_bar(2 + wg, 128);
#pragma unroll
    for (int r = 0; r < 6; r++) {
        uint32_t v[4][4], o[4];
        if (r > 0) {
#pragma unroll
            for (int i = 0; i < 4; i++) {
                asm volatile("ld.shared.u32 %0, [%1];" : "=r"(o[i]) : "r"(ytab + (32 * (r - 1) + 8 * i + row) * 4) : "memory");
                asm volatile("ld.shared.v4.b32 {%0,%1,%2,%3}, [%4];" : "=r"(v[i][0]), "=r"(v[i][1]), "=r"(v[i][2]), "=r"(v[i][3])
                             : "r"(src + ((r - 1) & 1) * 8192 + i * 2048) : "memory");
            }
        }
        if (r < 5) {
#pragma unroll
            for (int j = 4 * r; j < 4 * r + 4; j++) stmatrix_x4_t(addr + (r & 1) * 8192 + (j & 3) * 2048, a0[2 * j], a0[2 * j + 1], a1[2 * j], a1[2 * j + 1]);
#pragma unroll
            for (int j = 8 * r; j < 8 * r + 8; j++) {
                asm volatile("mov.b32 %0, %1;" : "=r"(a0[j]) : "r"(b0[j]));
                asm volatile("mov.b32 %0, %1;" : "=r"(a1[j]) : "r"(b1[j]));
            }
        } else if (first) {
            w_fetch(wn, f, V0 + HEND + 4);
        }
        if (r > 0) {
#pragma unroll
            for (int i = 0; i < 4; i++) stg128(dst + o[i], v[i][0], v[i][1], v[i][2], v[i][3]);
        }
        if (r < 5) named_bar(2 + wg, 128);
    }
}

template <bool DC>
__device__ __forceinline__ void gemm_last(uint32_t (&a0)[40], uint32_t (&a1)[40], uint32_t (&w)[2][4][4], const Xf& f, int wg, int m) {
    const uint32_t bars = f.sbase + OFF_BAR, sb = desc_lo(f.sbase), v0 = V0 + HEND + 4 * m;
    if (2 * m + wg > 0) named_bar(3 + 2 * m + wg, 256);
#pragma unroll
    for (uint32_t k = 0; k < 4; k++) {
        const uint32_t xb = sb + OFF_X / 16 + k * (XB / 16), dx0 = xb + f.xsw, dx1 = xb + (f.xsw ^ 4);
        wg_fence();
#pragma unroll
        for (int ks = 0; ks < 2; ks++) {
            wgmma_n160_hr<1>(a0, w[k & 1][ks], dx0 + 2 * ks);
            wgmma_n160_hr<1>(a1, w[k & 1][2 + ks], (DC ? dx1 : dx0) + 2 * ks);
            if (!DC) wgmma_n160_hr<1>(a0, w[k & 1][2 + ks], dx1 + 2 * ks);
            if (!DC) wgmma_n160_hr<-1>(a1, w[k & 1][ks], dx1 + 2 * ks);
        }
        wg_commit();
        if (m == 0 && f.lane == 0) mbar_arrive(bars + B_EMPTY + 8 * ((v0 + k) % NST));
        if (k == 3 && 2 * m + wg < 3) named_arrive(4 + 2 * m + wg, 256);
        if (k > 0) wg_wait<1>();
        if (k < 3) w_fetch(w[(k + 1) & 1], f, v0 + k + 1);
    }
    wg_wait<0>();
    if (m && f.lane == 0) mbar_arrive(bars + B_T2 + 8 * wg);
}

__device__ __forceinline__ float gelu_half(float hv) {
    float th;
    asm("tanh.approx.f32 %0, %1;" : "=f"(th) : "f"(hv * fmaf(hv * hv, 8.0f * 0.7978845608028654f * 0.044715f, 2.0f * 0.7978845608028654f)));
    return fmaf(hv, th, hv);
}
__device__ __noinline__ void direct_block(const __nv_bfloat16* __restrict__ x, const __nv_bfloat16* __restrict__ w,
                                          const __nv_bfloat16* __restrict__ gamma, const __nv_bfloat16* __restrict__ beta,
                                          __nv_bfloat16* __restrict__ out, float* sm, int b, int db, int part, uint32_t epoch) {
    float *xs = sm, *ws = sm + 32 * 17, *red = ws + 16 * 65;
    const int tid = threadIdx.x & 127, bar = 2 + (threadIdx.x >> 7), tx = tid & 15, ty = tid >> 4, row0 = part * 250, lim = min(250, kL - row0);
    float* h = g_direct + (size_t)((b * 8 + db) * 32 + part) * (250 * 64);
    for (int l0 = 0; l0 < lim; l0 += 32) {
        float acc[4][4] = {};
        for (int k0 = 0; k0 < 31 * 512; k0 += 16) {
            named_bar(bar, 128);
            for (int i = tid; i < 1024; i += 128) {
                if (i < 512) xs[(i >> 4) * 17 + (i & 15)] = __bfloat162float(x[((size_t)b * kRows + row0 + min(l0 + (i >> 4), lim - 1)) * 1024 + k0 + (i & 15)]);
                ws[(i >> 6) * 65 + (i & 63)] = __bfloat162float(w[(size_t)(k0 + (i >> 6)) * 512 + 64 * db + (i & 63)]);
            }
            named_bar(bar, 128);
            for (int k = 0; k < 16; k++)
#pragma unroll
                for (int i = 0; i < 4; i++)
#pragma unroll
                    for (int j = 0; j < 4; j++) acc[i][j] = fmaf(xs[(ty * 4 + i) * 17 + k], ws[k * 65 + tx * 4 + j], acc[i][j]);
        }
#pragma unroll
        for (int i = 0; i < 4; i++)
#pragma unroll
            for (int j = 0; j < 4; j++)
                if (l0 + ty * 4 + i < lim) h[(l0 + ty * 4 + i) * 64 + tx * 4 + j] = acc[i][j];
    }
    const int c = tid & 63;
    float mean = 0.f, var = 0.f;
    for (int r = 0; r < 2; r++) {
        named_bar(bar, 128);
        float s = 0.f;
        for (int l = tid >> 6; l < lim; l += 2) {
            const float v = h[l * 64 + c] - mean;
            s += r ? v * v : v;
        }
        red[tid] = s;
        named_bar(bar, 128);
        unsigned long long* p = g_dpart + ((r * 16 + b * 8 + db) * 32) * 64 + c;
        if (tid < 64)
            asm volatile("st.relaxed.gpu.global.v2.b32 [%0], {%1, %2};" ::"l"(p + part * 64), "r"(__float_as_uint(red[c] + red[64 + c])), "r"(epoch) : "memory");
        s = 0.f;
        for (int k = 0; k < 32; k++) {
            unsigned long long v = 0;
#pragma unroll 1
            for (uint32_t n = 0; n < (1u << 19); n++) {
                asm volatile("ld.relaxed.gpu.global.u64 %0, [%1];" : "=l"(v) : "l"(p + k * 64) : "memory");
                if ((uint32_t)(v >> 32) == epoch) break;
                __nanosleep(200);
            }
            s += __uint_as_float((uint32_t)v);
        }
        (r ? var : mean) = s * (1.0f / kL);
    }
    const float a = __bfloat162float(gamma[64 * db + c]) / sqrtf(var + 1e-5f), be = __bfloat162float(beta[64 * db + c]);
    for (int l = tid >> 6; l < lim; l += 2)
        out[((size_t)b * kL + row0 + l) * 512 + 64 * db + c] = __float2bfloat16(gelu_half(0.5f * fmaf(h[l * 64 + c] - mean, a, be)));
    named_bar(bar, 128);
}

__device__ __forceinline__ int tail_block(uint32_t gr, int t) { return 4 * (t >> 1) + ((gr >> 4) & 2) + (t & 1); }
__device__ __forceinline__ void tail_poll(uint8_t* sp, uint32_t gr, int t) {
#pragma unroll 1
    for (uint32_t n = 0; n < (1u << 15); n++) {
        unsigned v;
        asm volatile("ld.relaxed.gpu.global.u32 %0, [%1];" : "=r"(v) : "l"(y_flag(sp, gr >> 6, tail_block(gr, t))) : "memory");
        if (v >= 32) break;
        __nanosleep(YSLEEP);
    }
    asm volatile("fence.acquire.gpu;" ::: "memory");
    asm volatile("fence.proxy.async.global;" ::: "memory");
}
__device__ __forceinline__ const float* corr_src(uint32_t gr, int t) { return &g_corr[(((gr >> 6) * 8 + tail_block(gr, t)) * kNT + (gr & 31) * 5) * 64]; }
__device__ __forceinline__ void corr_load(uint32_t sbase, uint32_t gr, int t, uint32_t bar) {
    bulk_g2s(sbase + (t < 2 ? OFF_C0 : OFF_C1) + (t & 1) * 1280, corr_src(gr, t), 1280, bar);
}
__device__ __forceinline__ void tail_phase(uint32_t sbase, uint8_t* smem, uint8_t* sp, int wg, uint32_t gr, float sx, float sw, const __nv_bfloat16* __restrict__ x,
                                           const __nv_bfloat16* __restrict__ wt, const __nv_bfloat16* __restrict__ gamma,
                                           const __nv_bfloat16* __restrict__ beta, __nv_bfloat16* __restrict__ out) {
    const uint32_t* ts = reinterpret_cast<const uint32_t*>(smem + OFF_TS);
    const int tid = threadIdx.x, w = (tid >> 5) & 3, lane = tid & 31, g = lane >> 2, q = lane & 3;
    const int b = gr >> 6, part = gr & 31;
#pragma unroll 1
    for (int rd = 0; rd < 3; rd++) {
        if (rd < 2) {
            float acc[28], acc2[28], s[8] = {0.f, 0.f, 0.f, 0.f, 0.f, 0.f, 0.f, 0.f};
            const float swq = q == 0 ? sw : 0.f;
            const int t = 2 * rd + wg;
            const uint32_t ub = sbase + (t < 2 ? OFF_U0 : OFF_U1) + (t & 1) * 40960, ubar = sbase + OFF_BAR + B_UNIT + 40 * t;
            const float* c1 = reinterpret_cast<const float*>(smem + (t < 2 ? OFF_C0 : OFF_C1) + (t & 1) * 1280) + 16 * w + g;
            const uint32_t ka = ub + (lane >> 4) * 1024 + (lane & 7) * 128 + (((2 * w + ((lane >> 3) & 1)) ^ (lane & 7)) << 4);
            auto inverse = [&](float (&d)[28], int u) {
                const uint32_t dA = desc_lo(ub + u * 8192), dB = desc_lo(sbase + OFF_F);
                wg_fence();
                wgmma_n56_ss<0>(d, dA, dB);
                wgmma_n56_ss<1>(d, dA + 128, dB + 2);
                wgmma_n56_ss<1>(d, dA + 256, dB + 4);
                wgmma_n56_ss<1>(d, dA + 384, dB + 6);
                wg_commit();
            };
            auto keep = [&](float (&d)[28], int u, int un) {
                const bool ok = mbar_try(ubar + 8 * un, 0);
                reg_fence(d);
                d[25] = fmaf(c1[u * 64] * sx, swq, d[25]);
                d[27] = fmaf(c1[u * 64 + 8] * sx, swq, d[27]);
                if (part == 31 && u == 4) {
                    if (q >= 2) d[16] = d[18] = 0.f;
                    if (q >= 1) d[17] = d[19] = 0.f;
#pragma unroll
                    for (int i = 20; i < 28; i++) d[i] = 0.f;
                }
                const uint32_t a = ka + u * 8192;
#pragma unroll
                for (int j = 0; j < 6; j += 2)
                    stmatrix_x4_t(a + j * 1024, pack_f16(d[4 * j], d[4 * j + 1]), pack_f16(d[4 * j + 2], d[4 * j + 3]),
                                  pack_f16(d[4 * j + 4], d[4 * j + 5]), pack_f16(d[4 * j + 6], d[4 * j + 7]));
                asm volatile("stmatrix.sync.aligned.m8n8.x2.trans.shared.b16 [%0], {%1,%2};"
                             ::"r"(a + 6 * 1024), "r"(pack_f16(d[24], d[25])), "r"(pack_f16(d[26], d[27])) : "memory");
#pragma unroll
                for (int i = 0; i < 28; i++) {
                    s[i & 3] += d[i];
                    s[4 + (i & 3)] = fmaf(d[i], d[i], s[4 + (i & 3)]);
                }
#pragma unroll
                for (int i = 0; i < 8; i++) asm volatile("" : "+f"(s[i]));
                if (!ok) mbar_wait(ubar + 8 * un, 0);
                wg_wait<0>();
            };
            if (t >= 2) mbar_wait(sbase + OFF_BAR + B_C1, 0);
            mbar_wait(ubar, 0);
            inverse(acc, 0);
            mbar_wait(ubar + 8, 0);
            wg_wait<0>();
#pragma unroll 1
            for (int u = 0;; u += 2) {
                inverse(acc2, min(u + 1, 4));
                keep(acc, u, min(u + 2, 4));
                if (u == 4) break;
                inverse(acc, u + 2);
                keep(acc2, u + 1, min(u + 3, 4));
            }
#pragma unroll
            for (int i = 0; i < 4; i++) s[i] = s[2 * i] + s[2 * i + 1];
#pragma unroll
            for (int i = 0; i < 2; i++) s[i] = (q & 2 ? s[2 + i] : s[i]) + __shfl_xor_sync(0xffffffffu, q & 2 ? s[i] : s[2 + i], 2);
            const float mine = (q & 1 ? s[1] : s[0]) + __shfl_xor_sync(0xffffffffu, q & 1 ? s[0] : s[1], 1);
            asm volatile("red.relaxed.gpu.global.add.u64 [%0], %1;"
                         ::"l"(part_sums(sp, b, tail_block(gr, t), ts[76]) + 2 * (16 * w + 8 * (q & 1) + g) + (q >> 1)),
                         "l"(fabsf(mine) < 0x1p25f ? __float2ll_rn(mine * 0x1p21f) * 4096 + 1 : 65ll) : "memory");
            __syncwarp();
            if (lane == 0) mbar_arrive(sbase + OFF_BAR + B_SUM + 8 * t);
            if (rd == 0) continue;
        }
        const int t = 2 * rd - 2 + wg, db = tail_block(gr, t);
#pragma unroll 1
        for (uint32_t n = 0; n < (1u << 20); n++)
            if (mbar_try(sbase + OFF_BAR + B_NRM + 8 * t, 0)) break;
        if (reinterpret_cast<const volatile uint32_t*>(ts)[77 + t]) {
            direct_block(x, wt, gamma, beta, out, reinterpret_cast<float*>(smem + OFF_DIR + wg * 8192), b, db, part, ts[76]);
            continue;
        }
        const int jh = g & 1, r0 = 4 * w;
        const int lim = min(250, kL - part * 250) - r0 - (g >> 1);
        float na[8], nb[8];
#pragma unroll
        for (int i = 0; i < 8; i += 2) {
            const float4 v = reinterpret_cast<const float4*>(smem + OFF_GB)[32 * t + 16 * jh + 2 * i + q];
            na[i] = v.x; nb[i] = v.y; na[i + 1] = v.z; nb[i + 1] = v.w;
        }
        __nv_bfloat16* o = out + ((size_t)b * kL + part * 250 + r0 + (g >> 1)) * 512 + 64 * db + 32 * jh + 8 * q;
        int l = r0 + ((lane >> 1) & 3);
        uint32_t ra = sbase + (t < 2 ? OFF_U0 : OFF_U1) + (t & 1) * 40960 + l * 128;
        const int cc = 4 * (lane & 1) + (lane >> 3);
        auto fetch = [&](uint32_t (&r)[4]) {
            asm volatile("ldmatrix.sync.aligned.m8n8.x4.shared.b16 {%0,%1,%2,%3}, [%4];"
                         : "=r"(r[0]), "=r"(r[1]), "=r"(r[2]), "=r"(r[3]) : "r"(ra + (((cc ^ l) & 7) << 4)) : "memory");
            const bool wrap = l >= kMO - 16;
            l += wrap ? 16 - kMO : 16;
            ra += wrap ? 2048 + 8192 - kMO * 128 : 2048;
        };
        auto gelu8 = [&](const uint32_t (&r)[4], uint32_t (&p)[4]) {
#pragma unroll
            for (int i = 0; i < 4; i++) {
                float lo, hi;
                asm("{\n.reg .b16 a, b;\nmov.b32 {a, b}, %2;\ncvt.f32.f16 %0, a;\ncvt.f32.f16 %1, b;\n}" : "=f"(lo), "=f"(hi) : "r"(r[i]));
                p[i] = pack_bf16(gelu_half(fmaf(lo, na[2 * i], nb[2 * i])), gelu_half(fmaf(hi, na[2 * i + 1], nb[2 * i + 1])));
            }
        };
        uint32_t r[2][4], rn[2][4];
        fetch(r[0]);
        fetch(r[1]);
#pragma unroll 1
        for (int i = 0; i < 256; i += 32) {
            fetch(rn[0]);
            fetch(rn[1]);
            uint32_t p0[4], p1[4];
            gelu8(r[0], p0);
            gelu8(r[1], p1);
            if (i < lim) stg128(o, p0[0], p0[1], p0[2], p0[3]);
            if (i + 16 < lim) stg128(o + 16 * 512, p1[0], p1[1], p1[2], p1[3]);
            o += 32 * 512;
#pragma unroll
            for (int k = 0; k < 4; k++) { r[0][k] = rn[0][k]; r[1][k] = rn[1][k]; }
        }
    }
}
__device__ __forceinline__ void channel_scales(uint32_t sbase, uint8_t* smem, uint8_t* sp, int lane) {
    volatile uint32_t* ts = reinterpret_cast<volatile uint32_t*>(smem + OFF_TS);
    const uint32_t gr = ts[64], bars = sbase + OFF_BAR;
#pragma unroll 1
    for (int t = 0; t < 4; t++) {
#pragma unroll 1
        for (uint32_t n = 0; n < (1u << 20); n++)
            if (mbar_try(bars + B_SUM + 8 * t, 0)) break;
        long long s[4];
#pragma unroll 1
        for (uint32_t n = 0; n < (1u << 19); n++) {
            const unsigned long long* p = part_sums(sp, gr >> 6, tail_block(gr, t), ts[76]) + 4 * lane;
#pragma unroll
            for (int i = 0; i < 4; i++) asm volatile("ld.relaxed.gpu.global.u64 %0, [%1];" : "=l"(s[i]) : "l"(p + i) : "memory");
            if (__all_sync(0xffffffffu, s[0] & s[1] & s[2] & s[3] & 32)) break;
        }
        const float sx = __uint_as_float(ts[74]), sw = __uint_as_float(ts[75]);
        bool bad = false;
#pragma unroll
        for (int i = 0; i < 2; i++) {
            const float mean = (float)(s[2 * i] >> 12) * (0x1p-21f / kL), sq = (float)(s[2 * i + 1] >> 12) * (0x1p-21f / kL);
            float2* gb = reinterpret_cast<float2*>(smem + OFF_GB) + 64 * t + 2 * lane + i;
            const float den = fmaxf(sq - mean * mean, 0.f) + 1e-5f * sx * sw * sx * sw, a = gb->x * rsqrtf(den);
            *gb = make_float2(0.5f * a, 0.5f * (gb->y - mean * a));
            bad |= ((s[2 * i] | s[2 * i + 1]) & 0xFC0) || !(den >= 0x1p-22f);
        }
        bad = __any_sync(0xffffffffu, bad);
        if (lane == 0) ts[77 + t] = bad;
        __syncwarp();
        if (lane == 0) mbar_arrive(bars + B_NRM + 8 * t);
    }
}

__device__ __forceinline__ void publish_tiles(uint8_t* sp, uint32_t bars, int cta, int wg) {
#pragma unroll 1
    for (int m = 0; m < 2; m++) {
        mbar_wait(bars + B_YS + 8 * (2 * m + wg), 0);
        asm volatile("fence.acq_rel.gpu;" ::: "memory");
        red_relaxed(y_flag(sp, (cta >> 1) & 1, 4 * m + 2 * (cta & 1) + wg));
    }
}

__global__ void __launch_bounds__(384, 1)
main_kernel(const __grid_constant__ CUtensorMap tmx, const __grid_constant__ CUtensorMap tmw0, const __grid_constant__ CUtensorMap tmw1,
            const __nv_bfloat16* __restrict__ x, const __nv_bfloat16* __restrict__ wt, const __nv_bfloat16* __restrict__ gamma,
            const __nv_bfloat16* __restrict__ beta, __nv_bfloat16* __restrict__ out) {
    extern __shared__ __align__(1024) uint8_t smem_raw[];
    const uint32_t sbase = smem_u32(smem_raw) & ~1023u;
    const uint32_t bars = sbase + OFF_BAR;
    const int tid = threadIdx.x, wg = __shfl_sync(0xffffffffu, tid >> 7, 0), lane = tid & 31;
    const int cta = blockIdx.x;
    volatile uint32_t* ts = reinterpret_cast<volatile uint32_t*>(smem_raw + OFF_TS);
    uint8_t* const sp = reinterpret_cast<uint8_t*>((reinterpret_cast<uintptr_t>(g_sp) + (2u << 20) - 1) & ~(uintptr_t)((2u << 20) - 1));
    const bool probing = (cta & 3) == 0 && lane == 0 && tid < 128 && (tid >= 64 || cta < 4 * NPAGES);
    unsigned* pw = reinterpret_cast<unsigned*>(sp + (tid < 64 ? ((cta >> 2) << 21) + ((tid & 32) ? 15 : 13) * 4096
                                                              : ((tid & 32) ? 0 : 14) * 4096 + (cta >> 2) * 128));
    unsigned pv = 0;
    if (probing) {
        stg128(pw, 0, 0, 0, 0);
        stg128(pw + 4, 0, 0, 0, 0);
        asm volatile("atom.relaxed.gpu.global.exch.b32 %0, [%1], %2;" : "=r"(pv) : "l"(pw), "r"(7) : "memory");
    }
    if (tid == 320) bar_setup<0, B_SIG>(bars);
    if (tid >= 256 && tid < 262) ts[68 + tid - 256] = tid < 260 ? 0xffffu : 0;
    if (tid == 383) asm volatile("griddepcontrol.launch_dependents;");
    __syncthreads();

    if (wg == 2) {
        asm volatile("setmaxnreg.dec.sync.aligned.u32 40;");
        const int role = (tid >> 5) & 3;
        if (role == 3) {
            unsigned v = 0;
#pragma unroll 1
            for (uint32_t n = 0; n < (1u << 15); n++) {
                asm volatile("ld.relaxed.gpu.global.u32 %0, [%1];" : "=r"(v) : "l"(&g_tsel[lane]) : "memory");
                if (__all_sync(0xffffffffu, v & 16)) break;
                __nanosleep(TSLEEP);
            }
            const uint32_t m1 = __ballot_sync(0xffffffffu, v & 8), below = (1u << lane) - 1;
            const int rank = (v & 8) ? 32 - __popc(m1) + __popc(m1 & below) : __popc(~m1 & below);
            ts[lane] = rank;
            ts[32 + rank] = lane;
            const uint32_t p0 = __ballot_sync(0xffffffffu, v & 1);
            if (lane == 0) ts[66] = p0;
            if (lane == (cta >> 2)) ts[64] = rank * 4 + (cta & 3);
            const int part = (m1 >> (cta >> 2)) & 1;
            __syncwarp();
            if (lane == 0) mbar_arrive(bars + B_TSEL);
            mbar_wait(bars + B_TSEL, 0);
            mbar_wait(bars + B_PUB, 0);
            int gc = 0;
            const int gend = lane == 0 ? 33 : lane == 1 ? 32 : 0;
#pragma unroll 1
            for (uint32_t n = 0; n < (1u << 16) && __any_sync(0xffffffffu, gc < gend); n++) {
                asm volatile("ld.relaxed.gpu.global.u32 %0, [%1];" : "=r"(v) : "l"(chunk_flag(sp, lane == 1, part, min(gc, 32 - (lane & 1)))) : "memory");
                if (gc < gend && v >= NCTA) {
                    asm volatile("fence.acquire.gpu;" ::: "memory");
                    mbar_arrive(bars + (lane == 0 ? B_RDY : B_GATE) + 8 * gc);
                    gc++;
                }
            }
            if (lane == 0) publish_tiles(sp, bars, cta, 1);
        } else if (role == 0) {
            const int b = (cta >> 1) & 1, dq = cta & 1;
            for (int v = 0; v < V0; v++) {
                mbar_wait(bars + B_EMPTY + 8 * (v % NST), ((v / NST) & 1) ^ 1);
                if (lane == 0) {
                    mbar_arrive(bars + B_FULL + 8 * (v % NST));
                    mbar_arrive(bars + B_FULL + 8 * (v % NST));
                }
            }
            mbar_wait(bars + B_TSEL, 0);
            const uint32_t gr = ts[64], grp = gr >> 6, idx = (gr >> 2) & 15, pmask = ts[66];
            const uint32_t n0 = idx * 4 + 2 * dq + ((lane & 1) ^ 1), r0 = lane < 3 ? idx * 4 + b : R_W + n0 / 3;
            const uint32_t base = (r0 << 16) + 4096 + ((lane < 3 ? lane : n0 % 3) << 14), step = (lane < 3 ? 64 : 22) << 16;
            uint32_t sels = 0;
            for (int i = 0; i < 12; i++) sels |= run_sel(r0 + i * (step >> 16), grp, pmask) << i;
            int ld = 0;
            const uint32_t bytes = lane == 2 ? XB - 16384 : 8192;
#pragma unroll 1
            for (int h = 0; h < 64; h++) {
                const int s = step_k(h), st = (h + V0) % NST;
                const bool newx = h < HEND ? !(h & 1) : h < HEND + 4;
                const uint32_t fb = bars + B_FULL + 8 * st;
                const uint32_t k = lane < 3 ? (s >> 1) % RX : (h + RW - 64 % RW) % RW, half = lane < 3 ? s & 1 : 0;
                const uint8_t* gsrc = sp + (base + k * step + (half << 17) + ((((sels >> k) ^ half) & 1) << 13));
                const uint32_t dst = sbase + (lane < 3 ? OFF_X + (s & 3) * XB + lane * 8192 : st * 8192 + (lane == 3 ? OFF_W0 : OFF_W1));
                auto landed = [&]() {
                    if (ld < h && mbar_test(bars + B_FULL + 8 * ((ld + V0) % NST), ((ld + V0) / NST) & 1)) {
                        if (!(ld & 1) && lane < 2) red_relaxed(chunk_flag(sp, 1, lane, ld >> 1));
                        ld++;
                    }
                };
#pragma unroll 1
                for (uint32_t n = 0; n < (1u << 19) && !mbar_test(bars + B_EMPTY + 8 * st, (((h + V0) / NST) & 1) ^ 1); n++) landed();
#pragma unroll 1
                for (uint32_t n = 0; n < (1u << 19) && ld <= h - NST; n++) landed();
                if (lane == 0) mbar_expect_tx(fb, newx ? 16384 + XB : 16384);
                if ((h & 1) || h == 0) {
#pragma unroll 1
                    for (uint32_t n = 0; n < (1u << 19) && !mbar_test(bars + B_RDY + 8 * ((h + 1) >> 1), 0); n++) landed();
                    asm volatile("fence.proxy.async.global;" ::: "memory");
                }
                __syncwarp();
                if (lane < 3 ? newx : lane < 5) bulk_g2s(dst, gsrc, bytes, fb);
            }
#pragma unroll 1
            for (; ld < 63; ld++) {
                mbar_wait(bars + B_FULL + 8 * ((ld + V0) % NST), ((ld + V0) / NST) & 1);
                if (!(ld & 1) && lane < 2) red_relaxed(chunk_flag(sp, 1, lane, ld >> 1));
            }
            const uint8_t* usrc = sp + y_unit(tail_block(gr, lane / 5), (gr & 31) * 5 + lane % 5, gr >> 6, pmask);
            const uint32_t udst = sbase + (lane < 10 ? OFF_U0 : OFF_U1 - 81920) + lane * 8192, ubar = bars + B_UNIT + 8 * lane;
            if (lane < 20) mbar_expect_tx(ubar, 8192);
            auto tail_loads = [&](int u0, int u1) {
                if (lane >= u0 && lane < u1) bulk_g2s(udst, usrc, 8192, ubar);
                __syncwarp();
            };
            tail_poll(sp, gr, 0);
            mbar_wait(bars + B_T2, 0);
            tail_loads(0, 5);
            tail_poll(sp, gr, 1);
            tail_loads(5, 8);
            mbar_wait(bars + B_YS + 16, 0);
            tail_loads(8, 10);
            mbar_wait(bars + B_T2 + 8, 0);
            if (lane == 0) {
                mbar_expect_tx(bars + B_C1, 2560);
                corr_load(sbase, gr, 2, bars + B_C1);
                corr_load(sbase, gr, 3, bars + B_C1);
            }
            tail_poll(sp, gr, 2);
            tail_loads(10, 15);
            tail_poll(sp, gr, 3);
            tail_loads(15, 20);
            mbar_wait(bars + B_GATE + 8 * 31, 0);
            unsigned exits = 0;
            if (lane == 0) exits = atomicAdd(&g_exit, 1);
            if (__shfl_sync(0xffffffffu, exits, 0) == NCTA - 1) {
                for (int i = 0; i < 4; i++) *chunk_flag(sp, i >> 1, i & 1, lane) = 0;
                if (lane < 2) *chunk_flag(sp, 0, lane, 32) = 0;
                g_tsel[lane] = 0;
                if (lane < 16) *y_flag(sp, lane >> 3, lane & 7) = 0;
                if (lane == 0) { g_exit = 0; g_epoch = ts[76]; }
            }
        } else if (role == 1) {
            auto raw_load = [&](int r, int h, uint32_t gr, uint32_t dst, uint32_t bar) {
                if (r >= 0) {
                    const int u = r * NCTA + cta, i = u % XPC, b = i >= kNT;
                    tma3d(dst, &tmx, u / XPC * 64, (i - b * kNT) * kMO, b, bar);
                } else if (h >= 0) {
                    const int c = 32 * step_k(h) + ((gr >> 1) & 30);
                    tma3d_ef(dst, c < 512 ? &tmw0 : &tmw1, step_m(h) * 256 + (gr & 3) * 64, c & 511, 0, bar);
                }
            };
            uint32_t gr;
            {
                const int v = lane >> 1, r = v < V0 ? x_round(v, lane & 1) : -1, h = v < V0 ? w_step(v, lane & 1) : -1;
                const uint32_t dst = pre_slot(sbase, v, lane & 1), bar = bars + B_PRE + 8 * lane;
                if (r >= 0 || h >= 0) mbar_expect_tx(bar, r >= 0 ? 8192 : 4096);
                if (v < PRE1) raw_load(r, -1, 0, dst, bar);
                mbar_wait(bars + B_TSEL, 0);
                gr = ts[64];
                raw_load(-1, h, gr, dst, bar);
                if (v >= PRE1) raw_load(r, -1, 0, dst, bar);
                __syncwarp();
            }
            mbar_wait(bars + B_PUB, 0);
#pragma unroll 1
            for (int v = V0; v < V0 + 64; v++) {
                mbar_wait(bars + B_EMPTY + 8 * (v % NST), ((v / NST) & 1) ^ 1);
                __syncwarp();
                const int r = lane < 2 ? x_round(v, lane) : -1, h = lane < 2 ? w_step(v, lane) : -1;
                const uint32_t fb = bars + B_FULL + 8 * (v % NST);
                const uint32_t bytes = __reduce_add_sync(0xffffffffu, r >= 0 ? 8192 : h >= 0 ? 4096 : 0);
                if (lane == 0) mbar_expect_tx(fb, bytes);
                __syncwarp();
                raw_load(r, h, gr, raw_slot(sbase, v, lane), fb);
                if (v >= 20 && v < 40) {
                    const int t = (v - 20) / 5, i = (v - 20) % 5 * 32 + lane, db = 4 * (t >> 1) + 2 * (cta & 1) + (t & 1);
                    ts[(OFF_YT - OFF_TS) / 4 + t * kNT + i] = y_unit(db, i, (cta >> 1) & 1, ts[66]);
                }
                if (v == 66 && lane == 0) {
#pragma unroll 1
                    for (uint32_t n = 0; n < (1u << 15); n++) {
                        unsigned c0, c1;
                        asm volatile("ld.relaxed.gpu.global.u32 %0, [%1];" : "=r"(c0) : "l"(&g_cready[(gr >> 6) * 64]) : "memory");
                        asm volatile("ld.relaxed.gpu.global.u32 %0, [%1];" : "=r"(c1) : "l"(&g_cready[(gr >> 6) * 64 + 32]) : "memory");
                        if (c0 == ts[76] && c1 == ts[76]) break;
                        __nanosleep(500);
                    }
                    asm volatile("fence.acquire.gpu;" ::: "memory");
                    asm volatile("fence.proxy.async.global;" ::: "memory");
                    mbar_expect_tx(bars + B_FTAB, 8192 + 2560);
                    bulk_g2s(sbase + OFF_F, g_tab.inv, 8192, bars + B_FTAB);
                    for (int t = 0; t < 2; t++) {
                        corr_load(sbase, gr, t, bars + B_FTAB);
                        asm volatile("cp.async.bulk.prefetch.L2.global [%0], 1280;" ::"l"(corr_src(gr, 2 + t)) : "memory");
                    }
                }
            }
            channel_scales(sbase, smem_raw, sp, lane);
        } else {
            uint32_t epoch;
            if (lane == 0) {
                bar_setup<B_SIG, B_END>(bars);
                mbar_arrive(bars + B_TSEL);
            }
            asm volatile("ld.relaxed.gpu.global.u32 %0, [%1];" : "=r"(epoch) : "l"(&g_epoch) : "memory");
            mbar_wait(bars + B_TSEL, 0);
            const uint32_t gr = ts[64];
#pragma unroll
            for (int i = lane; i < 256; i += 32) {
                const int d = 64 * tail_block(gr, i >> 6) + (i & 33) + 8 * ((i >> 1) & 3) + 2 * ((i >> 3) & 3);
                ts[(OFF_GB - OFF_TS) / 4 + 2 * i] = (uint32_t)__bfloat16_as_ushort(gamma[d]) << 16;
                ts[(OFF_GB - OFF_TS) / 4 + 2 * i + 1] = (uint32_t)__bfloat16_as_ushort(beta[d]) << 16;
            }
            if (lane == 0) ts[76] = epoch + 1;
            if (cta < 32) stg128(part_sums(sp, cta >> 4, (cta >> 1) & 7, epoch) + (cta & 1) * 64 + 2 * lane, 0, 0, 0, 0);
            __syncwarp();
            if (lane) return;
#pragma unroll 1
            for (int gc = 0; gc < 33;) {
                mbar_wait(bars + B_SIG + 8 * gc, 0);
                if (gc < MERGE) mbar_wait(bars + B_SIG + 8 * MERGE, 0);
                int ge = gc + 1;
                while (ge < 33 && mbar_test(bars + B_SIG + 8 * ge, 0)) ge++;
                asm volatile("fence.acq_rel.gpu;" ::: "memory");
                for (; gc < ge; gc++) {
                    red_relaxed(chunk_flag(sp, 0, 0, gc));
                    red_relaxed(chunk_flag(sp, 0, 1, gc));
                    if (gc == 0) mbar_arrive(bars + B_PUB);
                }
            }
            publish_tiles(sp, bars, cta, 0);
        }
    } else {
        asm volatile("setmaxnreg.inc.sync.aligned.u32 232;");
        uint4 fw[2];
#pragma unroll
        for (int j = 0; j < 2; j++) fw[j] = __ldg(reinterpret_cast<const uint4*>(g_tab.fwd) + tid + 256 * j);
        if (wg == 1) {
            uint4 sm[8];
#pragma unroll
            for (int j = 0; j < 4; j++) {
                const int r = 2 * j + ((tid >> 6) & 1);
                sm[j] = __ldg(reinterpret_cast<const uint4*>(x) + ((r >> 2) * kRows + 1000 + 2000 * (r & 3)) * 128 + (((j + r) & 1) << 6) + (tid & 63));
                sm[4 + j] = __ldg(reinterpret_cast<const uint4*>(wt) + (4 * r * 512 + 67 * r + 7) * 64 + (tid & 63));
            }
#pragma unroll
            for (int k = 0; k < 2; k++) {
                uint32_t mx = 0;
#pragma unroll
                for (int j = 4 * k; j < 4 * k + 4; j++)
                    mx = __vmaxu2(__vmaxu2(mx, __vmaxu2(sm[j].x & 0x7FFF7FFFu, sm[j].y & 0x7FFF7FFFu)), __vmaxu2(sm[j].z & 0x7FFF7FFFu, sm[j].w & 0x7FFF7FFFu));
                mx = __reduce_max_sync(0xffffffffu, max(mx & 0xFFFFu, mx >> 16));
                if (lane == 0) atomicMax(const_cast<uint32_t*>(ts) + 72 + k, mx);
            }
        }
        if ((cta & 3) == 0) {
            if (probing) {
                const int w = tid >> 5;
                unsigned best = 0xffffu;
#pragma unroll 1
                for (int r = 0; r < 6; r++) {
                    unsigned t0, t1;
                    asm volatile("{\n.reg .pred p;\nsetp.eq.u32 p, %1, 0xffffffff;\nmov.u32 %0, 0;\n@!p mov.u32 %0, %%clock;\n}"
                                 : "=r"(t0) : "r"(pv) : "memory");
                    asm volatile("atom.relaxed.gpu.global.exch.b32 %0, [%1], %2;" : "=r"(pv) : "l"(pw), "r"(r) : "memory");
                    asm volatile("{\n.reg .pred p;\nsetp.eq.u32 p, %1, 0xffffffff;\nmov.u32 %0, 0;\n@!p mov.u32 %0, %%clock;\n}"
                                 : "=r"(t1) : "r"(pv) : "memory");
                    ts[68 + w] = best = min(best, t1 - t0);
                    const unsigned other = ts[68 + (w ^ 1)];
                    if (min(best, other) < PROBE_NEAR && max(best, other) > PROBE_NEAR) break;
                }
            }
            if (wg == 0) {
                named_bar(2, 128);
                if (tid == 0) {
                    const uint32_t part = ts[71] < ts[70];
                    const uint32_t v = 16 | (part << 3) | ((ts[69] < ts[68]) ^ part);
                    asm volatile("st.relaxed.gpu.global.u32 [%0], %1;" ::"l"(&g_tsel[cta >> 2]), "r"(v) : "memory");
                }
            }
        }
        if (tid < 2 * (V0 + 65)) ts[(OFF_PLAN - OFF_TS) / 4 + tid] = plan_word(tid >> 1, tid & 1, cta);
        {
            named_bar(1, 256);
            const uint32_t ex = min(max(251 - (int)(ts[72] >> 7), 8), 187), ew = min(max(251 - (int)(ts[73] >> 7), 8), 187);
            if (tid == 0) { ts[74] = ex << 23; ts[75] = ew << 23; }
            const uint32_t sx = ex * 0x800080u, sw = ew * 0x800080u;
#pragma unroll
            for (int j = 0; j < 2; j++) {
                const int i = tid + 256 * j, row = i >> 3, c = (i ^ row) & 7;
                sts128(sbase + OFF_F + 16 * i, mul_bf16x2(fw[j].x, sx), mul_bf16x2(fw[j].y, sx), mul_bf16x2(fw[j].z, sx), mul_bf16x2(fw[j].w, sx));
                if (c < 2) sts128(sbase + OFF_TMP + row * 32 + c * 16, mul_bf16x2(fw[j].x, sw), mul_bf16x2(fw[j].y, sw), mul_bf16x2(fw[j].z, sw), mul_bf16x2(fw[j].w, sw));
            }
            fence_proxy_async_smem();
            named_bar(1, 256);
        }
        const int t = tid & 127;
        Xf f;
        f.sbase = sbase; f.lane = lane; f.xsw = cta & 4; f.dw = desc_lo(sbase + (wg ? OFF_W1 : OFF_W0));
        {
            const int w = t >> 5;
            const uint32_t nw = (8 * (w & 1) + (lane >> 2)) * 4 + (cta & 3), rw = R_W + nw / 3;
            f.pw = sp + (rw << 16) + 4096 + ((nw % 3) << 14) + (w >> 1) * 128;
            f.cw = ((lane & 7) ^ (w >> 1)) << 4;
            for (int i = 0; i < RW; i++) f.cw |= run_sel(rw + i * 22, 0, 0) << (8 + i);
            mbar_wait(bars + B_FULL + 8 * (NST - 1), 0);
            mbar_wait(bars + B_TSEL, 0);
            const uint32_t gr = ts[64], pmask = ts[66];
            const uint32_t rx = ts[8 * w + (lane >> 2)];
            f.px = sp + ((rx & 15) << 18) + 4096;
            f.cx = ((lane & 7) << 4) | ((((pmask >> ((rx >> 3) & 1)) ^ -(((rx >> 1) ^ (rx >> 4)) & 1)) & 0x55) << 8);
#pragma unroll
            for (int i = 0; i < RW; i++) f.cw ^= (((pmask >> ((rw + i * 22) >> 5)) ^ (gr >> 6)) & 1) << (8 + i);
            const uint32_t row = ((gr & 12) << 1) | ((gr & 48) >> 3);
            f.pw += row * 128;
            f.cw ^= (row & 7) << 4;
            const uint32_t s = ts[32 + (gr >> 6) * 16 + 8 * (w & 1) + (lane >> 2)], ga = sbase + OFF_TMP + (16 * (s >> 3) + (s & 7)) * 32 + (lane & 3) * 4;
#pragma unroll
            for (int i = 0; i < 4; i++) asm volatile("ld.shared.u32 %0, [%1];" : "=r"(f.g[i]) : "r"(ga + (i & 1) * 256 + (i >> 1) * 16) : "memory");
        }
        {
            float at[32];
#pragma unroll 1
            for (uint32_t v = 0; v < V0; v++) {
                const uint32_t e = plan_load(f, v, wg), raw = pre_slot(sbase, v, wg);
                if (v >= NST) mbar_wait(bars + B_FULL + 8 * (v % NST), (v / NST) & 1);
                if (e & 6) mbar_wait(bars + B_PRE + 16 * v + 8 * wg, 0);
                if (v == PAUSE) mbar_wait(bars + B_PUB, 0);
                wg_fence();
                if ((e & 6) == 2) {
                    unit_mma<false>(at, f, raw);
                    wg_wait<0>();
                    unit_store<false>(at, f, e);
                } else if (e & 4) {
                    unit_mma<true>(at, f, raw);
                    wg_wait<0>();
                    unit_store<true>(at, f, e);
                }
                if (lane == 0) mbar_arrive(bars + B_EMPTY + 8 * (v % NST));
                unit_done(f, e, v);
            }
        }
        const int slot = cta >> 2;
        f.e = plan_load(f, V0, wg);
        uint32_t a0[40], a1[40], b0[40], b1[40];
#pragma unroll
        for (int i = 0; i < 40; i++) a0[i] = a1[i] = b0[i] = b1[i] = 0;
        if (slot == 0) gemm_main<true>(a0, a1, b0, b1, f, wg);
        else gemm_main<false>(a0, a1, b0, b1, f, wg);
        const uint32_t gr = __shfl_sync(0xffffffffu, ts[64], 0);
        const float sx = __uint_as_float(ts[74]), sw = __uint_as_float(ts[75]);
        uint32_t wr[2][4][4];
        w_fetch(wr[0], f, V0 + HEND);
#pragma unroll 1
        for (int m = 0; m < 2; m++) {
            if (slot == 0) gemm_last<true>(a0, a1, wr, f, wg, m);
            else gemm_last<false>(a0, a1, wr, f, wg, m);
            reg_fence(a0);
            reg_fence(a1);
            const int wsw = gr & 4;
            mbar_wait(bars + B_GATE + 8 * y_gate(2 * m + wg), 0);
            if (m) mbar_wait(bars + B_FTAB, 0);
            const uint32_t ytab = sbase + OFF_YT + (m * 2 + wg) * (kNT * 4);
            store_tile(a0, a1, b0, b1, wr[0], f, m == 0, sbase + OFF_STG + wg * 16384, t, wg, sp, slot, ytab, wsw);
            __syncwarp();
            if (lane == 0) mbar_arrive(bars + B_YS + 8 * (2 * m + wg));
        }
        tail_phase(sbase, smem_raw, sp, wg, gr, sx, sw, x, wt, gamma, beta, out);
    }
}

constexpr int C_STAGE = 32768 + 2 * XB, C_SMEM = 3 * C_STAGE + 64;
__global__ void __launch_bounds__(256, 1) corr_kernel(const __grid_constant__ CUtensorMap tmx, const __grid_constant__ CUtensorMap tmw) {
    extern __shared__ __align__(1024) uint8_t smem_raw[];
    const uint32_t sbase = smem_u32(smem_raw) & ~1023u, bars = sbase + 3 * C_STAGE;
    const int tid = threadIdx.x, wg = __shfl_sync(0xffffffffu, tid >> 7, 0), b = blockIdx.x >> 1, dh = blockIdx.x & 1;
    auto load = [&](int k) {
        const uint32_t st = sbase + (k % 3) * C_STAGE, bar = bars + 8 * (k % 3);
        mbar_expect_tx(bar, C_STAGE);
        for (int i = 0; i < 4; i++) tma2d(st + i * 8192, &tmw, 256 * dh + 64 * i, 64 * k, bar);
        tma4d(st + 32768, &tmx, 64 * k, 64 - kMO, 1, b, bar);
        tma4d(st + 32768 + XB, &tmx, 64 * k, 0, 0, b, bar);
    };
    uint32_t epoch = 0;
    if (tid == 0) {
        for (int i = 0; i < 3; i++) mbar_init(bars + 8 * i, 1);
        fence_mbar_init();
        fence_proxy_async_smem();
        for (int k = 0; k < 3; k++) load(k);
        asm volatile("ld.relaxed.gpu.global.u32 %0, [%1];" : "=r"(epoch) : "l"(&g_epoch) : "memory");
    }
    __syncthreads();
    float a[2][80];
#pragma unroll
    for (int i = 0; i < 80; i++) a[0][i] = a[1][i] = 0.f;
#pragma unroll 1
    for (int k = 0; k < 8; k++) {
        const uint32_t dA = desc_lo(sbase + (k % 3) * C_STAGE + wg * 16384), dB = desc_lo(sbase + (k % 3) * C_STAGE + 32768);
        mbar_wait(bars + 8 * (k % 3), (k / 3) & 1);
        wg_fence();
#pragma unroll
        for (int i = 0; i < 8; i++) {
            wgmma_n160_f<1>(a[i & 1], dA + (i & 1) * 512 + (i >> 1) * 128, dB + (i >> 1) * 2);
            wgmma_n160_f<-1>(a[i & 1], dA + (i & 1) * 512 + (i >> 1) * 128, dB + XB / 16 + (i >> 1) * 2);
        }
        wg_commit();
        wg_wait<0>();
        __syncthreads();
        if (tid == 0 && k + 3 < 8) load(k + 3);
    }
    reg_fence(a[0]);
    reg_fence(a[1]);
    const int w = (tid >> 5) & 3, g = (tid & 31) >> 2, q = tid & 3;
    float* stage = reinterpret_cast<float*>(smem_raw);
#pragma unroll
    for (int i = 0; i < 160; i++) {
        const int m = i / 80, j = i % 80, d = 16 * w + 8 * ((j >> 1) & 1) + g;
        stage[((2 * wg + m) * kNT + 8 * (j >> 2) + 2 * q + (j & 1)) * 64 + (d & 33) + 8 * ((d >> 1) & 3) + 2 * ((d >> 3) & 3)] = a[m][j];
    }
    __syncthreads();
    for (int i = tid; i < 4 * kNT * 16; i += 256)
        reinterpret_cast<float4*>(g_corr)[(b * 8 + 4 * dh) * kNT * 16 + i] = reinterpret_cast<const float4*>(stage)[i];
    __syncthreads();
    if (tid == 0) {
        asm volatile("fence.acq_rel.gpu;" ::: "memory");
        asm volatile("st.relaxed.gpu.global.u32 [%0], %1;" ::"l"(&g_cready[blockIdx.x * 32]), "r"(epoch + 1) : "memory");
    }
}

__global__ void __launch_bounds__(256) plain_conv(const __nv_bfloat16* __restrict__ x, const __nv_bfloat16* __restrict__ w) {
    __shared__ float xs[64][17], ws[16][65];
    float* h = g_direct;
    const int b = blockIdx.z, l0 = blockIdx.x * 64, d0 = blockIdx.y * 64, tx = threadIdx.x & 15, ty = threadIdx.x >> 4;
    float acc[4][4] = {};
    for (int k0 = 0; k0 < 31 * 512; k0 += 16) {
        for (int i = threadIdx.x; i < 1024; i += 256) {
            const int l = min(l0 + (i >> 4), kL - 1);
            xs[i >> 4][i & 15] = __bfloat162float(x[((size_t)b * kRows + l) * 1024 + k0 + (i & 15)]);
            ws[i >> 6][i & 63] = __bfloat162float(w[(size_t)(k0 + (i >> 6)) * 512 + d0 + (i & 63)]);
        }
        __syncthreads();
        for (int k = 0; k < 16; k++)
            for (int i = 0; i < 4; i++)
                for (int j = 0; j < 4; j++) acc[i][j] = fmaf(xs[ty * 4 + i][k], ws[k][tx * 4 + j], acc[i][j]);
        __syncthreads();
    }
    for (int i = 0; i < 4; i++)
        for (int j = 0; j < 4; j++)
            if (l0 + ty * 4 + i < kL) h[((size_t)b * kL + l0 + ty * 4 + i) * 512 + d0 + tx * 4 + j] = acc[i][j];
}
__global__ void __launch_bounds__(256) plain_norm(const __nv_bfloat16* __restrict__ gamma, const __nv_bfloat16* __restrict__ beta,
                                                  __nv_bfloat16* __restrict__ out) {
    __shared__ float s1[8][32], s2[8][32];
    const int c = threadIdx.x & 31, r = threadIdx.x >> 5, d = blockIdx.x * 32 + c;
    const float* h = g_direct + (size_t)blockIdx.y * kL * 512 + d;
    float a = 0.f, q = 0.f;
    for (int l = r; l < kL; l += 8) { const float v = h[(size_t)l * 512]; a += v; q = fmaf(v, v, q); }
    s1[r][c] = a; s2[r][c] = q;
    __syncthreads();
    a = q = 0.f;
    for (int i = 0; i < 8; i++) { a += s1[i][c]; q += s2[i][c]; }
    const float mean = a * (1.0f / kL), sc = __bfloat162float(gamma[d]) / sqrtf(fmaxf(q * (1.0f / kL) - mean * mean, 0.f) + 1e-5f);
    const float sh = __bfloat162float(beta[d]) - mean * sc;
    for (int l = r; l < kL; l += 8)
        out[((size_t)blockIdx.y * kL + l) * 512 + d] = __float2bfloat16(gelu_half(0.5f * fmaf(h[(size_t)l * 512], sc, sh)));
}

typedef CUresult (*EncodeTiledFn)(CUtensorMap*, CUtensorMapDataType, cuuint32_t, void*, const cuuint64_t*, const cuuint64_t*,
                                  const cuuint32_t*, const cuuint32_t*, CUtensorMapInterleave, CUtensorMapSwizzle,
                                  CUtensorMapL2promotion, CUtensorMapFloatOOBfill);

void encode(EncodeTiledFn fn, CUtensorMap* tm, const void* ptr, int rank, const cuuint64_t* dims, const cuuint64_t* strides,
            const cuuint32_t* box, CUtensorMapL2promotion promo, CUtensorMapSwizzle swz = CU_TENSOR_MAP_SWIZZLE_128B) {
    const cuuint32_t es[5] = {1, 1, 1, 1, 1};
    fn(tm, CU_TENSOR_MAP_DATA_TYPE_BFLOAT16, rank, const_cast<void*>(ptr), dims, strides, box, es, CU_TENSOR_MAP_INTERLEAVE_NONE,
       swz, promo, CU_TENSOR_MAP_FLOAT_OOB_FILL_NONE);
}

}

extern "C" void kernel_launch(void* const* d_in, const int* in_sizes, int n_in, void* d_out, int out_size) {
    const __nv_bfloat16* x = (const __nv_bfloat16*)d_in[0];
    const __nv_bfloat16* w = (const __nv_bfloat16*)d_in[1];
    const __nv_bfloat16* gamma = (const __nv_bfloat16*)d_in[2];
    const __nv_bfloat16* beta = (const __nv_bfloat16*)d_in[3];
    static EncodeTiledFn enc = nullptr;
    static int resident = 0;
    if (!enc) {
        void* fn = nullptr;
        cudaDriverEntryPointQueryResult qr;
        cudaGetDriverEntryPoint("cuTensorMapEncodeTiled", &fn, cudaEnableDefault, &qr);
        enc = (EncodeTiledFn)fn;
        cudaFuncSetAttribute(main_kernel, cudaFuncAttributeMaxDynamicSharedMemorySize, MAIN_SMEM);
        cudaFuncSetAttribute(corr_kernel, cudaFuncAttributeMaxDynamicSharedMemorySize, C_SMEM);
        int dev = 0, per_sm = 0;
        cudaGetDevice(&dev);
        cudaDeviceGetAttribute(&resident, cudaDevAttrMultiProcessorCount, dev);
        cudaOccupancyMaxActiveBlocksPerMultiprocessor(&per_sm, main_kernel, 384, MAIN_SMEM);
        resident *= per_sm;
    }
    if (resident < NCTA + 4) {
        plain_conv<<<dim3((kL + 63) / 64, 8, 2), 256>>>(x, w);
        plain_norm<<<dim3(16, 2), 256>>>(gamma, beta, (__nv_bfloat16*)d_out);
        return;
    }
    CUtensorMap tmx, tmw0, tmw1, tmcx, tmcw;
    {
        const cuuint64_t dims[3] = {1024, kRows, 2}, strides[2] = {2048, (cuuint64_t)kRows * 2048};
        const cuuint32_t box[3] = {64, 64, 1};
        encode(enc, &tmx, x, 3, dims, strides, box, CU_TENSOR_MAP_L2_PROMOTION_L2_128B);
    }
    {
        const cuuint64_t dims0[3] = {512, 512, 16}, dims1[3] = {512, 512, 15}, strides[2] = {1024, 2 * 512 * 512 * 2};
        const cuuint32_t box[3] = {64, 2, 16};
        encode(enc, &tmw0, w, 3, dims0, strides, box, CU_TENSOR_MAP_L2_PROMOTION_L2_128B);
        encode(enc, &tmw1, w + 512 * 512, 3, dims1, strides, box, CU_TENSOR_MAP_L2_PROMOTION_L2_128B);
    }
    {
        const cuuint64_t dims[4] = {512, kMO, kNT, 2}, strides[3] = {2048, kMO * 2048, (cuuint64_t)kRows * 2048};
        const cuuint32_t box[4] = {64, 1, kNT, 1};
        encode(enc, &tmcx, x, 4, dims, strides, box, CU_TENSOR_MAP_L2_PROMOTION_L2_128B);
        const cuuint64_t dimw[2] = {512, 512}, stridew[1] = {1024};
        const cuuint32_t boxw[2] = {64, 64};
        encode(enc, &tmcw, w + 30 * 512 * 512, 2, dimw, stridew, boxw, CU_TENSOR_MAP_L2_PROMOTION_L2_128B);
    }
    main_kernel<<<NCTA, 384, MAIN_SMEM>>>(tmx, tmw0, tmw1, x, w, gamma, beta, (__nv_bfloat16*)d_out);
    cudaLaunchConfig_t cfg = {};
    cudaLaunchAttribute at[1];
    cfg.gridDim = 4;
    cfg.blockDim = 256;
    cfg.dynamicSmemBytes = C_SMEM;
    at[0].id = cudaLaunchAttributeProgrammaticStreamSerialization;
    at[0].val.programmaticStreamSerializationAllowed = 1;
    cfg.attrs = at;
    cfg.numAttrs = 1;
    cudaLaunchKernelEx(&cfg, corr_kernel, tmcx, tmcw);
}
```

```cpp
#include <cuda_runtime.h>
#include <cuda_bf16.h>
#include <cuda.h>
#include <stdint.h>

namespace {

constexpr int kL    = 7985;
constexpr int kRows = 8000;
constexpr int kMO   = 50;
constexpr int kNT   = 160;

constexpr int V0 = 7;
constexpr int NPRE = 6;
constexpr int RX = 4;
constexpr int PAUSE = 5;
constexpr int YSLEEP = 100;
constexpr int PRE1 = 4;
constexpr int TSLEEP = 200;
constexpr int MERGE = 1;
constexpr int RW = 10;

static_assert(V0 >= 7 && V0 <= 9 && RX >= 2 && RX <= 4 && RW >= V0 - 1 && RW <= 12, "rings must fit and be as deep as the look-ahead");
constexpr uint32_t HOME_MASK = 0xB;
constexpr uint32_t R_W = 64 * RX, NPAGES = (R_W + 22 * RW + 31) / 32;

__device__ __align__(1024) uint8_t g_sp[(size_t)(NPAGES + 1) * (2u << 20)];
__device__ __align__(128) unsigned g_tsel[32];
__device__ __forceinline__ uint32_t run_sel(uint32_t r, uint32_t group, uint32_t pmask) {
    return ((pmask >> (r >> 5)) ^ __popc(r & HOME_MASK) ^ group) & 1;
}
__device__ __forceinline__ uint32_t run_off(uint32_t r, uint32_t run, uint32_t group, uint32_t pmask) {
    return (r << 16) + 4096 + (run_sel(r, group, pmask) << 13) + (run << 14);
}
__device__ __forceinline__ unsigned* chunk_flag(uint8_t* sp, int done, int part, int chunk) {
    return reinterpret_cast<unsigned*>(sp + (4 + 3 * (chunk >> 5)) * 65536 + (done ? (part ? 15 : 13) : (part ? 0 : 14)) * 4096 + (chunk & 31) * 128);
}
__device__ __forceinline__ unsigned long long* part_sums(uint8_t* sp, int b, int db, uint32_t epoch) {
    return reinterpret_cast<unsigned long long*>(sp + (8 + 2 * db + ((__popc((8 + 2 * db) & HOME_MASK) ^ b) & 1)) * 65536 + 13 * 4096 + (epoch & 1) * 1024);
}
__device__ __forceinline__ unsigned* y_flag(uint8_t* sp, int b, int db) { return reinterpret_cast<unsigned*>(part_sums(sp, b, db, 0) + 512); }
__device__ __align__(256) float g_corr[16 * kNT * 64];
__device__ unsigned g_cready[4 * 32];
__device__ float g_direct[512 * 250 * 64];
__device__ unsigned long long g_dpart[2 * 512 * 64];
__device__ unsigned g_exit, g_epoch;

__device__ __forceinline__ uint32_t smem_u32(const void* p) { return (uint32_t)__cvta_generic_to_shared(p); }

__device__ __forceinline__ void mbar_init(uint32_t bar, uint32_t count) {
    asm volatile("mbarrier.init.shared::cta.b64 [%0], %1;" ::"r"(bar), "r"(count) : "memory");
}
__device__ __forceinline__ void mbar_expect_tx(uint32_t bar, uint32_t bytes) {
    asm volatile("mbarrier.arrive.expect_tx.shared::cta.b64 _, [%0], %1;" ::"r"(bar), "r"(bytes) : "memory");
}
__device__ __forceinline__ void mbar_arrive(uint32_t bar) {
    asm volatile("mbarrier.arrive.shared::cta.b64 _, [%0];" ::"r"(bar) : "memory");
}
__device__ __forceinline__ bool mbar_try(uint32_t bar, uint32_t parity) {
    uint32_t ok;
    asm volatile(
        "{\n.reg .pred p;\n"
        "mbarrier.try_wait.parity.shared::cta.b64 p, [%1], %2;\n"
        "selp.u32 %0, 1, 0, p;\n}\n"
        : "=r"(ok) : "r"(bar), "r"(parity) : "memory");
    return ok;
}
__device__ __forceinline__ bool mbar_test(uint32_t bar, uint32_t parity) {
    uint32_t ok;
    asm volatile(
        "{\n.reg .pred p;\n"
        "mbarrier.test_wait.parity.shared::cta.b64 p, [%1], %2;\n"
        "selp.u32 %0, 1, 0, p;\n}\n"
        : "=r"(ok) : "r"(bar), "r"(parity) : "memory");
    return ok;
}
__device__ __forceinline__ void mbar_wait(uint32_t bar, uint32_t parity) {
#pragma unroll 1
    for (uint32_t n = 0; n < (1u << 14); n++)
        if (mbar_try(bar, parity)) break;
}
__device__ __forceinline__ void fence_proxy_async_smem() { asm volatile("fence.proxy.async.shared::cta;" ::: "memory"); }
__device__ __forceinline__ void fence_mbar_init() { asm volatile("fence.mbarrier_init.release.cluster;" ::: "memory"); }

__device__ __forceinline__ void bulk_g2s(uint32_t dst, const void* src, uint32_t bytes, uint32_t bar) {
    asm volatile("cp.async.bulk.shared::cluster.global.mbarrier::complete_tx::bytes [%0], [%1], %2, [%3];"
                 ::"r"(dst), "l"(src), "r"(bytes), "r"(bar) : "memory");
}
__device__ __forceinline__ void tma3d_ef(uint32_t dst, const CUtensorMap* tm, int c0, int c1, int c2, uint32_t bar) {
    asm volatile("{\n.reg .b64 pol;\ncreatepolicy.fractional.L2::evict_first.b64 pol, 1.0;\n"
                 "cp.async.bulk.tensor.3d.shared::cluster.global.mbarrier::complete_tx::bytes.L2::cache_hint [%0], [%1, {%3, %4, %5}], [%2], pol;\n}"
                 ::"r"(dst), "l"(tm), "r"(bar), "r"(c0), "r"(c1), "r"(c2) : "memory");
}
__device__ __forceinline__ void tma3d(uint32_t dst, const CUtensorMap* tm, int c0, int c1, int c2, uint32_t bar) {
    asm volatile("cp.async.bulk.tensor.3d.shared::cluster.global.mbarrier::complete_tx::bytes [%0], [%1, {%3, %4, %5}], [%2];"
                 ::"r"(dst), "l"(tm), "r"(bar), "r"(c0), "r"(c1), "r"(c2) : "memory");
}
__device__ __forceinline__ void red_relaxed(unsigned* p) { asm volatile("red.relaxed.gpu.global.add.u32 [%0], 1;" ::"l"(p) : "memory"); }
__device__ __forceinline__ void named_arrive(int id, int n) { asm volatile("bar.arrive %0, %1;" ::"r"(id), "r"(n) : "memory"); }
__device__ __forceinline__ void named_bar(int id, int n) { asm volatile("bar.sync %0, %1;" ::"r"(id), "r"(n) : "memory"); }

__device__ __forceinline__ void wg_fence() { asm volatile("wgmma.fence.sync.aligned;" ::: "memory"); }
__device__ __forceinline__ void wg_commit() { asm volatile("wgmma.commit_group.sync.aligned;" ::: "memory"); }
template <int N> __device__ __forceinline__ void wg_wait() { asm volatile("wgmma.wait_group.sync.aligned %0;" ::"n"(N) : "memory"); }
template <int N> __device__ __forceinline__ void reg_fence(float (&d)[N]) {
#pragma unroll
    for (int i = 0; i < N; i++) asm volatile("" : "+f"(d[i])::"memory");
}

#define F4(a, i) "+f"(a[i]), "+f"(a[i + 1]), "+f"(a[i + 2]), "+f"(a[i + 3])
#define F8(a, i) F4(a, i), F4(a, i + 4)
#define F16(a, i) F8(a, i), F8(a, i + 8)

constexpr uint32_t HI128 = 0x40000040u, HI64 = 0x80000020u;
__device__ __forceinline__ uint32_t desc_lo(uint32_t addr) { return (addr >> 4) | 0x10000u; }

#define R4(a, i) "+r"(a[i]), "+r"(a[i + 1]), "+r"(a[i + 2]), "+r"(a[i + 3])
#define R8(a, i) R4(a, i), R4(a, i + 4)
template <int N> __device__ __forceinline__ void reg_fence(uint32_t (&d)[N]) {
#pragma unroll
    for (int i = 0; i < N; i++) asm volatile("" : "+r"(d[i])::"memory");
}
__device__ __forceinline__ void tma2d(uint32_t dst, const CUtensorMap* tm, int c0, int c1, uint32_t bar) {
    asm volatile("cp.async.bulk.tensor.2d.shared::cluster.global.mbarrier::complete_tx::bytes [%0], [%1, {%3, %4}], [%2];"
                 ::"r"(dst), "l"(tm), "r"(bar), "r"(c0), "r"(c1) : "memory");
}
__device__ __forceinline__ void tma4d(uint32_t dst, const CUtensorMap* tm, int c0, int c1, int c2, int c3, uint32_t bar) {
    asm volatile("cp.async.bulk.tensor.4d.shared::cluster.global.mbarrier::complete_tx::bytes [%0], [%1, {%3, %4, %5, %6}], [%2];"
                 ::"r"(dst), "l"(tm), "r"(bar), "r"(c0), "r"(c1), "r"(c2), "r"(c3) : "memory");
}

template <int ACC>
__device__ __forceinline__ void wgmma_n64_sps(float (&d)[32], uint32_t da, uint32_t db, uint32_t meta) {
    asm volatile(
        "{\n.reg .pred p;\n.reg .b64 da, db;\nsetp.ne.b32 p, %37, 0;\nmov.b64 da, {%32, %35};\nmov.b64 db, {%33, %36};\n"
        "wgmma.mma_async.sp.sync.aligned.m64n64k32.f32.bf16.bf16 "
        "{%0,%1,%2,%3,%4,%5,%6,%7,%8,%9,%10,%11,%12,%13,%14,%15,%16,%17,%18,%19,%20,%21,%22,%23,%24,%25,%26,%27,%28,%29,%30,%31},"
        "da, db, %34, 0, p, 1, 1, 0, 1;\n}\n"
        : F16(d, 0), F16(d, 16)
        : "r"(da), "r"(db), "r"(meta), "n"(HI64), "n"(HI128), "n"(ACC));
}
__device__ __forceinline__ void wgmma_n64_sp(float (&d)[32], const uint32_t (&a)[4], uint32_t db, uint32_t meta) {
    asm volatile(
        "{\n.reg .pred p;\n.reg .b64 db;\nsetp.ne.b32 p, 0, 0;\nmov.b64 db, {%36, %38};\n"
        "wgmma.mma_async.sp.sync.aligned.m64n64k32.f32.bf16.bf16 "
        "{%0,%1,%2,%3,%4,%5,%6,%7,%8,%9,%10,%11,%12,%13,%14,%15,%16,%17,%18,%19,%20,%21,%22,%23,%24,%25,%26,%27,%28,%29,%30,%31},"
        "{%32,%33,%34,%35}, db, %37, 0, p, 1, 1, 1;\n}\n"
        : F16(d, 0), F16(d, 16)
        : "r"(a[0]), "r"(a[1]), "r"(a[2]), "r"(a[3]), "r"(db), "r"(meta), "n"(HI128));
}

template <int ACC>
__device__ __forceinline__ void wgmma_n56_ss(float (&d)[28], uint32_t da, uint32_t db) {
    asm volatile(
        "{\n.reg .pred p;\n.reg .b64 da, db;\nsetp.ne.b32 p, %31, 0;\nmov.b64 da, {%28, %30};\nmov.b64 db, {%29, %30};\n"
        "wgmma.mma_async.sync.aligned.m64n56k16.f32.f16.f16 "
        "{%0,%1,%2,%3,%4,%5,%6,%7,%8,%9,%10,%11,%12,%13,%14,%15,%16,%17,%18,%19,%20,%21,%22,%23,%24,%25,%26,%27},"
        "da, db, p, 1, 1, 1, 0;\n}\n"
        : F16(d, 0), F8(d, 16), F4(d, 24)
        : "r"(da), "r"(db), "n"(HI128), "n"(ACC));
}

template <int SA>
__device__ __forceinline__ void wgmma_n160_h(uint32_t (&d)[40], uint32_t da, uint32_t db) {
    asm volatile(
        "{\n.reg .pred p;\n.reg .b64 da, db;\nsetp.eq.b32 p, 0, 0;\nmov.b64 da, {%40, %43};\nmov.b64 db, {%41, %43};\n"
        "wgmma.mma_async.sync.aligned.m64n160k16.f16.f16.f16 "
        "{%0,%1,%2,%3,%4,%5,%6,%7,%8,%9,%10,%11,%12,%13,%14,%15,%16,%17,%18,%19,%20,%21,%22,%23,%24,%25,%26,%27,"
        "%28,%29,%30,%31,%32,%33,%34,%35,%36,%37,%38,%39},"
        "da, db, p, %42, 1, 1, 0;\n}\n"
        : R8(d, 0), R8(d, 8), R8(d, 16), R8(d, 24), R8(d, 32)
        : "r"(da), "r"(db), "n"(SA), "n"(HI128));
}
template <int SA>
__device__ __forceinline__ void wgmma_n160_hr(uint32_t (&d)[40], const uint32_t (&a)[4], uint32_t db) {
    asm volatile(
        "{\n.reg .pred p;\n.reg .b64 db;\nsetp.eq.b32 p, 0, 0;\nmov.b64 db, {%44, %46};\n"
        "wgmma.mma_async.sync.aligned.m64n160k16.f16.f16.f16 "
        "{%0,%1,%2,%3,%4,%5,%6,%7,%8,%9,%10,%11,%12,%13,%14,%15,%16,%17,%18,%19,%20,%21,%22,%23,%24,%25,%26,%27,"
        "%28,%29,%30,%31,%32,%33,%34,%35,%36,%37,%38,%39},"
        "{%40,%41,%42,%43}, db, p, %45, 1, 0;\n}\n"
        : R8(d, 0), R8(d, 8), R8(d, 16), R8(d, 24), R8(d, 32)
        : "r"(a[0]), "r"(a[1]), "r"(a[2]), "r"(a[3]), "r"(db), "n"(SA), "n"(HI128));
}
template <int SA>
__device__ __forceinline__ void wgmma_n160_f(float (&d)[80], uint32_t da, uint32_t db) {
    asm volatile(
        "{\n.reg .pred p;\n.reg .b64 da, db;\nsetp.eq.b32 p, 0, 0;\nmov.b64 da, {%80, %83};\nmov.b64 db, {%81, %83};\n"
        "wgmma.mma_async.sync.aligned.m64n160k16.f32.bf16.bf16 "
        "{%0,%1,%2,%3,%4,%5,%6,%7,%8,%9,%10,%11,%12,%13,%14,%15,%16,%17,%18,%19,%20,%21,%22,%23,%24,%25,%26,%27,"
        "%28,%29,%30,%31,%32,%33,%34,%35,%36,%37,%38,%39,%40,%41,%42,%43,%44,%45,%46,%47,%48,%49,%50,%51,%52,%53,%54,%55,"
        "%56,%57,%58,%59,%60,%61,%62,%63,%64,%65,%66,%67,%68,%69,%70,%71,%72,%73,%74,%75,%76,%77,%78,%79},"
        "da, db, p, %82, 1, 1, 0;\n}\n"
        : F16(d, 0), F16(d, 16), F16(d, 32), F16(d, 48), F16(d, 64)
        : "r"(da), "r"(db), "n"(SA), "n"(HI128));
}

__device__ __forceinline__ uint32_t pack_f16(float lo, float hi) {
    uint32_t r;
    asm("cvt.rn.f16x2.f32 %0, %1, %2;" : "=r"(r) : "f"(hi), "f"(lo));
    return r;
}
__device__ __forceinline__ uint32_t mul_bf16x2(uint32_t a, uint32_t b) {
    uint32_t r;
    asm("mul.rn.bf16x2 %0, %1, %2;" : "=r"(r) : "r"(a), "r"(b));
    return r;
}
__device__ __forceinline__ void sts128(uint32_t p, uint32_t a, uint32_t b, uint32_t c, uint32_t d) {
    asm volatile("st.shared.v4.b32 [%0], {%1,%2,%3,%4};" ::"r"(p), "r"(a), "r"(b), "r"(c), "r"(d) : "memory");
}
__device__ __forceinline__ uint32_t pack_bf16(float lo, float hi) {
    uint32_t r;
    asm("cvt.rn.bf16x2.f32 %0, %1, %2;" : "=r"(r) : "f"(hi), "f"(lo));
    return r;
}
__device__ __forceinline__ void stg128(void* p, uint32_t a, uint32_t b, uint32_t c, uint32_t d) {
    asm volatile("st.global.v4.b32 [%0], {%1,%2,%3,%4};" ::"l"(p), "r"(a), "r"(b), "r"(c), "r"(d) : "memory");
}
__device__ __forceinline__ void stmatrix_x4_t(uint32_t addr, uint32_t a, uint32_t b, uint32_t c, uint32_t d) {
    asm volatile("stmatrix.sync.aligned.m8n8.x4.trans.shared.b16 [%0], {%1,%2,%3,%4};"
                 ::"r"(addr), "r"(a), "r"(b), "r"(c), "r"(d) : "memory");
}

constexpr uint32_t cos64(int k, bool half) {
    constexpr uint16_t q[17] = {0x3F80, 0x3F7F, 0x3F7B, 0x3F75, 0x3F6D, 0x3F62, 0x3F55, 0x3F46, 0x3F35, 0x3F22, 0x3F0E, 0x3EF1, 0x3EC4, 0x3E95, 0x3E48, 0x3DC9, 0x0000};
    constexpr uint16_t h[17] = {0x3C00, 0x3BF6, 0x3BD9, 0x3BA8, 0x3B64, 0x3B0E, 0x3AA7, 0x3A2F, 0x39A8, 0x3913, 0x3872, 0x378B, 0x361F, 0x34A5, 0x323E, 0x2E46, 0x0000};
    k &= 63;
    if (k > 32) k = 64 - k;
    const uint16_t* t = half ? h : q;
    return k <= 16 ? t[k] : (t[32 - k] | 0x8000u);
}
constexpr int freq(int s) { return s <= 16 ? s : 64 - s; }
constexpr uint32_t tap_coef(int s, int p, int t) { return (p && s == 0) ? cos64(32 * t, false) : cos64(freq(s) * t - 16 * p, false); }
constexpr uint32_t x_coef(int s, int p, int t) { return s ? cos64(s * t - 16 * p, false) : p ? cos64(16 * t + 16 * (t & 1), false) : cos64(0, false); }
constexpr uint32_t inv_coef(int l, int phi) {
    const int s = phi >> 1, p = phi & 1;
    if (l >= kMO) return 0;
    if (s == 16) return (0x3C00u - (6 << 10)) | ((((l + 1 - p) >> 1) ^ p) & 1) << 15;
    const uint32_t c = s == 0 ? cos64(32 * l * p, true) : cos64(freq(s) * l + 16 * p, true);
    return (c & 0x7FFF) ? c - ((s == 0 ? 6 : 5) << 10) : 0;
}
struct Tables {
    uint32_t fx[1024];
    uint32_t tap[512];
    uint32_t inv[2048];
};
constexpr Tables make_tables() {
    Tables t = {};
    for (int i = 0; i < 1024; i++) {
        const int row = i >> 4, j = 8 * (((i >> 2) & 3) ^ ((row >> 1) & 3)) + 2 * (i & 3), s = 4 * (row >> 4) + ((row & 7) >> 1), h = (row >> 3) & 1;
        t.fx[i] = x_coef(s, row & 1, 2 * j + h) | (x_coef(s, row & 1, 2 * j + 2 + h) << 16);
    }
    for (int i = 0; i < 512; i++) {
        const int row = i >> 3, s = 8 * (row >> 4) + (row & 7), p = (row >> 3) & 1;
        t.tap[i] = tap_coef(s, p, 2 * (i & 7)) | (tap_coef(s, p, 2 * (i & 7) + 1) << 16);
    }
    for (int i = 0; i < 2048; i++) {
        const int row = i >> 5, tt = 8 * (((i >> 2) & 7) ^ (row & 7)) + 2 * (i & 3);
        t.inv[i] = inv_coef(row, tt) | (inv_coef(row, tt + 1) << 16);
    }
    return t;
}
__device__ __align__(128) const Tables g_tab = make_tables();

constexpr int NCTA = 128;
constexpr int NST = 4;
constexpr int HEND = 56;
constexpr int XB = kNT * 128;
constexpr int OFF_W1 = 0, OFF_X = OFF_W1 + NST * 8192, OFF_W0 = OFF_X + 4 * XB, OFF_RAW = OFF_W0 + NST * 8192;
constexpr int OFF_STG = OFF_RAW + 32768;
constexpr int OFF_U0 = OFF_W0, OFF_U1 = OFF_X, OFF_C1 = OFF_W1, OFF_DIR = OFF_W1 + 8192;
constexpr int OFF_F = OFF_RAW + 65536;
constexpr int OFF_C0 = OFF_F + 8192;
constexpr int OFF_TMP = OFF_C0, OFF_BAR = OFF_C0 + 4096;
constexpr int B_FULL = 0, B_EMPTY = 8 * NST, B_TSEL = 16 * NST, B_PRE = B_TSEL + 8, B_SIG = B_PRE + 16 * V0, B_YS = B_SIG + 8 * 33,
              B_T2 = B_YS + 8 * 4, B_SUM = B_T2 + 16, B_GATE = B_SUM + 32, B_RDY = B_GATE + 8 * 32, B_PUB = B_RDY + 8 * 33, B_UNIT = B_PUB + 8,
              B_FTAB = B_UNIT + 8 * 20, B_C1 = B_FTAB + 8, B_NRM = B_C1 + 8, B_END = B_NRM + 32;
template <int O0, int O1>
__device__ __forceinline__ void bar_setup(uint32_t bars) {
#pragma unroll
    for (int o = O0; o < O1; o += 8)
        mbar_init(bars + o, o < B_EMPTY ? 2 : o < B_TSEL ? 8 : o == B_TSEL ? 2 : o < B_SIG ? 1 : o < B_YS - 8 ? 8 : o < B_GATE ? 4 : 1);
    fence_mbar_init();
    fence_proxy_async_smem();
}
constexpr int OFF_TS = OFF_BAR + B_END;
constexpr int OFF_PLAN = OFF_TS + 336;
constexpr int OFF_YT = OFF_PLAN + (V0 + 65) * 8;
constexpr int OFF_GB = (OFF_YT + 4 * kNT * 4 + 15) & ~15;
constexpr int MAIN_SMEM = OFF_GB + 2048;
static_assert(MAIN_SMEM <= 232448 && OFF_U0 + 10 * 8192 == OFF_STG + 16384, "shared memory");
constexpr int XPC = 2 * kNT;
constexpr unsigned PROBE_NEAR = 400;

__device__ __forceinline__ uint32_t raw_slot(uint32_t sbase, uint32_t v, int wg) { return sbase + OFF_RAW + ((v & 3) * 2 + wg) * 8192; }

__device__ __forceinline__ uint32_t pre_slot(uint32_t sbase, uint32_t v, int wg) {
    return v < 4 ? raw_slot(sbase, v, wg) : v < 8 ? sbase + OFF_X + (v - 4) * XB + wg * 8192 : sbase + (wg ? OFF_W1 : OFF_W0) + ((V0 + 3) % NST) * 8192;
}

template <bool DC, int I>
__device__ __forceinline__ void gemm_mma(uint32_t (&a0)[40], uint32_t (&a1)[40], uint32_t dx0, uint32_t dx1, uint32_t dw) {
    constexpr int ks = I >> 2;
    const uint32_t A0 = dw + ks * 128, A1 = A0 + 256, B0 = dx0 + ks * 2, B1 = dx1 + ks * 2;
    if ((I & 3) == 0) wgmma_n160_h<1>(a0, A0, B0);
    if ((I & 3) == 1) wgmma_n160_h<1>(a1, A1, DC ? B1 : B0);
    if ((I & 3) == 2 && !DC) wgmma_n160_h<1>(a0, A1, B1);
    if ((I & 3) == 3 && !DC) wgmma_n160_h<-1>(a1, A0, B1);
}

template <bool DC, int I0, int I1>
__device__ __forceinline__ void gemm_mmas(uint32_t (&a0)[40], uint32_t (&a1)[40], uint32_t dx0, uint32_t dx1, uint32_t dw) {
    if constexpr (I0 < I1) {
        gemm_mma<DC, I0>(a0, a1, dx0, dx1, dw);
        gemm_mmas<DC, I0 + 1, I1>(a0, a1, dx0, dx1, dw);
    }
}
static_assert(RX == 4 && RW == 10, "placement of the output spectra");
__device__ __forceinline__ uint32_t y_unit(uint32_t db, uint32_t tau, uint32_t b, uint32_t pmask) {
    const uint32_t n = (((db >> 1) & 2) + (db & 1)) * XPC + ((db >> 1) & 1) * kNT + tau, r = n / 3;
    return run_off(r + (r >= 192 && r < 278 ? (r < 214 ? 64 : -22) : 0), n % 3, b, pmask);
}
__device__ __forceinline__ int y_gate(int t) { return t ? 28 + t : 27; }
__device__ __forceinline__ int step_k(int h) { return h < HEND ? h >> 1 : 28 + (h & 3); }
__device__ __forceinline__ int step_m(int h) { return h < HEND ? h & 1 : (h >> 2) & 1; }
constexpr uint64_t x_mask() {
    uint64_t r = 2 | (3ull << 58);
    for (int v = 2; v < 58; v++)
        if ((0x73 >> (v & 7)) & 1) r |= 1ull << v;
    return r;
}
constexpr uint64_t XMASK = x_mask();
__device__ __forceinline__ int x_round(int v, int wg) {
    return v == 0 ? wg : (v < 60 && wg != (v & 1) && ((XMASK >> v) & 1)) ? 1 + __popcll(XMASK << (63 - v)) : -1;
}
__device__ __forceinline__ int w_step(int v, int wg) {
    return v == 0 ? -1 : v < 60 ? (wg == (v & 1) ? v - 1 : -1) : v < 62 ? 2 * v - 61 + wg : (v == 62 && wg == 1) ? 63 : -1;
}

__device__ __forceinline__ uint32_t plan_word(int v, int wg, int cta) {
    const int r = x_round(v, wg), h = w_step(v, wg);
    if (r < 0 && h < 0) return 0;
    const bool last = v >= 60 || (v & 1) || (v > 0 && wg == 0 && x_round(v + 1, 0) < 0);
    uint32_t off, row, gate;
    if (r >= 0) {
        const int u = r * NCTA + cta, cb = u / XPC, i = u - cb * XPC, b = i >= kNT, tau = i - b * kNT;
        row = tau & 63;
        off = (((cb % RX) * 64 + b) << 16) + ((tau >> 6) << 14) + b + 2;
        gate = cb >= RX ? 2 * (cb - RX) + 2 : 0;
    } else {
        const int ring = (h + RW - 64 % RW) % RW;
        row = 0;
        off = ((ring * 22) << 16) + (ring << 12) + 4;
        gate = h >= RW ? ((h - RW + 1) >> 1) + 1 : 0;
    }
    return (off + row * 128) | ((row & 7) << 4) | (last << 3) | ((v > 60) << 24) | (gate << 26);
}

struct Xf {
    uint32_t sbase;
    uint8_t *px[2], *pw;
    uint32_t cx[2], cw;
    uint32_t g[4];
    uint32_t dw;
    uint32_t e;
    int lane;
};
__device__ __forceinline__ uint32_t plan_load(const Xf& f, uint32_t v, int wg) {
    uint32_t e;
    asm volatile("ld.shared.u32 %0, [%1];" : "=r"(e) : "r"(f.sbase + OFF_PLAN + v * 8 + wg * 4));
    return __shfl_sync(0xffffffffu, e, 0);
}
template <bool W>
__device__ __forceinline__ void unit_mma(float (&acc)[32], const Xf& f, uint32_t raw) {
    const uint32_t dB = desc_lo(raw);
    if (W) {
        wgmma_n64_sp(acc, f.g, dB, threadIdx.x & 64 ? 0xDDDDDDDDu : 0x88888888u);
    } else {
        const uint32_t dF = desc_lo(f.sbase + OFF_F);
        wgmma_n64_sps<0>(acc, dF, dB, 0xDDDD8888u);
        wgmma_n64_sps<1>(acc, dF + 2, dB + 256, 0xDDDD8888u);
    }
    wg_commit();
}
constexpr int DROP = 3;
__device__ __forceinline__ uint32_t pack_sp(float lo, float hi) {
    const uint32_t r = pack_f16(lo, hi);
    return DROP ? (r + (0x10001u << DROP >> 1)) & ~(((1u << DROP) - 1) * 0x10001u) : r;
}
__device__ __forceinline__ void st_quad(uint8_t* p, const float (&acc)[32], int j0) {
    stg128(p, pack_sp(acc[j0], acc[j0 + 1]), pack_sp(acc[j0 + 4], acc[j0 + 5]), pack_sp(acc[j0 + 8], acc[j0 + 9]),
           pack_sp(acc[j0 + 12], acc[j0 + 13]));
}
template <bool W>
__device__ __forceinline__ void unit_store(float (&acc)[32], const Xf& f, uint32_t e) {
    if (W) {
        const uint32_t o = (e & 0xFF0F80u) + ((e ^ f.cw) & 0x70) + (((f.cw >> (8 + ((e >> 12) & 15))) & 1) << 13);
        uint8_t *p0 = f.pw + o, *p1 = f.pw + (o ^ 64);
        reg_fence(acc);
        st_quad(p0, acc, 0);
        st_quad(p1, acc, 16);
        st_quad(p0 + 4096, acc, 2);
        st_quad(p1 + 4096, acc, 18);
    } else {
        uint8_t* p[2][2];
#pragma unroll
        for (int i = 0; i < 2; i++) {
            const uint32_t sel = ((e ^ (f.cx[i] >> (8 + ((e >> 21) & 6)))) & 1) << 13, o = (e & 0xFFFF80u) + ((e ^ f.cx[i]) & 0x70);
            p[i][0] = f.px[i] + (o + sel);
            p[i][1] = f.px[i] + (o + 131072 + 8192 - sel);
        }
        reg_fence(acc);
#pragma unroll
        for (int i = 0; i < 32; i++)
            if (!(i & 2)) {
                const float ev = acc[i], od = acc[i + 2];
                acc[i] = ev + od;
                acc[i + 2] = ev - od;
            }
        st_quad(p[0][0], acc, 0);
        st_quad(p[1][0], acc, 2);
        st_quad(p[0][1], acc, 16);
        st_quad(p[1][1], acc, 18);
    }
}
__device__ __forceinline__ void unit_done(const Xf& f, uint32_t e, uint32_t v) {
    if (e & 8) {
        __syncwarp();
        if (f.lane == 0) mbar_arrive(f.sbase + OFF_BAR + B_SIG + 8 * ((v >> 1) + ((e >> 24) & 1)));
    }
}
__device__ __forceinline__ void step_wait(Xf& f, uint32_t v, int wg) {
    const uint32_t bars = f.sbase + OFF_BAR;
    mbar_wait(bars + B_FULL + 8 * (v % NST), (v / NST) & 1);
}

template <bool DC, int KIND>
__device__ __forceinline__ void gemm_step(uint32_t (&a0)[40], uint32_t (&a1)[40], float (&at)[32], Xf& f, uint32_t v, uint32_t xs, int wg, bool first) {
    const uint32_t bars = f.sbase + OFF_BAR, sb = desc_lo(f.sbase), xb = sb + OFF_X / 16 + xs * (XB / 16), raw = raw_slot(f.sbase, v, wg);
    const uint32_t dx0 = xb, dx1 = xb + 4, dw = f.dw + (v % NST) * 512, e = f.e;
    wg_fence();
    if (KIND) unit_mma<KIND != 1>(at, f, raw);
    constexpr int N1 = KIND == 0 ? 2 : NPRE;
    gemm_mmas<DC, 0, N1>(a0, a1, dx0, dx1, dw);
    wg_commit();
    const uint32_t gate = bars + ((e >> 26) ? B_GATE - 8 + 8 * (e >> 26) : B_PUB);
    const bool open = !KIND || mbar_test(gate, 0);
    f.e = plan_load(f, v + 1, wg);
    wg_wait<1>();
    if (!open) mbar_wait(gate, 0);
    if (!KIND && !first && f.lane == 0) mbar_arrive(bars + B_EMPTY + 8 * ((v - 1) % NST));
    if (KIND) unit_store<KIND != 1>(at, f, e);
    if (KIND) unit_done(f, e, v);
    gemm_mmas<DC, N1, 7>(a0, a1, dx0, dx1, dw);
    if (KIND && !first && f.lane == 0) mbar_arrive(bars + B_EMPTY + 8 * ((v - 1) % NST));
    gemm_mma<DC, 7>(a0, a1, dx0, dx1, dw);
    wg_commit();
}
template <bool DC>
__device__ __forceinline__ void any_step(uint32_t (&a0)[40], uint32_t (&a1)[40], float (&at)[32], Xf& f, uint32_t v, uint32_t xs, int wg, bool first) {
    step_wait(f, v, wg);
    const uint32_t kind = (f.e >> 1) & 3;
    if (kind == 1) gemm_step<DC, 1>(a0, a1, at, f, v, xs, wg, first);
    else if (kind == 2) gemm_step<DC, 2>(a0, a1, at, f, v, xs, wg, first);
    else gemm_step<DC, 0>(a0, a1, at, f, v, xs, wg, first);
}
template <bool DC>
__device__ __forceinline__ void gemm_main(uint32_t (&a0)[40], uint32_t (&a1)[40], uint32_t (&b0)[40], uint32_t (&b1)[40], Xf& f, int wg) {
    float at[32];
#pragma unroll 1
    for (uint32_t k = 0; k < HEND / 2; k++) {
        any_step<DC>(a0, a1, at, f, V0 + 2 * k, k & 3, wg, k == 0);
        any_step<DC>(b0, b1, at, f, V0 + 2 * k + 1, k & 3, wg, false);
    }
    wg_wait<0>();
    if (f.lane == 0) mbar_arrive(f.sbase + OFF_BAR + B_EMPTY + 8 * ((V0 + HEND - 1) % NST));
}
__device__ __forceinline__ void w_fetch(uint32_t (&d)[4][4], const Xf& f, uint32_t v) {
    const uint32_t bars = f.sbase + OFF_BAR, lane = f.lane;
    const uint32_t wa = ((f.dw & 0xFFFF) << 4) + (v % NST) * 8192 + (lane >> 4) * 1024 + (lane & 7) * 128 +
                        (((((threadIdx.x >> 4) & 6) + ((lane >> 3) & 1)) ^ (lane & 7)) << 4);
    mbar_wait(bars + B_FULL + 8 * (v % NST), (v / NST) & 1);
#pragma unroll
    for (int i = 0; i < 4; i++)
        asm volatile("ldmatrix.sync.aligned.m8n8.x4.trans.shared.b16 {%0,%1,%2,%3}, [%4];" : "=r"(d[i][0]), "=r"(d[i][1]), "=r"(d[i][2]), "=r"(d[i][3])
                     : "r"(wa + i * 2048) : "memory");
}
__device__ __forceinline__ void store_tile(uint32_t (&a0)[40], uint32_t (&a1)[40], const uint32_t (&b0)[40], const uint32_t (&b1)[40], uint32_t (&wn)[4][4],
                                           const Xf& f, bool first, uint32_t stg, int t, int wg, uint8_t* sp, int slot, uint32_t ytab, int wsw) {
    const int w = t >> 5, lane = t & 31, m = lane >> 3, i8 = lane & 7;
    const uint32_t addr = stg + i8 * 256 + (m >> 1) * 128 + (((2 * w + (m & 1)) ^ i8 ^ wsw) << 4);
    const int row = 2 * w + (lane >> 4), phi = 2 * slot + (m & 1);
    const uint32_t src = stg + row * 256 + (m & 1) * 128 + ((i8 ^ row) << 4);
    uint8_t* dst = sp + phi * 128 + ((i8 ^ (phi & 7)) << 4);
    named_bar(2 + wg, 128);
#pragma unroll
    for (int r = 0; r < 6; r++) {
        uint32_t v[4][4], o[4];
        if (r > 0) {
#pragma unroll
            for (int i = 0; i < 4; i++) {
                asm volatile("ld.shared.u32 %0, [%1];" : "=r"(o[i]) : "r"(ytab + (32 * (r - 1) + 8 * i + row) * 4) : "memory");
                asm volatile("ld.shared.v4.b32 {%0,%1,%2,%3}, [%4];" : "=r"(v[i][0]), "=r"(v[i][1]), "=r"(v[i][2]), "=r"(v[i][3])
                             : "r"(src + ((r - 1) & 1) * 8192 + i * 2048) : "memory");
            }
        }
        if (r < 5) {
#pragma unroll
            for (int j = 4 * r; j < 4 * r + 4; j++) stmatrix_x4_t(addr + (r & 1) * 8192 + (j & 3) * 2048, a0[2 * j], a0[2 * j + 1], a1[2 * j], a1[2 * j + 1]);
#pragma unroll
            for (int j = 8 * r; j < 8 * r + 8; j++) {
                asm volatile("mov.b32 %0, %1;" : "=r"(a0[j]) : "r"(b0[j]));
                asm volatile("mov.b32 %0, %1;" : "=r"(a1[j]) : "r"(b1[j]));
            }
        } else if (first) {
            w_fetch(wn, f, V0 + HEND + 4);
        }
        if (r > 0) {
#pragma unroll
            for (int i = 0; i < 4; i++) stg128(dst + o[i], v[i][0], v[i][1], v[i][2], v[i][3]);
        }
        if (r < 5) named_bar(2 + wg, 128);
    }
}

template <bool DC>
__device__ __forceinline__ void gemm_last(uint32_t (&a0)[40], uint32_t (&a1)[40], uint32_t (&w)[2][4][4], const Xf& f, int wg, int m) {
    const uint32_t bars = f.sbase + OFF_BAR, sb = desc_lo(f.sbase), v0 = V0 + HEND + 4 * m;
    if (2 * m + wg > 0) named_bar(3 + 2 * m + wg, 256);
#pragma unroll
    for (uint32_t k = 0; k < 4; k++) {
        const uint32_t dx0 = sb + OFF_X / 16 + k * (XB / 16), dx1 = dx0 + 4;
        wg_fence();
#pragma unroll
        for (int ks = 0; ks < 2; ks++) {
            wgmma_n160_hr<1>(a0, w[k & 1][ks], dx0 + 2 * ks);
            wgmma_n160_hr<1>(a1, w[k & 1][2 + ks], (DC ? dx1 : dx0) + 2 * ks);
            if (!DC) wgmma_n160_hr<1>(a0, w[k & 1][2 + ks], dx1 + 2 * ks);
            if (!DC) wgmma_n160_hr<-1>(a1, w[k & 1][ks], dx1 + 2 * ks);
        }
        wg_commit();
        if (m == 0 && f.lane == 0) mbar_arrive(bars + B_EMPTY + 8 * ((v0 + k) % NST));
        if (k == 3 && 2 * m + wg < 3) named_arrive(4 + 2 * m + wg, 256);
        if (k > 0) wg_wait<1>();
        if (k < 3) w_fetch(w[(k + 1) & 1], f, v0 + k + 1);
    }
    wg_wait<0>();
    if (m && f.lane == 0) mbar_arrive(bars + B_T2 + 8 * wg);
}

__device__ __forceinline__ float gelu_half(float hv) {
    float th;
    asm("tanh.approx.f32 %0, %1;" : "=f"(th) : "f"(hv * fmaf(hv * hv, 8.0f * 0.7978845608028654f * 0.044715f, 2.0f * 0.7978845608028654f)));
    return fmaf(hv, th, hv);
}
__device__ __noinline__ void direct_block(const __nv_bfloat16* __restrict__ x, const __nv_bfloat16* __restrict__ w,
                                          const __nv_bfloat16* __restrict__ gamma, const __nv_bfloat16* __restrict__ beta,
                                          __nv_bfloat16* __restrict__ out, float* sm, int b, int db, int part, uint32_t epoch) {
    float *xs = sm, *ws = sm + 32 * 17, *red = ws + 16 * 65;
    const int tid = threadIdx.x & 127, bar = 2 + (threadIdx.x >> 7), tx = tid & 15, ty = tid >> 4, row0 = part * 250, lim = min(250, kL - row0);
    float* h = g_direct + (size_t)((b * 8 + db) * 32 + part) * (250 * 64);
    for (int l0 = 0; l0 < lim; l0 += 32) {
        float acc[4][4] = {};
        for (int k0 = 0; k0 < 31 * 512; k0 += 16) {
            named_bar(bar, 128);
            for (int i = tid; i < 1024; i += 128) {
                if (i < 512) xs[(i >> 4) * 17 + (i & 15)] = __bfloat162float(x[((size_t)b * kRows + row0 + min(l0 + (i >> 4), lim - 1)) * 1024 + k0 + (i & 15)]);
                ws[(i >> 6) * 65 + (i & 63)] = __bfloat162float(w[(size_t)(k0 + (i >> 6)) * 512 + 64 * db + (i & 63)]);
            }
            named_bar(bar, 128);
            for (int k = 0; k < 16; k++)
#pragma unroll
                for (int i = 0; i < 4; i++)
#pragma unroll
                    for (int j = 0; j < 4; j++) acc[i][j] = fmaf(xs[(ty * 4 + i) * 17 + k], ws[k * 65 + tx * 4 + j], acc[i][j]);
        }
#pragma unroll
        for (int i = 0; i < 4; i++)
#pragma unroll
            for (int j = 0; j < 4; j++)
                if (l0 + ty * 4 + i < lim) h[(l0 + ty * 4 + i) * 64 + tx * 4 + j] = acc[i][j];
    }
    const int c = tid & 63;
    float mean = 0.f, var = 0.f;
    for (int r = 0; r < 2; r++) {
        named_bar(bar, 128);
        float s = 0.f;
        for (int l = tid >> 6; l < lim; l += 2) {
            const float v = h[l * 64 + c] - mean;
            s += r ? v * v : v;
        }
        red[tid] = s;
        named_bar(bar, 128);
        unsigned long long* p = g_dpart + ((r * 16 + b * 8 + db) * 32) * 64 + c;
        if (tid < 64)
            asm volatile("st.relaxed.gpu.global.v2.b32 [%0], {%1, %2};" ::"l"(p + part * 64), "r"(__float_as_uint(red[c] + red[64 + c])), "r"(epoch) : "memory");
        s = 0.f;
        for (int k = 0; k < 32; k++) {
            unsigned long long v = 0;
#pragma unroll 1
            for (uint32_t n = 0; n < (1u << 19); n++) {
                asm volatile("ld.relaxed.gpu.global.u64 %0, [%1];" : "=l"(v) : "l"(p + k * 64) : "memory");
                if ((uint32_t)(v >> 32) == epoch) break;
                __nanosleep(200);
            }
            s += __uint_as_float((uint32_t)v);
        }
        (r ? var : mean) = s * (1.0f / kL);
    }
    const float a = __bfloat162float(gamma[64 * db + c]) / sqrtf(var + 1e-5f), be = __bfloat162float(beta[64 * db + c]);
    for (int l = tid >> 6; l < lim; l += 2)
        out[((size_t)b * kL + row0 + l) * 512 + 64 * db + c] = __float2bfloat16(gelu_half(0.5f * fmaf(h[l * 64 + c] - mean, a, be)));
    named_bar(bar, 128);
}

__device__ __forceinline__ int tail_block(uint32_t gr, int t) { return 4 * (t >> 1) + ((gr >> 4) & 2) + (t & 1); }
__device__ __forceinline__ void tail_poll(uint8_t* sp, uint32_t gr, int t) {
#pragma unroll 1
    for (uint32_t n = 0; n < (1u << 15); n++) {
        unsigned v;
        asm volatile("ld.relaxed.gpu.global.u32 %0, [%1];" : "=r"(v) : "l"(y_flag(sp, gr >> 6, tail_block(gr, t))) : "memory");
        if (v >= 32) break;
        __nanosleep(YSLEEP);
    }
    asm volatile("fence.acquire.gpu;" ::: "memory");
    asm volatile("fence.proxy.async.global;" ::: "memory");
}
__device__ __forceinline__ const float* corr_src(uint32_t gr, int t) { return &g_corr[(((gr >> 6) * 8 + tail_block(gr, t)) * kNT + (gr & 31) * 5) * 64]; }
__device__ __forceinline__ void corr_load(uint32_t sbase, uint32_t gr, int t, uint32_t bar) {
    bulk_g2s(sbase + (t < 2 ? OFF_C0 : OFF_C1) + (t & 1) * 1280, corr_src(gr, t), 1280, bar);
}
__device__ __forceinline__ void tail_phase(uint32_t sbase, uint8_t* smem, uint8_t* sp, int wg, uint32_t gr, float sx, float sw, const __nv_bfloat16* __restrict__ x,
                                           const __nv_bfloat16* __restrict__ wt, const __nv_bfloat16* __restrict__ gamma,
                                           const __nv_bfloat16* __restrict__ beta, __nv_bfloat16* __restrict__ out) {
    const uint32_t* ts = reinterpret_cast<const uint32_t*>(smem + OFF_TS);
    const int tid = threadIdx.x, w = (tid >> 5) & 3, lane = tid & 31, g = lane >> 2, q = lane & 3;
    const int b = gr >> 6, part = gr & 31;
#pragma unroll 1
    for (int rd = 0; rd < 3; rd++) {
        if (rd < 2) {
            float acc[28], acc2[28], s[8] = {0.f, 0.f, 0.f, 0.f, 0.f, 0.f, 0.f, 0.f};
            const float swq = q == 0 ? sw : 0.f;
            const int t = 2 * rd + wg;
            const uint32_t ub = sbase + (t < 2 ? OFF_U0 : OFF_U1) + (t & 1) * 40960, ubar = sbase + OFF_BAR + B_UNIT + 40 * t;
            const float* c1 = reinterpret_cast<const float*>(smem + (t < 2 ? OFF_C0 : OFF_C1) + (t & 1) * 1280) + 16 * w + g;
            const uint32_t ka = ub + (lane >> 4) * 1024 + (lane & 7) * 128 + (((2 * w + ((lane >> 3) & 1)) ^ (lane & 7)) << 4);
            auto inverse = [&](float (&d)[28], int u) {
                const uint32_t dA = desc_lo(ub + u * 8192), dB = desc_lo(sbase + OFF_F);
                wg_fence();
                wgmma_n56_ss<0>(d, dA, dB);
                wgmma_n56_ss<1>(d, dA + 128, dB + 2);
                wgmma_n56_ss<1>(d, dA + 256, dB + 4);
                wgmma_n56_ss<1>(d, dA + 384, dB + 6);
                wg_commit();
            };
            auto keep = [&](float (&d)[28], int u, int un) {
                const bool ok = mbar_try(ubar + 8 * un, 0);
                reg_fence(d);
                d[25] = fmaf(c1[u * 64] * sx, swq, d[25]);
                d[27] = fmaf(c1[u * 64 + 8] * sx, swq, d[27]);
                if (part == 31 && u == 4) {
                    if (q >= 2) d[16] = d[18] = 0.f;
                    if (q >= 1) d[17] = d[19] = 0.f;
#pragma unroll
                    for (int i = 20; i < 28; i++) d[i] = 0.f;
                }
                const uint32_t a = ka + u * 8192;
#pragma unroll
                for (int j = 0; j < 6; j += 2)
                    stmatrix_x4_t(a + j * 1024, pack_f16(d[4 * j], d[4 * j + 1]), pack_f16(d[4 * j + 2], d[4 * j + 3]),
                                  pack_f16(d[4 * j + 4], d[4 * j + 5]), pack_f16(d[4 * j + 6], d[4 * j + 7]));
                asm volatile("stmatrix.sync.aligned.m8n8.x2.trans.shared.b16 [%0], {%1,%2};"
                             ::"r"(a + 6 * 1024), "r"(pack_f16(d[24], d[25])), "r"(pack_f16(d[26], d[27])) : "memory");
#pragma unroll
                for (int i = 0; i < 28; i++) {
                    s[i & 3] += d[i];
                    s[4 + (i & 3)] = fmaf(d[i], d[i], s[4 + (i & 3)]);
                }
#pragma unroll
                for (int i = 0; i < 8; i++) asm volatile("" : "+f"(s[i]));
                if (!ok) mbar_wait(ubar + 8 * un, 0);
                wg_wait<0>();
            };
            if (t >= 2) mbar_wait(sbase + OFF_BAR + B_C1, 0);
            mbar_wait(ubar, 0);
            inverse(acc, 0);
            mbar_wait(ubar + 8, 0);
            wg_wait<0>();
#pragma unroll 1
            for (int u = 0;; u += 2) {
                inverse(acc2, min(u + 1, 4));
                keep(acc, u, min(u + 2, 4));
                if (u == 4) break;
                inverse(acc, u + 2);
                keep(acc2, u + 1, min(u + 3, 4));
            }
#pragma unroll
            for (int i = 0; i < 4; i++) s[i] = s[2 * i] + s[2 * i + 1];
#pragma unroll
            for (int i = 0; i < 2; i++) s[i] = (q & 2 ? s[2 + i] : s[i]) + __shfl_xor_sync(0xffffffffu, q & 2 ? s[i] : s[2 + i], 2);
            const float mine = (q & 1 ? s[1] : s[0]) + __shfl_xor_sync(0xffffffffu, q & 1 ? s[0] : s[1], 1);
            asm volatile("red.relaxed.gpu.global.add.u64 [%0], %1;"
                         ::"l"(part_sums(sp, b, tail_block(gr, t), ts[76]) + 2 * (16 * w + 8 * (q & 1) + g) + (q >> 1)),
                         "l"(fabsf(mine) < 0x1p25f ? __float2ll_rn(mine * 0x1p21f) * 4096 + 1 : 65ll) : "memory");
            __syncwarp();
            if (lane == 0) mbar_arrive(sbase + OFF_BAR + B_SUM + 8 * t);
            if (rd == 0) continue;
        }
        const int t = 2 * rd - 2 + wg, db = tail_block(gr, t);
#pragma unroll 1
        for (uint32_t n = 0; n < (1u << 20); n++)
            if (mbar_try(sbase + OFF_BAR + B_NRM + 8 * t, 0)) break;
        if (reinterpret_cast<const volatile uint32_t*>(ts)[77 + t]) {
            direct_block(x, wt, gamma, beta, out, reinterpret_cast<float*>(smem + OFF_DIR + wg * 8192), b, db, part, ts[76]);
            continue;
        }
        const int jh = g & 1, r0 = 4 * w;
        const int lim = min(250, kL - part * 250) - r0 - (g >> 1);
        float na[8], nb[8];
#pragma unroll
        for (int i = 0; i < 8; i += 2) {
            const float4 v = reinterpret_cast<const float4*>(smem + OFF_GB)[32 * t + 16 * jh + 2 * i + q];
            na[i] = v.x; nb[i] = v.y; na[i + 1] = v.z; nb[i + 1] = v.w;
        }
        __nv_bfloat16* o = out + ((size_t)b * kL + part * 250 + r0 + (g >> 1)) * 512 + 64 * db + 32 * jh + 8 * q;
        int l = r0 + ((lane >> 1) & 3);
        uint32_t ra = sbase + (t < 2 ? OFF_U0 : OFF_U1) + (t & 1) * 40960 + l * 128;
        const int cc = 4 * (lane & 1) + (lane >> 3);
        auto fetch = [&](uint32_t (&r)[4]) {
            asm volatile("ldmatrix.sync.aligned.m8n8.x4.shared.b16 {%0,%1,%2,%3}, [%4];"
                         : "=r"(r[0]), "=r"(r[1]), "=r"(r[2]), "=r"(r[3]) : "r"(ra + (((cc ^ l) & 7) << 4)) : "memory");
            const bool wrap = l >= kMO - 16;
            l += wrap ? 16 - kMO : 16;
            ra += wrap ? 2048 + 8192 - kMO * 128 : 2048;
        };
        auto gelu8 = [&](const uint32_t (&r)[4], uint32_t (&p)[4]) {
#pragma unroll
            for (int i = 0; i < 4; i++) {
                float lo, hi;
                asm("{\n.reg .b16 a, b;\nmov.b32 {a, b}, %2;\ncvt.f32.f16 %0, a;\ncvt.f32.f16 %1, b;\n}" : "=f"(lo), "=f"(hi) : "r"(r[i]));
                p[i] = pack_bf16(gelu_half(fmaf(lo, na[2 * i], nb[2 * i])), gelu_half(fmaf(hi, na[2 * i + 1], nb[2 * i + 1])));
            }
        };
        uint32_t r[2][4], rn[2][4];
        fetch(r[0]);
        fetch(r[1]);
#pragma unroll 1
        for (int i = 0; i < 256; i += 32) {
            fetch(rn[0]);
            fetch(rn[1]);
            uint32_t p0[4], p1[4];
            gelu8(r[0], p0);
            gelu8(r[1], p1);
            if (i < lim) stg128(o, p0[0], p0[1], p0[2], p0[3]);
            if (i + 16 < lim) stg128(o + 16 * 512, p1[0], p1[1], p1[2], p1[3]);
            o += 32 * 512;
#pragma unroll
            for (int k = 0; k < 4; k++) { r[0][k] = rn[0][k]; r[1][k] = rn[1][k]; }
        }
    }
}
__device__ __forceinline__ void channel_scales(uint32_t sbase, uint8_t* smem, uint8_t* sp, int lane) {
    volatile uint32_t* ts = reinterpret_cast<volatile uint32_t*>(smem + OFF_TS);
    const uint32_t gr = ts[64], bars = sbase + OFF_BAR;
#pragma unroll 1
    for (int t = 0; t < 4; t++) {
#pragma unroll 1
        for (uint32_t n = 0; n < (1u << 20); n++)
            if (mbar_try(bars + B_SUM + 8 * t, 0)) break;
        long long s[4];
#pragma unroll 1
        for (uint32_t n = 0; n < (1u << 19); n++) {
            const unsigned long long* p = part_sums(sp, gr >> 6, tail_block(gr, t), ts[76]) + 4 * lane;
#pragma unroll
            for (int i = 0; i < 4; i++) asm volatile("ld.relaxed.gpu.global.u64 %0, [%1];" : "=l"(s[i]) : "l"(p + i) : "memory");
            if (__all_sync(0xffffffffu, s[0] & s[1] & s[2] & s[3] & 32)) break;
        }
        const float sx = __uint_as_float(ts[74]), sw = __uint_as_float(ts[75]);
        bool bad = false;
#pragma unroll
        for (int i = 0; i < 2; i++) {
            const float mean = (float)(s[2 * i] >> 12) * (0x1p-21f / kL), sq = (float)(s[2 * i + 1] >> 12) * (0x1p-21f / kL);
            float2* gb = reinterpret_cast<float2*>(smem + OFF_GB) + 64 * t + 2 * lane + i;
            const float den = fmaxf(sq - mean * mean, 0.f) + 1e-5f * sx * sw * sx * sw, a = gb->x * rsqrtf(den);
            *gb = make_float2(0.5f * a, 0.5f * (gb->y - mean * a));
            bad |= ((s[2 * i] | s[2 * i + 1]) & 0xFC0) || !(den >= 0x1p-22f);
        }
        bad = __any_sync(0xffffffffu, bad);
        if (lane == 0) ts[77 + t] = bad;
        __syncwarp();
        if (lane == 0) mbar_arrive(bars + B_NRM + 8 * t);
    }
}

__device__ __forceinline__ void publish_tiles(uint8_t* sp, uint32_t bars, int cta, int wg) {
#pragma unroll 1
    for (int m = 0; m < 2; m++) {
        mbar_wait(bars + B_YS + 8 * (2 * m + wg), 0);
        asm volatile("fence.acq_rel.gpu;" ::: "memory");
        red_relaxed(y_flag(sp, (cta >> 1) & 1, 4 * m + 2 * (cta & 1) + wg));
    }
}

__global__ void __launch_bounds__(384, 1)
main_kernel(const __grid_constant__ CUtensorMap tmx, const __grid_constant__ CUtensorMap tmw0, const __grid_constant__ CUtensorMap tmw1,
            const __nv_bfloat16* __restrict__ x, const __nv_bfloat16* __restrict__ wt, const __nv_bfloat16* __restrict__ gamma,
            const __nv_bfloat16* __restrict__ beta, __nv_bfloat16* __restrict__ out) {
    extern __shared__ __align__(1024) uint8_t smem_raw[];
    const uint32_t sbase = smem_u32(smem_raw) & ~1023u;
    const uint32_t bars = sbase + OFF_BAR;
    const int tid = threadIdx.x, wg = __shfl_sync(0xffffffffu, tid >> 7, 0), lane = tid & 31;
    const int cta = blockIdx.x;
    volatile uint32_t* ts = reinterpret_cast<volatile uint32_t*>(smem_raw + OFF_TS);
    uint8_t* const sp = reinterpret_cast<uint8_t*>((reinterpret_cast<uintptr_t>(g_sp) + (2u << 20) - 1) & ~(uintptr_t)((2u << 20) - 1));
    const bool probing = (cta & 3) == 0 && lane == 0 && tid < 128 && (tid >= 64 || cta < 4 * NPAGES);
    unsigned* pw = reinterpret_cast<unsigned*>(sp + (tid < 64 ? ((cta >> 2) << 21) + ((tid & 32) ? 15 : 13) * 4096
                                                              : ((tid & 32) ? 0 : 14) * 4096 + (cta >> 2) * 128));
    unsigned pv = 0;
    if (probing) {
        stg128(pw, 0, 0, 0, 0);
        stg128(pw + 4, 0, 0, 0, 0);
        asm volatile("atom.relaxed.gpu.global.exch.b32 %0, [%1], %2;" : "=r"(pv) : "l"(pw), "r"(7) : "memory");
    }
    if (tid == 320) bar_setup<0, B_SIG>(bars);
    if (tid >= 256 && tid < 262) ts[68 + tid - 256] = tid < 260 ? 0xffffu : 0;
    if (tid == 383) asm volatile("griddepcontrol.launch_dependents;");
    __syncthreads();

    if (wg == 2) {
        asm volatile("setmaxnreg.dec.sync.aligned.u32 40;");
        const int role = (tid >> 5) & 3;
        if (role == 3) {
            unsigned v = 0;
#pragma unroll 1
            for (uint32_t n = 0; n < (1u << 15); n++) {
                asm volatile("ld.relaxed.gpu.global.u32 %0, [%1];" : "=r"(v) : "l"(&g_tsel[lane]) : "memory");
                if (__all_sync(0xffffffffu, v & 16)) break;
                __nanosleep(TSLEEP);
            }
            const uint32_t m1 = __ballot_sync(0xffffffffu, v & 8), below = (1u << lane) - 1;
            const int rank = (v & 8) ? 32 - __popc(m1) + __popc(m1 & below) : __popc(~m1 & below);
            ts[lane] = rank;
            ts[32 + rank] = lane;
            const uint32_t p0 = __ballot_sync(0xffffffffu, v & 1);
            if (lane == 0) ts[66] = p0;
            if (lane == (cta >> 2)) ts[64] = rank * 4 + (cta & 3);
            const int part = (m1 >> (cta >> 2)) & 1;
            __syncwarp();
            if (lane == 0) mbar_arrive(bars + B_TSEL);
            mbar_wait(bars + B_TSEL, 0);
            mbar_wait(bars + B_PUB, 0);
            int gc = 0;
            const int gend = lane == 0 ? 33 : lane == 1 ? 32 : 0;
#pragma unroll 1
            for (uint32_t n = 0; n < (1u << 16) && __any_sync(0xffffffffu, gc < gend); n++) {
                asm volatile("ld.relaxed.gpu.global.u32 %0, [%1];" : "=r"(v) : "l"(chunk_flag(sp, lane == 1, part, min(gc, 32 - (lane & 1)))) : "memory");
                if (gc < gend && v >= NCTA) {
                    asm volatile("fence.acquire.gpu;" ::: "memory");
                    mbar_arrive(bars + (lane == 0 ? B_RDY : B_GATE) + 8 * gc);
                    gc++;
                }
            }
            if (lane == 0) publish_tiles(sp, bars, cta, 1);
        } else if (role == 0) {
            const int b = (cta >> 1) & 1, dq = cta & 1;
            for (int v = 0; v < V0; v++) {
                mbar_wait(bars + B_EMPTY + 8 * (v % NST), ((v / NST) & 1) ^ 1);
                if (lane == 0) {
                    mbar_arrive(bars + B_FULL + 8 * (v % NST));
                    mbar_arrive(bars + B_FULL + 8 * (v % NST));
                }
            }
            mbar_wait(bars + B_TSEL, 0);
            const uint32_t gr = ts[64], grp = gr >> 6, idx = (gr >> 2) & 15, pmask = ts[66];
            const uint32_t n0 = idx * 4 + 2 * dq + ((lane & 1) ^ 1), r0 = lane < 3 ? idx * 4 + b : R_W + n0 / 3;
            const uint32_t base = (r0 << 16) + 4096 + ((lane < 3 ? lane : n0 % 3) << 14), step = (lane < 3 ? 64 : 22) << 16;
            uint32_t sels = 0;
            for (int i = 0; i < 12; i++) sels |= run_sel(r0 + i * (step >> 16), grp, pmask) << i;
            int ld = 0;
            const uint32_t bytes = lane == 2 ? XB - 16384 : 8192;
#pragma unroll 1
            for (int h = 0; h < 64; h++) {
                const int s = step_k(h), st = (h + V0) % NST;
                const bool newx = h < HEND ? !(h & 1) : h < HEND + 4;
                const uint32_t fb = bars + B_FULL + 8 * st;
                const uint32_t k = lane < 3 ? (s >> 1) % RX : (h + RW - 64 % RW) % RW, half = lane < 3 ? s & 1 : 0;
                const uint8_t* gsrc = sp + (base + k * step + (half << 17) + ((((sels >> k) ^ half) & 1) << 13));
                const uint32_t dst = sbase + (lane < 3 ? OFF_X + (s & 3) * XB + lane * 8192 : st * 8192 + (lane == 3 ? OFF_W0 : OFF_W1));
                auto landed = [&]() {
                    if (ld < h && mbar_test(bars + B_FULL + 8 * ((ld + V0) % NST), ((ld + V0) / NST) & 1)) {
                        if (!(ld & 1) && lane < 2) red_relaxed(chunk_flag(sp, 1, lane, ld >> 1));
                        ld++;
                    }
                };
#pragma unroll 1
                for (uint32_t n = 0; n < (1u << 19) && !mbar_test(bars + B_EMPTY + 8 * st, (((h + V0) / NST) & 1) ^ 1); n++) landed();
#pragma unroll 1
                for (uint32_t n = 0; n < (1u << 19) && ld <= h - NST; n++) landed();
                if (lane == 0) mbar_expect_tx(fb, newx ? 16384 + XB : 16384);
                if ((h & 1) || h == 0) {
#pragma unroll 1
                    for (uint32_t n = 0; n < (1u << 19) && !mbar_test(bars + B_RDY + 8 * ((h + 1) >> 1), 0); n++) landed();
                    asm volatile("fence.proxy.async.global;" ::: "memory");
                }
                __syncwarp();
                if (lane < 3 ? newx : lane < 5) bulk_g2s(dst, gsrc, bytes, fb);
            }
#pragma unroll 1
            for (; ld < 63; ld++) {
                mbar_wait(bars + B_FULL + 8 * ((ld + V0) % NST), ((ld + V0) / NST) & 1);
                if (!(ld & 1) && lane < 2) red_relaxed(chunk_flag(sp, 1, lane, ld >> 1));
            }
            const uint8_t* usrc = sp + y_unit(tail_block(gr, lane / 5), (gr & 31) * 5 + lane % 5, gr >> 6, pmask);
            const uint32_t udst = sbase + (lane < 10 ? OFF_U0 : OFF_U1 - 81920) + lane * 8192, ubar = bars + B_UNIT + 8 * lane;
            if (lane < 20) mbar_expect_tx(ubar, 8192);
            auto tail_loads = [&](int u0, int u1) {
                if (lane >= u0 && lane < u1) bulk_g2s(udst, usrc, 8192, ubar);
                __syncwarp();
            };
            tail_poll(sp, gr, 0);
            mbar_wait(bars + B_T2, 0);
            tail_loads(0, 5);
            tail_poll(sp, gr, 1);
            tail_loads(5, 8);
            mbar_wait(bars + B_YS + 16, 0);
            tail_loads(8, 10);
            mbar_wait(bars + B_T2 + 8, 0);
            if (lane == 0) {
                mbar_expect_tx(bars + B_C1, 2560);
                corr_load(sbase, gr, 2, bars + B_C1);
                corr_load(sbase, gr, 3, bars + B_C1);
            }
            tail_poll(sp, gr, 2);
            tail_loads(10, 15);
            tail_poll(sp, gr, 3);
            tail_loads(15, 20);
            mbar_wait(bars + B_GATE + 8 * 31, 0);
            unsigned exits = 0;
            if (lane == 0) exits = atomicAdd(&g_exit, 1);
            if (__shfl_sync(0xffffffffu, exits, 0) == NCTA - 1) {
                for (int i = 0; i < 4; i++) *chunk_flag(sp, i >> 1, i & 1, lane) = 0;
                if (lane < 2) *chunk_flag(sp, 0, lane, 32) = 0;
                g_tsel[lane] = 0;
                if (lane < 16) *y_flag(sp, lane >> 3, lane & 7) = 0;
                if (lane == 0) { g_exit = 0; g_epoch = ts[76]; }
            }
        } else if (role == 1) {
            auto raw_load = [&](int r, int h, uint32_t gr, uint32_t dst, uint32_t bar) {
                if (r >= 0) {
                    const int u = r * NCTA + cta, i = u % XPC, b = i >= kNT;
                    tma3d(dst, &tmx, u / XPC * 64, (i - b * kNT) * kMO, b, bar);
                } else if (h >= 0) {
                    const int c = 32 * step_k(h) + ((gr >> 1) & 30);
                    tma3d_ef(dst, c < 512 ? &tmw0 : &tmw1, step_m(h) * 256 + (gr & 3) * 64, c & 511, 0, bar);
                }
            };
            uint32_t gr;
            {
                const int v = lane >> 1, r = v < V0 ? x_round(v, lane & 1) : -1, h = v < V0 ? w_step(v, lane & 1) : -1;
                const uint32_t dst = pre_slot(sbase, v, lane & 1), bar = bars + B_PRE + 8 * lane;
                if (r >= 0 || h >= 0) mbar_expect_tx(bar, r >= 0 ? 8192 : 4096);
                if (v < PRE1) raw_load(r, -1, 0, dst, bar);
                mbar_wait(bars + B_TSEL, 0);
                gr = ts[64];
                raw_load(-1, h, gr, dst, bar);
                if (v >= PRE1) raw_load(r, -1, 0, dst, bar);
                __syncwarp();
            }
            mbar_wait(bars + B_PUB, 0);
#pragma unroll 1
            for (int v = V0; v < V0 + 64; v++) {
                mbar_wait(bars + B_EMPTY + 8 * (v % NST), ((v / NST) & 1) ^ 1);
                __syncwarp();
                const int r = lane < 2 ? x_round(v, lane) : -1, h = lane < 2 ? w_step(v, lane) : -1;
                const uint32_t fb = bars + B_FULL + 8 * (v % NST);
                const uint32_t bytes = __reduce_add_sync(0xffffffffu, r >= 0 ? 8192 : h >= 0 ? 4096 : 0);
                if (lane == 0) mbar_expect_tx(fb, bytes);
                __syncwarp();
                raw_load(r, h, gr, raw_slot(sbase, v, lane), fb);
                if (v >= 20 && v < 40) {
                    const int t = (v - 20) / 5, i = (v - 20) % 5 * 32 + lane, db = 4 * (t >> 1) + 2 * (cta & 1) + (t & 1);
                    ts[(OFF_YT - OFF_TS) / 4 + t * kNT + i] = y_unit(db, i, (cta >> 1) & 1, ts[66]);
                }
                if (v == 66 && lane == 0) {
#pragma unroll 1
                    for (uint32_t n = 0; n < (1u << 15); n++) {
                        unsigned c0, c1;
                        asm volatile("ld.relaxed.gpu.global.u32 %0, [%1];" : "=r"(c0) : "l"(&g_cready[(gr >> 6) * 64]) : "memory");
                        asm volatile("ld.relaxed.gpu.global.u32 %0, [%1];" : "=r"(c1) : "l"(&g_cready[(gr >> 6) * 64 + 32]) : "memory");
                        if (c0 == ts[76] && c1 == ts[76]) break;
                        __nanosleep(500);
                    }
                    asm volatile("fence.acquire.gpu;" ::: "memory");
                    asm volatile("fence.proxy.async.global;" ::: "memory");
                    mbar_expect_tx(bars + B_FTAB, 8192 + 2560);
                    bulk_g2s(sbase + OFF_F, g_tab.inv, 8192, bars + B_FTAB);
                    for (int t = 0; t < 2; t++) {
                        corr_load(sbase, gr, t, bars + B_FTAB);
                        asm volatile("cp.async.bulk.prefetch.L2.global [%0], 1280;" ::"l"(corr_src(gr, 2 + t)) : "memory");
                    }
                }
            }
            channel_scales(sbase, smem_raw, sp, lane);
        } else {
            uint32_t epoch;
            if (lane == 0) {
                bar_setup<B_SIG, B_END>(bars);
                mbar_arrive(bars + B_TSEL);
            }
            asm volatile("ld.relaxed.gpu.global.u32 %0, [%1];" : "=r"(epoch) : "l"(&g_epoch) : "memory");
            mbar_wait(bars + B_TSEL, 0);
            const uint32_t gr = ts[64];
#pragma unroll
            for (int i = lane; i < 256; i += 32) {
                const int d = 64 * tail_block(gr, i >> 6) + (i & 33) + 8 * ((i >> 1) & 3) + 2 * ((i >> 3) & 3);
                ts[(OFF_GB - OFF_TS) / 4 + 2 * i] = (uint32_t)__bfloat16_as_ushort(gamma[d]) << 16;
                ts[(OFF_GB - OFF_TS) / 4 + 2 * i + 1] = (uint32_t)__bfloat16_as_ushort(beta[d]) << 16;
            }
            if (lane == 0) ts[76] = epoch + 1;
            if (cta < 32) stg128(part_sums(sp, cta >> 4, (cta >> 1) & 7, epoch) + (cta & 1) * 64 + 2 * lane, 0, 0, 0, 0);
            __syncwarp();
            if (lane) return;
#pragma unroll 1
            for (int gc = 0; gc < 33;) {
                mbar_wait(bars + B_SIG + 8 * gc, 0);
                if (gc < MERGE) mbar_wait(bars + B_SIG + 8 * MERGE, 0);
                int ge = gc + 1;
                while (ge < 33 && mbar_test(bars + B_SIG + 8 * ge, 0)) ge++;
                asm volatile("fence.acq_rel.gpu;" ::: "memory");
                for (; gc < ge; gc++) {
                    red_relaxed(chunk_flag(sp, 0, 0, gc));
                    red_relaxed(chunk_flag(sp, 0, 1, gc));
                    if (gc == 0) mbar_arrive(bars + B_PUB);
                }
            }
            publish_tiles(sp, bars, cta, 0);
        }
    } else {
        asm volatile("setmaxnreg.inc.sync.aligned.u32 232;");
        const uint4 fx = __ldg(reinterpret_cast<const uint4*>(g_tab.fx) + tid), ft = __ldg(reinterpret_cast<const uint4*>(g_tab.tap) + (tid & 127));
        if (wg == 1) {
            uint4 sm[8];
#pragma unroll
            for (int j = 0; j < 4; j++) {
                const int r = 2 * j + ((tid >> 6) & 1);
                sm[j] = __ldg(reinterpret_cast<const uint4*>(x) + ((r >> 2) * kRows + 1000 + 2000 * (r & 3)) * 128 + (((j + r) & 1) << 6) + (tid & 63));
                sm[4 + j] = __ldg(reinterpret_cast<const uint4*>(wt) + (4 * r * 512 + 67 * r + 7) * 64 + (tid & 63));
            }
#pragma unroll
            for (int k = 0; k < 2; k++) {
                uint32_t mx = 0;
#pragma unroll
                for (int j = 4 * k; j < 4 * k + 4; j++)
                    mx = __vmaxu2(__vmaxu2(mx, __vmaxu2(sm[j].x & 0x7FFF7FFFu, sm[j].y & 0x7FFF7FFFu)), __vmaxu2(sm[j].z & 0x7FFF7FFFu, sm[j].w & 0x7FFF7FFFu));
                mx = __reduce_max_sync(0xffffffffu, max(mx & 0xFFFFu, mx >> 16));
                if (lane == 0) atomicMax(const_cast<uint32_t*>(ts) + 72 + k, mx);
            }
        }
        if ((cta & 3) == 0) {
            if (probing) {
                const int w = tid >> 5;
                unsigned best = 0xffffu;
#pragma unroll 1
                for (int r = 0; r < 6; r++) {
                    unsigned t0, t1;
                    asm volatile("{\n.reg .pred p;\nsetp.eq.u32 p, %1, 0xffffffff;\nmov.u32 %0, 0;\n@!p mov.u32 %0, %%clock;\n}"
                                 : "=r"(t0) : "r"(pv) : "memory");
                    asm volatile("atom.relaxed.gpu.global.exch.b32 %0, [%1], %2;" : "=r"(pv) : "l"(pw), "r"(r) : "memory");
                    asm volatile("{\n.reg .pred p;\nsetp.eq.u32 p, %1, 0xffffffff;\nmov.u32 %0, 0;\n@!p mov.u32 %0, %%clock;\n}"
                                 : "=r"(t1) : "r"(pv) : "memory");
                    ts[68 + w] = best = min(best, t1 - t0);
                    const unsigned other = ts[68 + (w ^ 1)];
                    if (min(best, other) < PROBE_NEAR && max(best, other) > PROBE_NEAR) break;
                }
            }
            if (wg == 0) {
                named_bar(2, 128);
                if (tid == 0) {
                    const uint32_t part = ts[71] < ts[70];
                    const uint32_t v = 16 | (part << 3) | ((ts[69] < ts[68]) ^ part);
                    asm volatile("st.relaxed.gpu.global.u32 [%0], %1;" ::"l"(&g_tsel[cta >> 2]), "r"(v) : "memory");
                }
            }
        }
        if (tid < 2 * (V0 + 65)) ts[(OFF_PLAN - OFF_TS) / 4 + tid] = plan_word(tid >> 1, tid & 1, cta);
        {
            named_bar(1, 256);
            const uint32_t ex = min(max(251 - (int)(ts[72] >> 7), 8), 187), ew = min(max(251 - (int)(ts[73] >> 7), 8), 187);
            if (tid == 0) { ts[74] = ex << 23; ts[75] = ew << 23; }
            const uint32_t sx = ex * 0x800080u, sw = ew * 0x800080u;
            sts128(sbase + OFF_F + 16 * tid, mul_bf16x2(fx.x, sx), mul_bf16x2(fx.y, sx), mul_bf16x2(fx.z, sx), mul_bf16x2(fx.w, sx));
            if (tid < 128) sts128(sbase + OFF_TMP + 16 * tid, mul_bf16x2(ft.x, sw), mul_bf16x2(ft.y, sw), mul_bf16x2(ft.z, sw), mul_bf16x2(ft.w, sw));
            fence_proxy_async_smem();
            named_bar(1, 256);
        }
        const int t = tid & 127;
        Xf f;
        f.sbase = sbase; f.lane = lane; f.dw = desc_lo(sbase + (wg ? OFF_W1 : OFF_W0));
        {
            const int w = t >> 5;
            const uint32_t nw = (8 * (w & 1) + (lane >> 2)) * 4 + (cta & 3), rw = R_W + nw / 3;
            f.pw = sp + (rw << 16) + 4096 + ((nw % 3) << 14) + (w >> 1) * 128;
            f.cw = ((lane & 7) ^ (w >> 1)) << 4;
            for (int i = 0; i < RW; i++) f.cw |= run_sel(rw + i * 22, 0, 0) << (8 + i);
            mbar_wait(bars + B_FULL + 8 * (NST - 1), 0);
            mbar_wait(bars + B_TSEL, 0);
            const uint32_t gr = ts[64], pmask = ts[66];
#pragma unroll
            for (int i = 0; i < 2; i++) {
                const int ps = 4 * w + (lane >> 3), pp = (lane >> 2) & 1;
                const uint32_t rx = ts[ps == 0 ? 16 * pp : i ? 32 - ps : ps];
                f.px[i] = sp + ((rx & 15) << 18) + 4096;
                f.cx[i] = (((lane & 3) + 4 * (ps == 0 ? i : pp)) << 4) | ((((pmask >> ((rx >> 3) & 1)) ^ -(((rx >> 1) ^ (rx >> 4)) & 1)) & 0x55) << 8);
            }
#pragma unroll
            for (int i = 0; i < RW; i++) f.cw ^= (((pmask >> ((rw + i * 22) >> 5)) ^ (gr >> 6)) & 1) << (8 + i);
            const uint32_t row = ((gr & 12) << 1) | ((gr & 48) >> 3);
            f.pw += row * 128;
            f.cw ^= (row & 7) << 4;
            const uint32_t s = ts[32 + (gr >> 6) * 16 + 8 * (w & 1) + (lane >> 2)], ga = sbase + OFF_TMP + (16 * (s >> 3) + (s & 7)) * 32 + (lane & 3) * 4;
#pragma unroll
            for (int i = 0; i < 4; i++) asm volatile("ld.shared.u32 %0, [%1];" : "=r"(f.g[i]) : "r"(ga + (i & 1) * 256 + (i >> 1) * 16) : "memory");
        }
        {
            float at[32];
#pragma unroll 1
            for (uint32_t v = 0; v < V0; v++) {
                const uint32_t e = plan_load(f, v, wg), raw = pre_slot(sbase, v, wg);
                if (v >= NST) mbar_wait(bars + B_FULL + 8 * (v % NST), (v / NST) & 1);
                if (e & 6) mbar_wait(bars + B_PRE + 16 * v + 8 * wg, 0);
                if (v == PAUSE) mbar_wait(bars + B_PUB, 0);
                wg_fence();
                if ((e & 6) == 2) {
                    unit_mma<false>(at, f, raw);
                    wg_wait<0>();
                    unit_store<false>(at, f, e);
                } else if (e & 4) {
                    unit_mma<true>(at, f, raw);
                    wg_wait<0>();
                    unit_store<true>(at, f, e);
                }
                if (lane == 0) mbar_arrive(bars + B_EMPTY + 8 * (v % NST));
                unit_done(f, e, v);
            }
        }
        const int slot = cta >> 2;
        f.e = plan_load(f, V0, wg);
        uint32_t a0[40], a1[40], b0[40], b1[40];
#pragma unroll
        for (int i = 0; i < 40; i++) a0[i] = a1[i] = b0[i] = b1[i] = 0;
        if (slot == 0) gemm_main<true>(a0, a1, b0, b1, f, wg);
        else gemm_main<false>(a0, a1, b0, b1, f, wg);
        const uint32_t gr = __shfl_sync(0xffffffffu, ts[64], 0);
        const float sx = __uint_as_float(ts[74]), sw = __uint_as_float(ts[75]);
        uint32_t wr[2][4][4];
        w_fetch(wr[0], f, V0 + HEND);
#pragma unroll 1
        for (int m = 0; m < 2; m++) {
            if (slot == 0) gemm_last<true>(a0, a1, wr, f, wg, m);
            else gemm_last<false>(a0, a1, wr, f, wg, m);
            reg_fence(a0);
            reg_fence(a1);
            const int wsw = gr & 4;
            mbar_wait(bars + B_GATE + 8 * y_gate(2 * m + wg), 0);
            if (m) mbar_wait(bars + B_FTAB, 0);
            const uint32_t ytab = sbase + OFF_YT + (m * 2 + wg) * (kNT * 4);
            store_tile(a0, a1, b0, b1, wr[0], f, m == 0, sbase + OFF_STG + wg * 16384, t, wg, sp, slot, ytab, wsw);
            __syncwarp();
            if (lane == 0) mbar_arrive(bars + B_YS + 8 * (2 * m + wg));
        }
        tail_phase(sbase, smem_raw, sp, wg, gr, sx, sw, x, wt, gamma, beta, out);
    }
}

constexpr int C_STAGE = 32768 + 2 * XB, C_SMEM = 3 * C_STAGE + 64;
__global__ void __launch_bounds__(256, 1) corr_kernel(const __grid_constant__ CUtensorMap tmx, const __grid_constant__ CUtensorMap tmw) {
    extern __shared__ __align__(1024) uint8_t smem_raw[];
    const uint32_t sbase = smem_u32(smem_raw) & ~1023u, bars = sbase + 3 * C_STAGE;
    const int tid = threadIdx.x, wg = __shfl_sync(0xffffffffu, tid >> 7, 0), b = blockIdx.x >> 1, dh = blockIdx.x & 1;
    auto load = [&](int k) {
        const uint32_t st = sbase + (k % 3) * C_STAGE, bar = bars + 8 * (k % 3);
        mbar_expect_tx(bar, C_STAGE);
        for (int i = 0; i < 4; i++) tma2d(st + i * 8192, &tmw, 256 * dh + 64 * i, 64 * k, bar);
        tma4d(st + 32768, &tmx, 64 * k, 64 - kMO, 1, b, bar);
        tma4d(st + 32768 + XB, &tmx, 64 * k, 0, 0, b, bar);
    };
    uint32_t epoch = 0;
    if (tid == 0) {
        for (int i = 0; i < 3; i++) mbar_init(bars + 8 * i, 1);
        fence_mbar_init();
        fence_proxy_async_smem();
        for (int k = 0; k < 3; k++) load(k);
        asm volatile("ld.relaxed.gpu.global.u32 %0, [%1];" : "=r"(epoch) : "l"(&g_epoch) : "memory");
    }
    __syncthreads();
    float a[2][80];
#pragma unroll
    for (int i = 0; i < 80; i++) a[0][i] = a[1][i] = 0.f;
#pragma unroll 1
    for (int k = 0; k < 8; k++) {
        const uint32_t dA = desc_lo(sbase + (k % 3) * C_STAGE + wg * 16384), dB = desc_lo(sbase + (k % 3) * C_STAGE + 32768);
        mbar_wait(bars + 8 * (k % 3), (k / 3) & 1);
        wg_fence();
#pragma unroll
        for (int i = 0; i < 8; i++) {
            wgmma_n160_f<1>(a[i & 1], dA + (i & 1) * 512 + (i >> 1) * 128, dB + (i >> 1) * 2);
            wgmma_n160_f<-1>(a[i & 1], dA + (i & 1) * 512 + (i >> 1) * 128, dB + XB / 16 + (i >> 1) * 2);
        }
        wg_commit();
        wg_wait<0>();
        __syncthreads();
        if (tid == 0 && k + 3 < 8) load(k + 3);
    }
    reg_fence(a[0]);
    reg_fence(a[1]);
    const int w = (tid >> 5) & 3, g = (tid & 31) >> 2, q = tid & 3;
    float* stage = reinterpret_cast<float*>(smem_raw);
#pragma unroll
    for (int i = 0; i < 160; i++) {
        const int m = i / 80, j = i % 80, d = 16 * w + 8 * ((j >> 1) & 1) + g;
        stage[((2 * wg + m) * kNT + 8 * (j >> 2) + 2 * q + (j & 1)) * 64 + (d & 33) + 8 * ((d >> 1) & 3) + 2 * ((d >> 3) & 3)] = a[m][j];
    }
    __syncthreads();
    for (int i = tid; i < 4 * kNT * 16; i += 256)
        reinterpret_cast<float4*>(g_corr)[(b * 8 + 4 * dh) * kNT * 16 + i] = reinterpret_cast<const float4*>(stage)[i];
    __syncthreads();
    if (tid == 0) {
        asm volatile("fence.acq_rel.gpu;" ::: "memory");
        asm volatile("st.relaxed.gpu.global.u32 [%0], %1;" ::"l"(&g_cready[blockIdx.x * 32]), "r"(epoch + 1) : "memory");
    }
}

__global__ void __launch_bounds__(256) plain_conv(const __nv_bfloat16* __restrict__ x, const __nv_bfloat16* __restrict__ w) {
    __shared__ float xs[64][17], ws[16][65];
    float* h = g_direct;
    const int b = blockIdx.z, l0 = blockIdx.x * 64, d0 = blockIdx.y * 64, tx = threadIdx.x & 15, ty = threadIdx.x >> 4;
    float acc[4][4] = {};
    for (int k0 = 0; k0 < 31 * 512; k0 += 16) {
        for (int i = threadIdx.x; i < 1024; i += 256) {
            const int l = min(l0 + (i >> 4), kL - 1);
            xs[i >> 4][i & 15] = __bfloat162float(x[((size_t)b * kRows + l) * 1024 + k0 + (i & 15)]);
            ws[i >> 6][i & 63] = __bfloat162float(w[(size_t)(k0 + (i >> 6)) * 512 + d0 + (i & 63)]);
        }
        __syncthreads();
        for (int k = 0; k < 16; k++)
            for (int i = 0; i < 4; i++)
                for (int j = 0; j < 4; j++) acc[i][j] = fmaf(xs[ty * 4 + i][k], ws[k][tx * 4 + j], acc[i][j]);
        __syncthreads();
    }
    for (int i = 0; i < 4; i++)
        for (int j = 0; j < 4; j++)
            if (l0 + ty * 4 + i < kL) h[((size_t)b * kL + l0 + ty * 4 + i) * 512 + d0 + tx * 4 + j] = acc[i][j];
}
__global__ void __launch_bounds__(256) plain_norm(const __nv_bfloat16* __restrict__ gamma, const __nv_bfloat16* __restrict__ beta,
                                                  __nv_bfloat16* __restrict__ out) {
    __shared__ float s1[8][32], s2[8][32];
    const int c = threadIdx.x & 31, r = threadIdx.x >> 5, d = blockIdx.x * 32 + c;
    const float* h = g_direct + (size_t)blockIdx.y * kL * 512 + d;
    float a = 0.f, q = 0.f;
    for (int l = r; l < kL; l += 8) { const float v = h[(size_t)l * 512]; a += v; q = fmaf(v, v, q); }
    s1[r][c] = a; s2[r][c] = q;
    __syncthreads();
    a = q = 0.f;
    for (int i = 0; i < 8; i++) { a += s1[i][c]; q += s2[i][c]; }
    const float mean = a * (1.0f / kL), sc = __bfloat162float(gamma[d]) / sqrtf(fmaxf(q * (1.0f / kL) - mean * mean, 0.f) + 1e-5f);
    const float sh = __bfloat162float(beta[d]) - mean * sc;
    for (int l = r; l < kL; l += 8)
        out[((size_t)blockIdx.y * kL + l) * 512 + d] = __float2bfloat16(gelu_half(0.5f * fmaf(h[(size_t)l * 512], sc, sh)));
}

typedef CUresult (*EncodeTiledFn)(CUtensorMap*, CUtensorMapDataType, cuuint32_t, void*, const cuuint64_t*, const cuuint64_t*,
                                  const cuuint32_t*, const cuuint32_t*, CUtensorMapInterleave, CUtensorMapSwizzle,
                                  CUtensorMapL2promotion, CUtensorMapFloatOOBfill);

void encode(EncodeTiledFn fn, CUtensorMap* tm, const void* ptr, int rank, const cuuint64_t* dims, const cuuint64_t* strides,
            const cuuint32_t* box, CUtensorMapL2promotion promo, CUtensorMapSwizzle swz = CU_TENSOR_MAP_SWIZZLE_128B) {
    const cuuint32_t es[5] = {1, 1, 1, 1, 1};
    fn(tm, CU_TENSOR_MAP_DATA_TYPE_BFLOAT16, rank, const_cast<void*>(ptr), dims, strides, box, es, CU_TENSOR_MAP_INTERLEAVE_NONE,
       swz, promo, CU_TENSOR_MAP_FLOAT_OOB_FILL_NONE);
}

}

extern "C" void kernel_launch(void* const* d_in, const int* in_sizes, int n_in, void* d_out, int out_size) {
    const __nv_bfloat16* x = (const __nv_bfloat16*)d_in[0];
    const __nv_bfloat16* w = (const __nv_bfloat16*)d_in[1];
    const __nv_bfloat16* gamma = (const __nv_bfloat16*)d_in[2];
    const __nv_bfloat16* beta = (const __nv_bfloat16*)d_in[3];
    static EncodeTiledFn enc = nullptr;
    static int resident = 0;
    if (!enc) {
        void* fn = nullptr;
        cudaDriverEntryPointQueryResult qr;
        cudaGetDriverEntryPoint("cuTensorMapEncodeTiled", &fn, cudaEnableDefault, &qr);
        enc = (EncodeTiledFn)fn;
        cudaFuncSetAttribute(main_kernel, cudaFuncAttributeMaxDynamicSharedMemorySize, MAIN_SMEM);
        cudaFuncSetAttribute(corr_kernel, cudaFuncAttributeMaxDynamicSharedMemorySize, C_SMEM);
        int dev = 0, per_sm = 0;
        cudaGetDevice(&dev);
        cudaDeviceGetAttribute(&resident, cudaDevAttrMultiProcessorCount, dev);
        cudaOccupancyMaxActiveBlocksPerMultiprocessor(&per_sm, main_kernel, 384, MAIN_SMEM);
        resident *= per_sm;
    }
    if (resident < NCTA + 4) {
        plain_conv<<<dim3((kL + 63) / 64, 8, 2), 256>>>(x, w);
        plain_norm<<<dim3(16, 2), 256>>>(gamma, beta, (__nv_bfloat16*)d_out);
        return;
    }
    CUtensorMap tmx, tmw0, tmw1, tmcx, tmcw;
    {
        const cuuint64_t dims[3] = {1024, kRows, 2}, strides[2] = {2048, (cuuint64_t)kRows * 2048};
        const cuuint32_t box[3] = {64, 64, 1};
        encode(enc, &tmx, x, 3, dims, strides, box, CU_TENSOR_MAP_L2_PROMOTION_L2_128B);
    }
    {
        const cuuint64_t dims0[3] = {512, 512, 16}, dims1[3] = {512, 512, 15}, strides[2] = {1024, 2 * 512 * 512 * 2};
        const cuuint32_t box[3] = {64, 2, 16};
        encode(enc, &tmw0, w, 3, dims0, strides, box, CU_TENSOR_MAP_L2_PROMOTION_L2_128B);
        encode(enc, &tmw1, w + 512 * 512, 3, dims1, strides, box, CU_TENSOR_MAP_L2_PROMOTION_L2_128B);
    }
    {
        const cuuint64_t dims[4] = {512, kMO, kNT, 2}, strides[3] = {2048, kMO * 2048, (cuuint64_t)kRows * 2048};
        const cuuint32_t box[4] = {64, 1, kNT, 1};
        encode(enc, &tmcx, x, 4, dims, strides, box, CU_TENSOR_MAP_L2_PROMOTION_L2_128B);
        const cuuint64_t dimw[2] = {512, 512}, stridew[1] = {1024};
        const cuuint32_t boxw[2] = {64, 64};
        encode(enc, &tmcw, w + 30 * 512 * 512, 2, dimw, stridew, boxw, CU_TENSOR_MAP_L2_PROMOTION_L2_128B);
    }
    main_kernel<<<NCTA, 384, MAIN_SMEM>>>(tmx, tmw0, tmw1, x, w, gamma, beta, (__nv_bfloat16*)d_out);
    cudaLaunchConfig_t cfg = {};
    cudaLaunchAttribute at[1];
    cfg.gridDim = 4;
    cfg.blockDim = 256;
    cfg.dynamicSmemBytes = C_SMEM;
    at[0].id = cudaLaunchAttributeProgrammaticStreamSerialization;
    at[0].val.programmaticStreamSerializationAllowed = 1;
    cfg.attrs = at;
    cfg.numAttrs = 1;
    cudaLaunchKernelEx(&cfg, corr_kernel, tmcx, tmcw);
}
```

```cpp
#include <cuda_runtime.h>
#include <cuda_bf16.h>
#include <cuda.h>
#include <stdint.h>

namespace {

constexpr int kL    = 7985;
constexpr int kRows = 8000;
constexpr int kMO   = 50;
constexpr int kNT   = 160;

constexpr int V0 = 7;
constexpr int NPRE = 6;
constexpr int RX = 4;
constexpr int PAUSE = 5;
constexpr int YSLEEP = 100;
constexpr int PRE1 = 4;
constexpr int TSLEEP = 200;
constexpr int MERGE = 1;
constexpr int RW = 10;

static_assert(V0 >= 7 && V0 <= 9 && RX >= 2 && RX <= 4 && RW >= V0 - 1 && RW <= 12, "rings must fit and be as deep as the look-ahead");
constexpr uint32_t HOME_MASK = 0xB;
constexpr uint32_t R_W = 64 * RX, NPAGES = (R_W + 22 * RW + 31) / 32;

__device__ __align__(1024) uint8_t g_sp[(size_t)(NPAGES + 1) * (2u << 20)];
__device__ __align__(128) unsigned g_tsel[32];
__device__ __forceinline__ uint32_t run_sel(uint32_t r, uint32_t group, uint32_t pmask) {
    return ((pmask >> (r >> 5)) ^ __popc(r & HOME_MASK) ^ group) & 1;
}
__device__ __forceinline__ uint32_t run_off(uint32_t r, uint32_t run, uint32_t group, uint32_t pmask) {
    return (r << 16) + 4096 + (run_sel(r, group, pmask) << 13) + (run << 14);
}
__device__ __forceinline__ unsigned* chunk_flag(uint8_t* sp, int done, int part, int chunk) {
    return reinterpret_cast<unsigned*>(sp + (4 + 3 * (chunk >> 5)) * 65536 + (done ? (part ? 15 : 13) : (part ? 0 : 14)) * 4096 + (chunk & 31) * 128);
}
__device__ __forceinline__ unsigned long long* part_sums(uint8_t* sp, int b, int db, uint32_t epoch) {
    return reinterpret_cast<unsigned long long*>(sp + (8 + 2 * db + ((__popc((8 + 2 * db) & HOME_MASK) ^ b) & 1)) * 65536 + 13 * 4096 + (epoch & 1) * 1024);
}
__device__ __forceinline__ unsigned* y_flag(uint8_t* sp, int b, int db) { return reinterpret_cast<unsigned*>(part_sums(sp, b, db, 0) + 512); }
__device__ __align__(256) float g_corr[16 * kNT * 64];
__device__ unsigned g_cready[4 * 32];
__device__ float g_direct[512 * 250 * 64];
__device__ unsigned long long g_dpart[2 * 512 * 64];
__device__ unsigned g_exit, g_epoch;

__device__ __forceinline__ uint32_t smem_u32(const void* p) { return (uint32_t)__cvta_generic_to_shared(p); }

__device__ __forceinline__ void mbar_init(uint32_t bar, uint32_t count) {
    asm volatile("mbarrier.init.shared::cta.b64 [%0], %1;" ::"r"(bar), "r"(count) : "memory");
}
__device__ __forceinline__ void mbar_expect_tx(uint32_t bar, uint32_t bytes) {
    asm volatile("mbarrier.arrive.expect_tx.shared::cta.b64 _, [%0], %1;" ::"r"(bar), "r"(bytes) : "memory");
}
__device__ __forceinline__ void mbar_arrive(uint32_t bar) {
    asm volatile("mbarrier.arrive.shared::cta.b64 _, [%0];" ::"r"(bar) : "memory");
}
__device__ __forceinline__ bool mbar_try(uint32_t bar, uint32_t parity) {
    uint32_t ok;
    asm volatile(
        "{\n.reg .pred p;\n"
        "mbarrier.try_wait.parity.shared::cta.b64 p, [%1], %2;\n"
        "selp.u32 %0, 1, 0, p;\n}\n"
        : "=r"(ok) : "r"(bar), "r"(parity) : "memory");
    return ok;
}
__device__ __forceinline__ bool mbar_test(uint32_t bar, uint32_t parity) {
    uint32_t ok;
    asm volatile(
        "{\n.reg .pred p;\n"
        "mbarrier.test_wait.parity.shared::cta.b64 p, [%1], %2;\n"
        "selp.u32 %0, 1, 0, p;\n}\n"
        : "=r"(ok) : "r"(bar), "r"(parity) : "memory");
    return ok;
}
__device__ __forceinline__ void mbar_wait(uint32_t bar, uint32_t parity) {
#pragma unroll 1
    for (uint32_t n = 0; n < (1u << 14); n++)
        if (mbar_try(bar, parity)) break;
}
__device__ __forceinline__ void fence_proxy_async_smem() { asm volatile("fence.proxy.async.shared::cta;" ::: "memory"); }
__device__ __forceinline__ void fence_mbar_init() { asm volatile("fence.mbarrier_init.release.cluster;" ::: "memory"); }

__device__ __forceinline__ void bulk_g2s(uint32_t dst, const void* src, uint32_t bytes, uint32_t bar) {
    asm volatile("cp.async.bulk.shared::cluster.global.mbarrier::complete_tx::bytes [%0], [%1], %2, [%3];"
                 ::"r"(dst), "l"(src), "r"(bytes), "r"(bar) : "memory");
}
__device__ __forceinline__ void tma3d_ef(uint32_t dst, const CUtensorMap* tm, int c0, int c1, int c2, uint32_t bar) {
    asm volatile("{\n.reg .b64 pol;\ncreatepolicy.fractional.L2::evict_first.b64 pol, 1.0;\n"
                 "cp.async.bulk.tensor.3d.shared::cluster.global.mbarrier::complete_tx::bytes.L2::cache_hint [%0], [%1, {%3, %4, %5}], [%2], pol;\n}"
                 ::"r"(dst), "l"(tm), "r"(bar), "r"(c0), "r"(c1), "r"(c2) : "memory");
}
__device__ __forceinline__ void tma3d(uint32_t dst, const CUtensorMap* tm, int c0, int c1, int c2, uint32_t bar) {
    asm volatile("cp.async.bulk.tensor.3d.shared::cluster.global.mbarrier::complete_tx::bytes [%0], [%1, {%3, %4, %5}], [%2];"
                 ::"r"(dst), "l"(tm), "r"(bar), "r"(c0), "r"(c1), "r"(c2) : "memory");
}
__device__ __forceinline__ void red_relaxed(unsigned* p) { asm volatile("red.relaxed.gpu.global.add.u32 [%0], 1;" ::"l"(p) : "memory"); }
__device__ __forceinline__ void named_arrive(int id, int n) { asm volatile("bar.arrive %0, %1;" ::"r"(id), "r"(n) : "memory"); }
__device__ __forceinline__ void named_bar(int id, int n) { asm volatile("bar.sync %0, %1;" ::"r"(id), "r"(n) : "memory"); }

__device__ __forceinline__ void wg_fence() { asm volatile("wgmma.fence.sync.aligned;" ::: "memory"); }
__device__ __forceinline__ void wg_commit() { asm volatile("wgmma.commit_group.sync.aligned;" ::: "memory"); }
template <int N> __device__ __forceinline__ void wg_wait() { asm volatile("wgmma.wait_group.sync.aligned %0;" ::"n"(N) : "memory"); }
template <int N> __device__ __forceinline__ void reg_fence(float (&d)[N]) {
#pragma unroll
    for (int i = 0; i < N; i++) asm volatile("" : "+f"(d[i])::"memory");
}

#define F4(a, i) "+f"(a[i]), "+f"(a[i + 1]), "+f"(a[i + 2]), "+f"(a[i + 3])
#define F8(a, i) F4(a, i), F4(a, i + 4)
#define F16(a, i) F8(a, i), F8(a, i + 8)

constexpr uint32_t HI128 = 0x40000040u;
__device__ __forceinline__ uint32_t desc_lo(uint32_t addr) { return (addr >> 4) | 0x10000u; }

#define R4(a, i) "+r"(a[i]), "+r"(a[i + 1]), "+r"(a[i + 2]), "+r"(a[i + 3])
#define R8(a, i) R4(a, i), R4(a, i + 4)
template <int N> __device__ __forceinline__ void reg_fence(uint32_t (&d)[N]) {
#pragma unroll
    for (int i = 0; i < N; i++) asm volatile("" : "+r"(d[i])::"memory");
}
__device__ __forceinline__ void tma2d(uint32_t dst, const CUtensorMap* tm, int c0, int c1, uint32_t bar) {
    asm volatile("cp.async.bulk.tensor.2d.shared::cluster.global.mbarrier::complete_tx::bytes [%0], [%1, {%3, %4}], [%2];"
                 ::"r"(dst), "l"(tm), "r"(bar), "r"(c0), "r"(c1) : "memory");
}
__device__ __forceinline__ void tma4d(uint32_t dst, const CUtensorMap* tm, int c0, int c1, int c2, int c3, uint32_t bar) {
    asm volatile("cp.async.bulk.tensor.4d.shared::cluster.global.mbarrier::complete_tx::bytes [%0], [%1, {%3, %4, %5, %6}], [%2];"
                 ::"r"(dst), "l"(tm), "r"(bar), "r"(c0), "r"(c1), "r"(c2), "r"(c3) : "memory");
}

template <int ACC>
__device__ __forceinline__ void wgmma_n64_sp(float (&d)[32], const uint32_t (&a)[4], uint32_t db, uint32_t meta) {
    asm volatile(
        "{\n.reg .pred p;\n.reg .b64 db;\nsetp.ne.b32 p, %39, 0;\nmov.b64 db, {%36, %38};\n"
        "wgmma.mma_async.sp.sync.aligned.m64n64k32.f32.bf16.bf16 "
        "{%0,%1,%2,%3,%4,%5,%6,%7,%8,%9,%10,%11,%12,%13,%14,%15,%16,%17,%18,%19,%20,%21,%22,%23,%24,%25,%26,%27,%28,%29,%30,%31},"
        "{%32,%33,%34,%35}, db, %37, 0, p, 1, 1, 1;\n}\n"
        : F16(d, 0), F16(d, 16)
        : "r"(a[0]), "r"(a[1]), "r"(a[2]), "r"(a[3]), "r"(db), "r"(meta), "n"(HI128), "n"(ACC));
}

template <int ACC>
__device__ __forceinline__ void wgmma_n56_ss(float (&d)[28], uint32_t da, uint32_t db) {
    asm volatile(
        "{\n.reg .pred p;\n.reg .b64 da, db;\nsetp.ne.b32 p, %31, 0;\nmov.b64 da, {%28, %30};\nmov.b64 db, {%29, %30};\n"
        "wgmma.mma_async.sync.aligned.m64n56k16.f32.f16.f16 "
        "{%0,%1,%2,%3,%4,%5,%6,%7,%8,%9,%10,%11,%12,%13,%14,%15,%16,%17,%18,%19,%20,%21,%22,%23,%24,%25,%26,%27},"
        "da, db, p, 1, 1, 1, 0;\n}\n"
        : F16(d, 0), F8(d, 16), F4(d, 24)
        : "r"(da), "r"(db), "n"(HI128), "n"(ACC));
}

template <int SA>
__device__ __forceinline__ void wgmma_n160_h(uint32_t (&d)[40], uint32_t da, uint32_t db) {
    asm volatile(
        "{\n.reg .pred p;\n.reg .b64 da, db;\nsetp.eq.b32 p, 0, 0;\nmov.b64 da, {%40, %43};\nmov.b64 db, {%41, %43};\n"
        "wgmma.mma_async.sync.aligned.m64n160k16.f16.f16.f16 "
        "{%0,%1,%2,%3,%4,%5,%6,%7,%8,%9,%10,%11,%12,%13,%14,%15,%16,%17,%18,%19,%20,%21,%22,%23,%24,%25,%26,%27,"
        "%28,%29,%30,%31,%32,%33,%34,%35,%36,%37,%38,%39},"
        "da, db, p, %42, 1, 1, 0;\n}\n"
        : R8(d, 0), R8(d, 8), R8(d, 16), R8(d, 24), R8(d, 32)
        : "r"(da), "r"(db), "n"(SA), "n"(HI128));
}
template <int SA>
__device__ __forceinline__ void wgmma_n160_hr(uint32_t (&d)[40], const uint32_t (&a)[4], uint32_t db) {
    asm volatile(
        "{\n.reg .pred p;\n.reg .b64 db;\nsetp.eq.b32 p, 0, 0;\nmov.b64 db, {%44, %46};\n"
        "wgmma.mma_async.sync.aligned.m64n160k16.f16.f16.f16 "
        "{%0,%1,%2,%3,%4,%5,%6,%7,%8,%9,%10,%11,%12,%13,%14,%15,%16,%17,%18,%19,%20,%21,%22,%23,%24,%25,%26,%27,"
        "%28,%29,%30,%31,%32,%33,%34,%35,%36,%37,%38,%39},"
        "{%40,%41,%42,%43}, db, p, %45, 1, 0;\n}\n"
        : R8(d, 0), R8(d, 8), R8(d, 16), R8(d, 24), R8(d, 32)
        : "r"(a[0]), "r"(a[1]), "r"(a[2]), "r"(a[3]), "r"(db), "n"(SA), "n"(HI128));
}
template <int SA>
__device__ __forceinline__ void wgmma_n160_f(float (&d)[80], uint32_t da, uint32_t db) {
    asm volatile(
        "{\n.reg .pred p;\n.reg .b64 da, db;\nsetp.eq.b32 p, 0, 0;\nmov.b64 da, {%80, %83};\nmov.b64 db, {%81, %83};\n"
        "wgmma.mma_async.sync.aligned.m64n160k16.f32.bf16.bf16 "
        "{%0,%1,%2,%3,%4,%5,%6,%7,%8,%9,%10,%11,%12,%13,%14,%15,%16,%17,%18,%19,%20,%21,%22,%23,%24,%25,%26,%27,"
        "%28,%29,%30,%31,%32,%33,%34,%35,%36,%37,%38,%39,%40,%41,%42,%43,%44,%45,%46,%47,%48,%49,%50,%51,%52,%53,%54,%55,"
        "%56,%57,%58,%59,%60,%61,%62,%63,%64,%65,%66,%67,%68,%69,%70,%71,%72,%73,%74,%75,%76,%77,%78,%79},"
        "da, db, p, %82, 1, 1, 0;\n}\n"
        : F16(d, 0), F16(d, 16), F16(d, 32), F16(d, 48), F16(d, 64)
        : "r"(da), "r"(db), "n"(SA), "n"(HI128));
}

__device__ __forceinline__ uint32_t pack_f16(float lo, float hi) {
    uint32_t r;
    asm("cvt.rn.f16x2.f32 %0, %1, %2;" : "=r"(r) : "f"(hi), "f"(lo));
    return r;
}
__device__ __forceinline__ uint32_t mul_bf16x2(uint32_t a, uint32_t b) {
    uint32_t r;
    asm("mul.rn.bf16x2 %0, %1, %2;" : "=r"(r) : "r"(a), "r"(b));
    return r;
}
__device__ __forceinline__ void sts128(uint32_t p, uint32_t a, uint32_t b, uint32_t c, uint32_t d) {
    asm volatile("st.shared.v4.b32 [%0], {%1,%2,%3,%4};" ::"r"(p), "r"(a), "r"(b), "r"(c), "r"(d) : "memory");
}
__device__ __forceinline__ uint32_t pack_bf16(float lo, float hi) {
    uint32_t r;
    asm("cvt.rn.bf16x2.f32 %0, %1, %2;" : "=r"(r) : "f"(hi), "f"(lo));
    return r;
}
__device__ __forceinline__ void stg128(void* p, uint32_t a, uint32_t b, uint32_t c, uint32_t d) {
    asm volatile("st.global.v4.b32 [%0], {%1,%2,%3,%4};" ::"l"(p), "r"(a), "r"(b), "r"(c), "r"(d) : "memory");
}
__device__ __forceinline__ void stmatrix_x4_t(uint32_t addr, uint32_t a, uint32_t b, uint32_t c, uint32_t d) {
    asm volatile("stmatrix.sync.aligned.m8n8.x4.trans.shared.b16 [%0], {%1,%2,%3,%4};"
                 ::"r"(addr), "r"(a), "r"(b), "r"(c), "r"(d) : "memory");
}

constexpr uint32_t cos64(int k, bool half) {
    constexpr uint16_t q[17] = {0x3F80, 0x3F7F, 0x3F7B, 0x3F75, 0x3F6D, 0x3F62, 0x3F55, 0x3F46, 0x3F35, 0x3F22, 0x3F0E, 0x3EF1, 0x3EC4, 0x3E95, 0x3E48, 0x3DC9, 0x0000};
    constexpr uint16_t h[17] = {0x3C00, 0x3BF6, 0x3BD9, 0x3BA8, 0x3B64, 0x3B0E, 0x3AA7, 0x3A2F, 0x39A8, 0x3913, 0x3872, 0x378B, 0x361F, 0x34A5, 0x323E, 0x2E46, 0x0000};
    k &= 63;
    if (k > 32) k = 64 - k;
    const uint16_t* t = half ? h : q;
    return k <= 16 ? t[k] : (t[32 - k] | 0x8000u);
}
constexpr int freq(int s) { return s <= 16 ? s : 64 - s; }
constexpr uint32_t tap_coef(int s, int p, int t) { return (p && s == 0) ? cos64(32 * t, false) : cos64(freq(s) * t - 16 * p, false); }
constexpr uint32_t x_coef(int s, int p, int t) { return s ? cos64(s * t - 16 * p, false) : p ? cos64(16 * t + 16 * (t & 1), false) : cos64(0, false); }
constexpr uint32_t inv_coef(int l, int phi) {
    const int s = phi >> 1, p = phi & 1;
    if (l >= kMO) return 0;
    if (s == 16) return (0x3C00u - (6 << 10)) | ((((l + 1 - p) >> 1) ^ p) & 1) << 15;
    const uint32_t c = s == 0 ? cos64(32 * l * p, true) : cos64(freq(s) * l + 16 * p, true);
    return (c & 0x7FFF) ? c - ((s == 0 ? 6 : 5) << 10) : 0;
}
struct Tables {
    uint32_t fx[1024];
    uint32_t tap[512];
    uint32_t inv[2048];
};
constexpr Tables make_tables() {
    Tables t = {};
    for (int i = 0; i < 1024; i++) {
        const int g = (i >> 5) & 7, s = 4 * (i >> 8) + (g >> 1), j = 8 * ((i >> 1) & 3) + 2 * ((i >> 3) & 3), h = i & 1;
        t.fx[i] = x_coef(s, g & 1, 2 * j + h) | (x_coef(s, g & 1, 2 * j + 2 + h) << 16);
    }
    for (int i = 0; i < 512; i++) {
        const int row = i >> 3, s = 8 * (row >> 4) + (row & 7), p = (row >> 3) & 1;
        t.tap[i] = tap_coef(s, p, 2 * (i & 7)) | (tap_coef(s, p, 2 * (i & 7) + 1) << 16);
    }
    for (int i = 0; i < 2048; i++) {
        const int row = i >> 5, tt = 8 * (((i >> 2) & 7) ^ (row & 7)) + 2 * (i & 3);
        t.inv[i] = inv_coef(row, tt) | (inv_coef(row, tt + 1) << 16);
    }
    return t;
}
__device__ __align__(128) const Tables g_tab = make_tables();

constexpr int NCTA = 128;
constexpr int NST = 4;
constexpr int HEND = 56;
constexpr int XB = kNT * 128;
constexpr int OFF_W1 = 0, OFF_X = OFF_W1 + NST * 8192, OFF_W0 = OFF_X + 4 * XB, OFF_RAW = OFF_W0 + NST * 8192;
constexpr int OFF_STG = OFF_RAW + 32768;
constexpr int OFF_U0 = OFF_W0, OFF_U1 = OFF_X, OFF_C1 = OFF_W1, OFF_DIR = OFF_W1 + 8192;
constexpr int OFF_F = OFF_RAW + 65536;
constexpr int OFF_C0 = OFF_F + 8192;
constexpr int OFF_TMP = OFF_C0, OFF_BAR = OFF_C0 + 4096;
constexpr int B_FULL = 0, B_EMPTY = 8 * NST, B_TSEL = 16 * NST, B_PRE = B_TSEL + 8, B_SIG = B_PRE + 16 * V0, B_YS = B_SIG + 8 * 33,
              B_T2 = B_YS + 8 * 4, B_SUM = B_T2 + 16, B_GATE = B_SUM + 32, B_RDY = B_GATE + 8 * 32, B_PUB = B_RDY + 8 * 33, B_UNIT = B_PUB + 8,
              B_FTAB = B_UNIT + 8 * 20, B_C1 = B_FTAB + 8, B_NRM = B_C1 + 8, B_END = B_NRM + 32;
template <int O0, int O1>
__device__ __forceinline__ void bar_setup(uint32_t bars) {
#pragma unroll
    for (int o = O0; o < O1; o += 8)
        mbar_init(bars + o, o < B_EMPTY ? 2 : o < B_TSEL ? 8 : o == B_TSEL ? 2 : o < B_SIG ? 1 : o < B_YS - 8 ? 8 : o < B_GATE ? 4 : 1);
    fence_mbar_init();
    fence_proxy_async_smem();
}
constexpr int OFF_TS = OFF_BAR + B_END;
constexpr int OFF_PLAN = OFF_TS + 336;
constexpr int OFF_YT = OFF_PLAN + (V0 + 65) * 8;
constexpr int OFF_GB = (OFF_YT + 4 * kNT * 4 + 15) & ~15;
constexpr int MAIN_SMEM = OFF_GB + 2048;
static_assert(MAIN_SMEM <= 232448 && OFF_U0 + 10 * 8192 == OFF_STG + 16384, "shared memory");
constexpr uint32_t META = 0xDDDD8888u;
constexpr int XPC = 2 * kNT;
constexpr unsigned PROBE_NEAR = 400;

__device__ __forceinline__ uint32_t raw_slot(uint32_t sbase, uint32_t v, int wg) { return sbase + OFF_RAW + ((v & 3) * 2 + wg) * 8192; }

__device__ __forceinline__ uint32_t pre_slot(uint32_t sbase, uint32_t v, int wg) {
    return v < 4 ? raw_slot(sbase, v, wg) : v < 8 ? sbase + OFF_X + (v - 4) * XB + wg * 8192 : sbase + (wg ? OFF_W1 : OFF_W0) + ((V0 + 3) % NST) * 8192;
}

template <bool DC, int I>
__device__ __forceinline__ void gemm_mma(uint32_t (&a0)[40], uint32_t (&a1)[40], uint32_t dx0, uint32_t dx1, uint32_t dw) {
    constexpr int ks = I >> 2;
    const uint32_t A0 = dw + ks * 128, A1 = A0 + 256, B0 = dx0 + ks * 2, B1 = dx1 + ks * 2;
    if ((I & 3) == 0) wgmma_n160_h<1>(a0, A0, B0);
    if ((I & 3) == 1) wgmma_n160_h<1>(a1, A1, DC ? B1 : B0);
    if ((I & 3) == 2 && !DC) wgmma_n160_h<1>(a0, A1, B1);
    if ((I & 3) == 3 && !DC) wgmma_n160_h<-1>(a1, A0, B1);
}

template <bool DC, int I0, int I1>
__device__ __forceinline__ void gemm_mmas(uint32_t (&a0)[40], uint32_t (&a1)[40], uint32_t dx0, uint32_t dx1, uint32_t dw) {
    if constexpr (I0 < I1) {
        gemm_mma<DC, I0>(a0, a1, dx0, dx1, dw);
        gemm_mmas<DC, I0 + 1, I1>(a0, a1, dx0, dx1, dw);
    }
}
static_assert(RX == 4 && RW == 10, "placement of the output spectra");
__device__ __forceinline__ uint32_t y_unit(uint32_t db, uint32_t tau, uint32_t b, uint32_t pmask) {
    const uint32_t n = (((db >> 1) & 2) + (db & 1)) * XPC + ((db >> 1) & 1) * kNT + tau, r = n / 3;
    return run_off(r + (r >= 192 && r < 278 ? (r < 214 ? 64 : -22) : 0), n % 3, b, pmask);
}
__device__ __forceinline__ int y_gate(int t) { return t ? 28 + t : 27; }
__device__ __forceinline__ int step_k(int h) { return h < HEND ? h >> 1 : 28 + (h & 3); }
__device__ __forceinline__ int step_m(int h) { return h < HEND ? h & 1 : (h >> 2) & 1; }
constexpr uint64_t x_mask() {
    uint64_t r = 2 | (3ull << 58);
    for (int v = 2; v < 58; v++)
        if ((0x73 >> (v & 7)) & 1) r |= 1ull << v;
    return r;
}
constexpr uint64_t XMASK = x_mask();
__device__ __forceinline__ int x_round(int v, int wg) {
    return v == 0 ? wg : (v < 60 && wg != (v & 1) && ((XMASK >> v) & 1)) ? 1 + __popcll(XMASK << (63 - v)) : -1;
}
__device__ __forceinline__ int w_step(int v, int wg) {
    return v == 0 ? -1 : v < 60 ? (wg == (v & 1) ? v - 1 : -1) : v < 62 ? 2 * v - 61 + wg : (v == 62 && wg == 1) ? 63 : -1;
}

__device__ __forceinline__ uint32_t plan_word(int v, int wg, int cta) {
    const int r = x_round(v, wg), h = w_step(v, wg);
    if (r < 0 && h < 0) return 0;
    const bool last = v >= 60 || (v & 1) || (v > 0 && wg == 0 && x_round(v + 1, 0) < 0);
    uint32_t off, row, gate;
    if (r >= 0) {
        const int u = r * NCTA + cta, cb = u / XPC, i = u - cb * XPC, b = i >= kNT, tau = i - b * kNT;
        row = tau & 63;
        off = (((cb % RX) * 64 + b) << 16) + ((tau >> 6) << 14) + b + 2;
        gate = cb >= RX ? 2 * (cb - RX) + 2 : 0;
    } else {
        const int ring = (h + RW - 64 % RW) % RW;
        row = 0;
        off = ((ring * 22) << 16) + (ring << 12) + 4;
        gate = h >= RW ? ((h - RW + 1) >> 1) + 1 : 0;
    }
    return (off + row * 128) | ((row & 7) << 4) | (last << 3) | ((v > 60) << 24) | (gate << 26);
}

struct Xf {
    uint32_t sbase;
    uint8_t *px[2], *pw;
    uint32_t cx, cw;
    uint32_t fx[2][4];
    uint32_t g[4];
    uint32_t dw;
    uint32_t e;
    int lane;
};
__device__ __forceinline__ uint32_t plan_load(const Xf& f, uint32_t v, int wg) {
    uint32_t e;
    asm volatile("ld.shared.u32 %0, [%1];" : "=r"(e) : "r"(f.sbase + OFF_PLAN + v * 8 + wg * 4));
    return __shfl_sync(0xffffffffu, e, 0);
}
template <bool W>
__device__ __forceinline__ void unit_mma(float (&acc)[32], const Xf& f, uint32_t raw) {
    const uint32_t dB = desc_lo(raw);
    if (W) {
        wgmma_n64_sp<0>(acc, f.g, dB, META);
    } else {
        wgmma_n64_sp<0>(acc, f.fx[0], dB, META);
        wgmma_n64_sp<1>(acc, f.fx[1], dB + 256, META);
    }
    wg_commit();
}
constexpr int DROP = 3;
__device__ __forceinline__ uint32_t pack_sp(float lo, float hi) {
    const uint32_t r = pack_f16(lo, hi);
    return DROP ? (r + (0x10001u << DROP >> 1)) & ~(((1u << DROP) - 1) * 0x10001u) : r;
}
__device__ __forceinline__ void st_quad(uint8_t* p, const float (&acc)[32], int j0) {
    stg128(p, pack_sp(acc[j0], acc[j0 + 1]), pack_sp(acc[j0 + 4], acc[j0 + 5]), pack_sp(acc[j0 + 8], acc[j0 + 9]),
           pack_sp(acc[j0 + 12], acc[j0 + 13]));
}
template <bool W>
__device__ __forceinline__ void unit_store(float (&acc)[32], const Xf& f, uint32_t e) {
    if (W) {
        const uint32_t o = (e & 0xFF0F80u) + ((e ^ f.cw) & 0x70) + (((f.cw >> (8 + ((e >> 12) & 15))) & 1) << 13);
        uint8_t *p0 = f.pw + o, *p1 = f.pw + (o ^ 64);
        reg_fence(acc);
        st_quad(p0, acc, 0);
        st_quad(p1, acc, 16);
        st_quad(f.pw + ((o ^ 16) + 128), acc, 2);
        st_quad(f.pw + ((o ^ 80) + 128), acc, 18);
    } else {
        uint8_t* p[2][2];
#pragma unroll
        for (int i = 0; i < 2; i++) {
            const uint32_t c = f.cx >> (16 * i), sel = ((e ^ (c >> (8 + ((e >> 21) & 6)))) & 1) << 13, o = (e & 0xFFFF80u) + ((e ^ c) & 0x70);
            p[i][0] = f.px[i] + (o + sel);
            p[i][1] = f.px[i] + (o + 131072 + 8192 - sel);
        }
        reg_fence(acc);
#pragma unroll
        for (int i = 0; i < 32; i++)
            if (!(i & 2)) {
                const float ev = acc[i], od = acc[i + 2];
                acc[i] = ev + od;
                acc[i + 2] = ev - od;
            }
        st_quad(p[0][0], acc, 0);
        st_quad(p[1][0], acc, 2);
        st_quad(p[0][1], acc, 16);
        st_quad(p[1][1], acc, 18);
    }
}
__device__ __forceinline__ void unit_done(const Xf& f, uint32_t e, uint32_t v) {
    if (e & 8) {
        __syncwarp();
        if (f.lane == 0) mbar_arrive(f.sbase + OFF_BAR + B_SIG + 8 * ((v >> 1) + ((e >> 24) & 1)));
    }
}
__device__ __forceinline__ void step_wait(Xf& f, uint32_t v, int wg) {
    const uint32_t bars = f.sbase + OFF_BAR;
    mbar_wait(bars + B_FULL + 8 * (v % NST), (v / NST) & 1);
}

template <bool DC, int KIND>
__device__ __forceinline__ void gemm_step(uint32_t (&a0)[40], uint32_t (&a1)[40], float (&at)[32], Xf& f, uint32_t v, uint32_t xs, int wg, bool first) {
    const uint32_t bars = f.sbase + OFF_BAR, sb = desc_lo(f.sbase), xb = sb + OFF_X / 16 + xs * (XB / 16), raw = raw_slot(f.sbase, v, wg);
    const uint32_t dx0 = xb, dx1 = xb + 4, dw = f.dw + (v % NST) * 512, e = f.e;
    wg_fence();
    if (KIND) unit_mma<KIND != 1>(at, f, raw);
    constexpr int N1 = KIND == 0 ? 2 : NPRE;
    gemm_mmas<DC, 0, N1>(a0, a1, dx0, dx1, dw);
    wg_commit();
    const uint32_t gate = bars + ((e >> 26) ? B_GATE - 8 + 8 * (e >> 26) : B_PUB);
    const bool open = !KIND || mbar_test(gate, 0);
    f.e = plan_load(f, v + 1, wg);
    wg_wait<1>();
    if (!open) mbar_wait(gate, 0);
    if (!KIND && !first && f.lane == 0) mbar_arrive(bars + B_EMPTY + 8 * ((v - 1) % NST));
    if (KIND) unit_store<KIND != 1>(at, f, e);
    if (KIND) unit_done(f, e, v);
    gemm_mmas<DC, N1, 7>(a0, a1, dx0, dx1, dw);
    if (KIND && !first && f.lane == 0) mbar_arrive(bars + B_EMPTY + 8 * ((v - 1) % NST));
    gemm_mma<DC, 7>(a0, a1, dx0, dx1, dw);
    wg_commit();
}
template <bool DC>
__device__ __forceinline__ void any_step(uint32_t (&a0)[40], uint32_t (&a1)[40], float (&at)[32], Xf& f, uint32_t v, uint32_t xs, int wg, bool first) {
    step_wait(f, v, wg);
    const uint32_t kind = (f.e >> 1) & 3;
    if (kind == 1) gemm_step<DC, 1>(a0, a1, at, f, v, xs, wg, first);
    else if (kind == 2) gemm_step<DC, 2>(a0, a1, at, f, v, xs, wg, first);
    else gemm_step<DC, 0>(a0, a1, at, f, v, xs, wg, first);
}
template <bool DC>
__device__ __forceinline__ void gemm_main(uint32_t (&a0)[40], uint32_t (&a1)[40], uint32_t (&b0)[40], uint32_t (&b1)[40], Xf& f, int wg) {
    float at[32];
#pragma unroll 1
    for (uint32_t k = 0; k < HEND / 2; k++) {
        any_step<DC>(a0, a1, at, f, V0 + 2 * k, k & 3, wg, k == 0);
        any_step<DC>(b0, b1, at, f, V0 + 2 * k + 1, k & 3, wg, false);
    }
    wg_wait<0>();
    if (f.lane == 0) mbar_arrive(f.sbase + OFF_BAR + B_EMPTY + 8 * ((V0 + HEND - 1) % NST));
}
__device__ __forceinline__ void w_fetch(uint32_t (&d)[4][4], const Xf& f, uint32_t v) {
    const uint32_t bars = f.sbase + OFF_BAR, lane = f.lane;
    const uint32_t wa = ((f.dw & 0xFFFF) << 4) + (v % NST) * 8192 + (lane >> 4) * 1024 + (lane & 7) * 128 +
                        (((((threadIdx.x >> 4) & 6) + ((lane >> 3) & 1)) ^ (lane & 7)) << 4);
    mbar_wait(bars + B_FULL + 8 * (v % NST), (v / NST) & 1);
#pragma unroll
    for (int i = 0; i < 4; i++)
        asm volatile("ldmatrix.sync.aligned.m8n8.x4.trans.shared.b16 {%0,%1,%2,%3}, [%4];" : "=r"(d[i][0]), "=r"(d[i][1]), "=r"(d[i][2]), "=r"(d[i][3])
                     : "r"(wa + i * 2048) : "memory");
}
__device__ __forceinline__ void store_tile(uint32_t (&a0)[40], uint32_t (&a1)[40], const uint32_t (&b0)[40], const uint32_t (&b1)[40], uint32_t (&wn)[4][4],
                                           const Xf& f, bool first, uint32_t stg, int t, int wg, uint8_t* sp, int slot, uint32_t ytab, int wsw) {
    const int w = t >> 5, lane = t & 31, m = lane >> 3, i8 = lane & 7;
    const uint32_t addr = stg + i8 * 256 + (m >> 1) * 128 + (((2 * w + (m & 1)) ^ i8 ^ wsw) << 4);
    const int row = 2 * w + (lane >> 4), phi = 2 * slot + (m & 1);
    const uint32_t src = stg + row * 256 + (m & 1) * 128 + ((i8 ^ row) << 4);
    uint8_t* dst = sp + phi * 128 + ((i8 ^ (phi & 7)) << 4);
    named_bar(2 + wg, 128);
#pragma unroll
    for (int r = 0; r < 6; r++) {
        uint32_t v[4][4], o[4];
        if (r > 0) {
#pragma unroll
            for (int i = 0; i < 4; i++) {
                asm volatile("ld.shared.u32 %0, [%1];" : "=r"(o[i]) : "r"(ytab + (32 * (r - 1) + 8 * i + row) * 4) : "memory");
                asm volatile("ld.shared.v4.b32 {%0,%1,%2,%3}, [%4];" : "=r"(v[i][0]), "=r"(v[i][1]), "=r"(v[i][2]), "=r"(v[i][3])
                             : "r"(src + ((r - 1) & 1) * 8192 + i * 2048) : "memory");
            }
        }
        if (r < 5) {
#pragma unroll
            for (int j = 4 * r; j < 4 * r + 4; j++) stmatrix_x4_t(addr + (r & 1) * 8192 + (j & 3) * 2048, a0[2 * j], a0[2 * j + 1], a1[2 * j], a1[2 * j + 1]);
#pragma unroll
            for (int j = 8 * r; j < 8 * r + 8; j++) {
                asm volatile("mov.b32 %0, %1;" : "=r"(a0[j]) : "r"(b0[j]));
                asm volatile("mov.b32 %0, %1;" : "=r"(a1[j]) : "r"(b1[j]));
            }
        } else if (first) {
            w_fetch(wn, f, V0 + HEND + 4);
        }
        if (r > 0) {
#pragma unroll
            for (int i = 0; i < 4; i++) stg128(dst + o[i], v[i][0], v[i][1], v[i][2], v[i][3]);
        }
        if (r < 5) named_bar(2 + wg, 128);
    }
}

template <bool DC>
__device__ __forceinline__ void gemm_last(uint32_t (&a0)[40], uint32_t (&a1)[40], uint32_t (&w)[2][4][4], const Xf& f, int wg, int m) {
    const uint32_t bars = f.sbase + OFF_BAR, sb = desc_lo(f.sbase), v0 = V0 + HEND + 4 * m;
    if (2 * m + wg > 0) named_bar(3 + 2 * m + wg, 256);
#pragma unroll
    for (uint32_t k = 0; k < 4; k++) {
        const uint32_t dx0 = sb + OFF_X / 16 + k * (XB / 16), dx1 = dx0 + 4;
        wg_fence();
#pragma unroll
        for (int ks = 0; ks < 2; ks++) {
            wgmma_n160_hr<1>(a0, w[k & 1][ks], dx0 + 2 * ks);
            wgmma_n160_hr<1>(a1, w[k & 1][2 + ks], (DC ? dx1 : dx0) + 2 * ks);
            if (!DC) wgmma_n160_hr<1>(a0, w[k & 1][2 + ks], dx1 + 2 * ks);
            if (!DC) wgmma_n160_hr<-1>(a1, w[k & 1][ks], dx1 + 2 * ks);
        }
        wg_commit();
        if (m == 0 && f.lane == 0) mbar_arrive(bars + B_EMPTY + 8 * ((v0 + k) % NST));
        if (k == 3 && 2 * m + wg < 3) named_arrive(4 + 2 * m + wg, 256);
        if (k > 0) wg_wait<1>();
        if (k < 3) w_fetch(w[(k + 1) & 1], f, v0 + k + 1);
    }
    wg_wait<0>();
    if (m && f.lane == 0) mbar_arrive(bars + B_T2 + 8 * wg);
}

__device__ __forceinline__ float gelu_half(float hv) {
    float th;
    asm("tanh.approx.f32 %0, %1;" : "=f"(th) : "f"(hv * fmaf(hv * hv, 8.0f * 0.7978845608028654f * 0.044715f, 2.0f * 0.7978845608028654f)));
    return fmaf(hv, th, hv);
}
__device__ __noinline__ void direct_block(const __nv_bfloat16* __restrict__ x, const __nv_bfloat16* __restrict__ w,
                                          const __nv_bfloat16* __restrict__ gamma, const __nv_bfloat16* __restrict__ beta,
                                          __nv_bfloat16* __restrict__ out, float* sm, int b, int db, int part, uint32_t epoch) {
    float *xs = sm, *ws = sm + 32 * 17, *red = ws + 16 * 65;
    const int tid = threadIdx.x & 127, bar = 2 + (threadIdx.x >> 7), tx = tid & 15, ty = tid >> 4, row0 = part * 250, lim = min(250, kL - row0);
    float* h = g_direct + (size_t)((b * 8 + db) * 32 + part) * (250 * 64);
    for (int l0 = 0; l0 < lim; l0 += 32) {
        float acc[4][4] = {};
        for (int k0 = 0; k0 < 31 * 512; k0 += 16) {
            named_bar(bar, 128);
            for (int i = tid; i < 1024; i += 128) {
                if (i < 512) xs[(i >> 4) * 17 + (i & 15)] = __bfloat162float(x[((size_t)b * kRows + row0 + min(l0 + (i >> 4), lim - 1)) * 1024 + k0 + (i & 15)]);
                ws[(i >> 6) * 65 + (i & 63)] = __bfloat162float(w[(size_t)(k0 + (i >> 6)) * 512 + 64 * db + (i & 63)]);
            }
            named_bar(bar, 128);
            for (int k = 0; k < 16; k++)
#pragma unroll
                for (int i = 0; i < 4; i++)
#pragma unroll
                    for (int j = 0; j < 4; j++) acc[i][j] = fmaf(xs[(ty * 4 + i) * 17 + k], ws[k * 65 + tx * 4 + j], acc[i][j]);
        }
#pragma unroll
        for (int i = 0; i < 4; i++)
#pragma unroll
            for (int j = 0; j < 4; j++)
                if (l0 + ty * 4 + i < lim) h[(l0 + ty * 4 + i) * 64 + tx * 4 + j] = acc[i][j];
    }
    const int c = tid & 63;
    float mean = 0.f, var = 0.f;
    for (int r = 0; r < 2; r++) {
        named_bar(bar, 128);
        float s = 0.f;
        for (int l = tid >> 6; l < lim; l += 2) {
            const float v = h[l * 64 + c] - mean;
            s += r ? v * v : v;
        }
        red[tid] = s;
        named_bar(bar, 128);
        unsigned long long* p = g_dpart + ((r * 16 + b * 8 + db) * 32) * 64 + c;
        if (tid < 64)
            asm volatile("st.relaxed.gpu.global.v2.b32 [%0], {%1, %2};" ::"l"(p + part * 64), "r"(__float_as_uint(red[c] + red[64 + c])), "r"(epoch) : "memory");
        s = 0.f;
        for (int k = 0; k < 32; k++) {
            unsigned long long v = 0;
#pragma unroll 1
            for (uint32_t n = 0; n < (1u << 19); n++) {
                asm volatile("ld.relaxed.gpu.global.u64 %0, [%1];" : "=l"(v) : "l"(p + k * 64) : "memory");
                if ((uint32_t)(v >> 32) == epoch) break;
                __nanosleep(200);
            }
            s += __uint_as_float((uint32_t)v);
        }
        (r ? var : mean) = s * (1.0f / kL);
    }
    const float a = __bfloat162float(gamma[64 * db + c]) / sqrtf(var + 1e-5f), be = __bfloat162float(beta[64 * db + c]);
    for (int l = tid >> 6; l < lim; l += 2)
        out[((size_t)b * kL + row0 + l) * 512 + 64 * db + c] = __float2bfloat16(gelu_half(0.5f * fmaf(h[l * 64 + c] - mean, a, be)));
    named_bar(bar, 128);
}

__device__ __forceinline__ int tail_block(uint32_t gr, int t) { return 4 * (t >> 1) + ((gr >> 4) & 2) + (t & 1); }
__device__ __forceinline__ void tail_poll(uint8_t* sp, uint32_t gr, int t) {
#pragma unroll 1
    for (uint32_t n = 0; n < (1u << 15); n++) {
        unsigned v;
        asm volatile("ld.relaxed.gpu.global.u32 %0, [%1];" : "=r"(v) : "l"(y_flag(sp, gr >> 6, tail_block(gr, t))) : "memory");
        if (v >= 32) break;
        __nanosleep(YSLEEP);
    }
    asm volatile("fence.acquire.gpu;" ::: "memory");
    asm volatile("fence.proxy.async.global;" ::: "memory");
}
__device__ __forceinline__ const float* corr_src(uint32_t gr, int t) { return &g_corr[(((gr >> 6) * 8 + tail_block(gr, t)) * kNT + (gr & 31) * 5) * 64]; }
__device__ __forceinline__ void corr_load(uint32_t sbase, uint32_t gr, int t, uint32_t bar) {
    bulk_g2s(sbase + (t < 2 ? OFF_C0 : OFF_C1) + (t & 1) * 1280, corr_src(gr, t), 1280, bar);
}
__device__ __forceinline__ void tail_phase(uint32_t sbase, uint8_t* smem, uint8_t* sp, int wg, uint32_t gr, float sx, float sw, const __nv_bfloat16* __restrict__ x,
                                           const __nv_bfloat16* __restrict__ wt, const __nv_bfloat16* __restrict__ gamma,
                                           const __nv_bfloat16* __restrict__ beta, __nv_bfloat16* __restrict__ out) {
    const uint32_t* ts = reinterpret_cast<const uint32_t*>(smem + OFF_TS);
    const int tid = threadIdx.x, w = (tid >> 5) & 3, lane = tid & 31, g = lane >> 2, q = lane & 3;
    const int b = gr >> 6, part = gr & 31;
#pragma unroll 1
    for (int rd = 0; rd < 3; rd++) {
        if (rd < 2) {
            float acc[28], acc2[28], s[8] = {0.f, 0.f, 0.f, 0.f, 0.f, 0.f, 0.f, 0.f};
            const float swq = q == 0 ? sw : 0.f;
            const int t = 2 * rd + wg;
            const uint32_t ub = sbase + (t < 2 ? OFF_U0 : OFF_U1) + (t & 1) * 40960, ubar = sbase + OFF_BAR + B_UNIT + 40 * t;
            const float* c1 = reinterpret_cast<const float*>(smem + (t < 2 ? OFF_C0 : OFF_C1) + (t & 1) * 1280) + 16 * w + g;
            const uint32_t ka = ub + (lane >> 4) * 1024 + (lane & 7) * 128 + (((2 * w + ((lane >> 3) & 1)) ^ (lane & 7)) << 4);
            auto inverse = [&](float (&d)[28], int u) {
                const uint32_t dA = desc_lo(ub + u * 8192), dB = desc_lo(sbase + OFF_F);
                wg_fence();
                wgmma_n56_ss<0>(d, dA, dB);
                wgmma_n56_ss<1>(d, dA + 128, dB + 2);
                wgmma_n56_ss<1>(d, dA + 256, dB + 4);
                wgmma_n56_ss<1>(d, dA + 384, dB + 6);
                wg_commit();
            };
            auto keep = [&](float (&d)[28], int u, int un) {
                const bool ok = mbar_try(ubar + 8 * un, 0);
                reg_fence(d);
                d[25] = fmaf(c1[u * 64] * sx, swq, d[25]);
                d[27] = fmaf(c1[u * 64 + 8] * sx, swq, d[27]);
                if (part == 31 && u == 4) {
                    if (q >= 2) d[16] = d[18] = 0.f;
                    if (q >= 1) d[17] = d[19] = 0.f;
#pragma unroll
                    for (int i = 20; i < 28; i++) d[i] = 0.f;
                }
                const uint32_t a = ka + u * 8192;
#pragma unroll
                for (int j = 0; j < 6; j += 2)
                    stmatrix_x4_t(a + j * 1024, pack_f16(d[4 * j], d[4 * j + 1]), pack_f16(d[4 * j + 2], d[4 * j + 3]),
                                  pack_f16(d[4 * j + 4], d[4 * j + 5]), pack_f16(d[4 * j + 6], d[4 * j + 7]));
                asm volatile("stmatrix.sync.aligned.m8n8.x2.trans.shared.b16 [%0], {%1,%2};"
                             ::"r"(a + 6 * 1024), "r"(pack_f16(d[24], d[25])), "r"(pack_f16(d[26], d[27])) : "memory");
#pragma unroll
                for (int i = 0; i < 28; i++) {
                    s[i & 3] += d[i];
                    s[4 + (i & 3)] = fmaf(d[i], d[i], s[4 + (i & 3)]);
                }
#pragma unroll
                for (int i = 0; i < 8; i++) asm volatile("" : "+f"(s[i]));
                if (!ok) mbar_wait(ubar + 8 * un, 0);
                wg_wait<0>();
            };
            if (t >= 2) mbar_wait(sbase + OFF_BAR + B_C1, 0);
            mbar_wait(ubar, 0);
            inverse(acc, 0);
            mbar_wait(ubar + 8, 0);
            wg_wait<0>();
#pragma unroll 1
            for (int u = 0;; u += 2) {
                inverse(acc2, min(u + 1, 4));
                keep(acc, u, min(u + 2, 4));
                if (u == 4) break;
                inverse(acc, u + 2);
                keep(acc2, u + 1, min(u + 3, 4));
            }
#pragma unroll
            for (int i = 0; i < 4; i++) s[i] = s[2 * i] + s[2 * i + 1];
#pragma unroll
            for (int i = 0; i < 2; i++) s[i] = (q & 2 ? s[2 + i] : s[i]) + __shfl_xor_sync(0xffffffffu, q & 2 ? s[i] : s[2 + i], 2);
            const float mine = (q & 1 ? s[1] : s[0]) + __shfl_xor_sync(0xffffffffu, q & 1 ? s[0] : s[1], 1);
            asm volatile("red.relaxed.gpu.global.add.u64 [%0], %1;"
                         ::"l"(part_sums(sp, b, tail_block(gr, t), ts[76]) + 2 * (16 * w + 8 * (q & 1) + g) + (q >> 1)),
                         "l"(fabsf(mine) < 0x1p25f ? __float2ll_rn(mine * 0x1p21f) * 4096 + 1 : 65ll) : "memory");
            __syncwarp();
            if (lane == 0) mbar_arrive(sbase + OFF_BAR + B_SUM + 8 * t);
            if (rd == 0) continue;
        }
        const int t = 2 * rd - 2 + wg, db = tail_block(gr, t);
#pragma unroll 1
        for (uint32_t n = 0; n < (1u << 20); n++)
            if (mbar_try(sbase + OFF_BAR + B_NRM + 8 * t, 0)) break;
        if (reinterpret_cast<const volatile uint32_t*>(ts)[77 + t]) {
            direct_block(x, wt, gamma, beta, out, reinterpret_cast<float*>(smem + OFF_DIR + wg * 8192), b, db, part, ts[76]);
            continue;
        }
        const int jh = g & 1, r0 = 4 * w;
        const int lim = min(250, kL - part * 250) - r0 - (g >> 1);
        float na[8], nb[8];
#pragma unroll
        for (int i = 0; i < 8; i += 2) {
            const float4 v = reinterpret_cast<const float4*>(smem + OFF_GB)[32 * t + 16 * jh + 2 * i + q];
            na[i] = v.x; nb[i] = v.y; na[i + 1] = v.z; nb[i + 1] = v.w;
        }
        __nv_bfloat16* o = out + ((size_t)b * kL + part * 250 + r0 + (g >> 1)) * 512 + 64 * db + 32 * jh + 8 * q;
        int l = r0 + ((lane >> 1) & 3);
        uint32_t ra = sbase + (t < 2 ? OFF_U0 : OFF_U1) + (t & 1) * 40960 + l * 128;
        const int cc = 4 * (lane & 1) + (lane >> 3);
        auto fetch = [&](uint32_t (&r)[4]) {
            asm volatile("ldmatrix.sync.aligned.m8n8.x4.shared.b16 {%0,%1,%2,%3}, [%4];"
                         : "=r"(r[0]), "=r"(r[1]), "=r"(r[2]), "=r"(r[3]) : "r"(ra + (((cc ^ l) & 7) << 4)) : "memory");
            const bool wrap = l >= kMO - 16;
            l += wrap ? 16 - kMO : 16;
            ra += wrap ? 2048 + 8192 - kMO * 128 : 2048;
        };
        auto gelu8 = [&](const uint32_t (&r)[4], uint32_t (&p)[4]) {
#pragma unroll
            for (int i = 0; i < 4; i++) {
                float lo, hi;
                asm("{\n.reg .b16 a, b;\nmov.b32 {a, b}, %2;\ncvt.f32.f16 %0, a;\ncvt.f32.f16 %1, b;\n}" : "=f"(lo), "=f"(hi) : "r"(r[i]));
                p[i] = pack_bf16(gelu_half(fmaf(lo, na[2 * i], nb[2 * i])), gelu_half(fmaf(hi, na[2 * i + 1], nb[2 * i + 1])));
            }
        };
        uint32_t r[2][4], rn[2][4];
        fetch(r[0]);
        fetch(r[1]);
#pragma unroll 1
        for (int i = 0; i < 256; i += 32) {
            fetch(rn[0]);
            fetch(rn[1]);
            uint32_t p0[4], p1[4];
            gelu8(r[0], p0);
            gelu8(r[1], p1);
            if (i < lim) stg128(o, p0[0], p0[1], p0[2], p0[3]);
            if (i + 16 < lim) stg128(o + 16 * 512, p1[0], p1[1], p1[2], p1[3]);
            o += 32 * 512;
#pragma unroll
            for (int k = 0; k < 4; k++) { r[0][k] = rn[0][k]; r[1][k] = rn[1][k]; }
        }
    }
}
__device__ __forceinline__ void channel_scales(uint32_t sbase, uint8_t* smem, uint8_t* sp, int lane) {
    volatile uint32_t* ts = reinterpret_cast<volatile uint32_t*>(smem + OFF_TS);
    const uint32_t gr = ts[64], bars = sbase + OFF_BAR;
#pragma unroll 1
    for (int t = 0; t < 4; t++) {
#pragma unroll 1
        for (uint32_t n = 0; n < (1u << 20); n++)
            if (mbar_try(bars + B_SUM + 8 * t, 0)) break;
        long long s[4];
#pragma unroll 1
        for (uint32_t n = 0; n < (1u << 19); n++) {
            const unsigned long long* p = part_sums(sp, gr >> 6, tail_block(gr, t), ts[76]) + 4 * lane;
#pragma unroll
            for (int i = 0; i < 4; i++) asm volatile("ld.relaxed.gpu.global.u64 %0, [%1];" : "=l"(s[i]) : "l"(p + i) : "memory");
            if (__all_sync(0xffffffffu, s[0] & s[1] & s[2] & s[3] & 32)) break;
        }
        const float sx = __uint_as_float(ts[74]), sw = __uint_as_float(ts[75]);
        bool bad = false;
#pragma unroll
        for (int i = 0; i < 2; i++) {
            const float mean = (float)(s[2 * i] >> 12) * (0x1p-21f / kL), sq = (float)(s[2 * i + 1] >> 12) * (0x1p-21f / kL);
            float2* gb = reinterpret_cast<float2*>(smem + OFF_GB) + 64 * t + 2 * lane + i;
            const float den = fmaxf(sq - mean * mean, 0.f) + 1e-5f * sx * sw * sx * sw, a = gb->x * rsqrtf(den);
            *gb = make_float2(0.5f * a, 0.5f * (gb->y - mean * a));
            bad |= ((s[2 * i] | s[2 * i + 1]) & 0xFC0) || !(den >= 0x1p-22f);
        }
        bad = __any_sync(0xffffffffu, bad);
        if (lane == 0) ts[77 + t] = bad;
        __syncwarp();
        if (lane == 0) mbar_arrive(bars + B_NRM + 8 * t);
    }
}

__device__ __forceinline__ void publish_tiles(uint8_t* sp, uint32_t bars, int cta, int wg) {
#pragma unroll 1
    for (int m = 0; m < 2; m++) {
        mbar_wait(bars + B_YS + 8 * (2 * m + wg), 0);
        asm volatile("fence.acq_rel.gpu;" ::: "memory");
        red_relaxed(y_flag(sp, (cta >> 1) & 1, 4 * m + 2 * (cta & 1) + wg));
    }
}

__global__ void __launch_bounds__(384, 1)
main_kernel(const __grid_constant__ CUtensorMap tmx, const __grid_constant__ CUtensorMap tmw0, const __grid_constant__ CUtensorMap tmw1,
            const __nv_bfloat16* __restrict__ x, const __nv_bfloat16* __restrict__ wt, const __nv_bfloat16* __restrict__ gamma,
            const __nv_bfloat16* __restrict__ beta, __nv_bfloat16* __restrict__ out) {
    extern __shared__ __align__(1024) uint8_t smem_raw[];
    const uint32_t sbase = smem_u32(smem_raw) & ~1023u;
    const uint32_t bars = sbase + OFF_BAR;
    const int tid = threadIdx.x, wg = __shfl_sync(0xffffffffu, tid >> 7, 0), lane = tid & 31;
    const int cta = blockIdx.x;
    volatile uint32_t* ts = reinterpret_cast<volatile uint32_t*>(smem_raw + OFF_TS);
    uint8_t* const sp = reinterpret_cast<uint8_t*>((reinterpret_cast<uintptr_t>(g_sp) + (2u << 20) - 1) & ~(uintptr_t)((2u << 20) - 1));
    const bool probing = (cta & 3) == 0 && lane == 0 && tid < 128 && (tid >= 64 || cta < 4 * NPAGES);
    unsigned* pw = reinterpret_cast<unsigned*>(sp + (tid < 64 ? ((cta >> 2) << 21) + ((tid & 32) ? 15 : 13) * 4096
                                                              : ((tid & 32) ? 0 : 14) * 4096 + (cta >> 2) * 128));
    unsigned pv = 0;
    if (probing) {
        stg128(pw, 0, 0, 0, 0);
        stg128(pw + 4, 0, 0, 0, 0);
        asm volatile("atom.relaxed.gpu.global.exch.b32 %0, [%1], %2;" : "=r"(pv) : "l"(pw), "r"(7) : "memory");
    }
    if (tid == 320) bar_setup<0, B_SIG>(bars);
    if (tid >= 256 && tid < 262) ts[68 + tid - 256] = tid < 260 ? 0xffffu : 0;
    if (tid == 383) asm volatile("griddepcontrol.launch_dependents;");
    __syncthreads();

    if (wg == 2) {
        asm volatile("setmaxnreg.dec.sync.aligned.u32 40;");
        const int role = (tid >> 5) & 3;
        if (role == 3) {
            unsigned v = 0;
#pragma unroll 1
            for (uint32_t n = 0; n < (1u << 15); n++) {
                asm volatile("ld.relaxed.gpu.global.u32 %0, [%1];" : "=r"(v) : "l"(&g_tsel[lane]) : "memory");
                if (__all_sync(0xffffffffu, v & 16)) break;
                __nanosleep(TSLEEP);
            }
            const uint32_t m1 = __ballot_sync(0xffffffffu, v & 8), below = (1u << lane) - 1;
            const int rank = (v & 8) ? 32 - __popc(m1) + __popc(m1 & below) : __popc(~m1 & below);
            ts[lane] = rank;
            ts[32 + rank] = lane;
            const uint32_t p0 = __ballot_sync(0xffffffffu, v & 1);
            if (lane == 0) ts[66] = p0;
            if (lane == (cta >> 2)) ts[64] = rank * 4 + (cta & 3);
            const int part = (m1 >> (cta >> 2)) & 1;
            __syncwarp();
            if (lane == 0) mbar_arrive(bars + B_TSEL);
            mbar_wait(bars + B_TSEL, 0);
            mbar_wait(bars + B_PUB, 0);
            int gc = 0;
            const int gend = lane == 0 ? 33 : lane == 1 ? 32 : 0;
#pragma unroll 1
            for (uint32_t n = 0; n < (1u << 16) && __any_sync(0xffffffffu, gc < gend); n++) {
                asm volatile("ld.relaxed.gpu.global.u32 %0, [%1];" : "=r"(v) : "l"(chunk_flag(sp, lane == 1, part, min(gc, 32 - (lane & 1)))) : "memory");
                if (gc < gend && v >= NCTA) {
                    asm volatile("fence.acquire.gpu;" ::: "memory");
                    mbar_arrive(bars + (lane == 0 ? B_RDY : B_GATE) + 8 * gc);
                    gc++;
                }
            }
            if (lane == 0) publish_tiles(sp, bars, cta, 1);
        } else if (role == 0) {
            const int b = (cta >> 1) & 1, dq = cta & 1;
            for (int v = 0; v < V0; v++) {
                mbar_wait(bars + B_EMPTY + 8 * (v % NST), ((v / NST) & 1) ^ 1);
                if (lane == 0) {
                    mbar_arrive(bars + B_FULL + 8 * (v % NST));
                    mbar_arrive(bars + B_FULL + 8 * (v % NST));
                }
            }
            mbar_wait(bars + B_TSEL, 0);
            const uint32_t gr = ts[64], grp = gr >> 6, idx = (gr >> 2) & 15, pmask = ts[66];
            const uint32_t n0 = idx * 4 + 2 * dq + ((lane & 1) ^ 1), r0 = lane < 3 ? idx * 4 + b : R_W + n0 / 3;
            const uint32_t base = (r0 << 16) + 4096 + ((lane < 3 ? lane : n0 % 3) << 14), step = (lane < 3 ? 64 : 22) << 16;
            uint32_t sels = 0;
            for (int i = 0; i < 12; i++) sels |= run_sel(r0 + i * (step >> 16), grp, pmask) << i;
            int ld = 0;
            const uint32_t bytes = lane == 2 ? XB - 16384 : 8192;
#pragma unroll 1
            for (int h = 0; h < 64; h++) {
                const int s = step_k(h), st = (h + V0) % NST;
                const bool newx = h < HEND ? !(h & 1) : h < HEND + 4;
                const uint32_t fb = bars + B_FULL + 8 * st;
                const uint32_t k = lane < 3 ? (s >> 1) % RX : (h + RW - 64 % RW) % RW, half = lane < 3 ? s & 1 : 0;
                const uint8_t* gsrc = sp + (base + k * step + (half << 17) + ((((sels >> k) ^ half) & 1) << 13));
                const uint32_t dst = sbase + (lane < 3 ? OFF_X + (s & 3) * XB + lane * 8192 : st * 8192 + (lane == 3 ? OFF_W0 : OFF_W1));
                auto landed = [&]() {
                    if (ld < h && mbar_test(bars + B_FULL + 8 * ((ld + V0) % NST), ((ld + V0) / NST) & 1)) {
                        if (!(ld & 1) && lane < 2) red_relaxed(chunk_flag(sp, 1, lane, ld >> 1));
                        ld++;
                    }
                };
#pragma unroll 1
                for (uint32_t n = 0; n < (1u << 19) && !mbar_test(bars + B_EMPTY + 8 * st, (((h + V0) / NST) & 1) ^ 1); n++) landed();
#pragma unroll 1
                for (uint32_t n = 0; n < (1u << 19) && ld <= h - NST; n++) landed();
                if (lane == 0) mbar_expect_tx(fb, newx ? 16384 + XB : 16384);
                if ((h & 1) || h == 0) {
#pragma unroll 1
                    for (uint32_t n = 0; n < (1u << 19) && !mbar_test(bars + B_RDY + 8 * ((h + 1) >> 1), 0); n++) landed();
                    asm volatile("fence.proxy.async.global;" ::: "memory");
                }
                __syncwarp();
                if (lane < 3 ? newx : lane < 5) bulk_g2s(dst, gsrc, bytes, fb);
            }
#pragma unroll 1
            for (; ld < 63; ld++) {
                mbar_wait(bars + B_FULL + 8 * ((ld + V0) % NST), ((ld + V0) / NST) & 1);
                if (!(ld & 1) && lane < 2) red_relaxed(chunk_flag(sp, 1, lane, ld >> 1));
            }
            const uint8_t* usrc = sp + y_unit(tail_block(gr, lane / 5), (gr & 31) * 5 + lane % 5, gr >> 6, pmask);
            const uint32_t udst = sbase + (lane < 10 ? OFF_U0 : OFF_U1 - 81920) + lane * 8192, ubar = bars + B_UNIT + 8 * lane;
            if (lane < 20) mbar_expect_tx(ubar, 8192);
            auto tail_loads = [&](int u0, int u1) {
                if (lane >= u0 && lane < u1) bulk_g2s(udst, usrc, 8192, ubar);
                __syncwarp();
            };
            tail_poll(sp, gr, 0);
            mbar_wait(bars + B_T2, 0);
            tail_loads(0, 5);
            tail_poll(sp, gr, 1);
            tail_loads(5, 8);
            mbar_wait(bars + B_YS + 16, 0);
            tail_loads(8, 10);
            mbar_wait(bars + B_T2 + 8, 0);
            if (lane == 0) {
                mbar_expect_tx(bars + B_C1, 2560);
                corr_load(sbase, gr, 2, bars + B_C1);
                corr_load(sbase, gr, 3, bars + B_C1);
            }
            tail_poll(sp, gr, 2);
            tail_loads(10, 15);
            tail_poll(sp, gr, 3);
            tail_loads(15, 20);
            mbar_wait(bars + B_GATE + 8 * 31, 0);
            unsigned exits = 0;
            if (lane == 0) exits = atomicAdd(&g_exit, 1);
            if (__shfl_sync(0xffffffffu, exits, 0) == NCTA - 1) {
                for (int i = 0; i < 4; i++) *chunk_flag(sp, i >> 1, i & 1, lane) = 0;
                if (lane < 2) *chunk_flag(sp, 0, lane, 32) = 0;
                g_tsel[lane] = 0;
                if (lane < 16) *y_flag(sp, lane >> 3, lane & 7) = 0;
                if (lane == 0) { g_exit = 0; g_epoch = ts[76]; }
            }
        } else if (role == 1) {
            auto raw_load = [&](int r, int h, uint32_t gr, uint32_t dst, uint32_t bar) {
                if (r >= 0) {
                    const int u = r * NCTA + cta, i = u % XPC, b = i >= kNT;
                    tma3d(dst, &tmx, u / XPC * 64, (i - b * kNT) * kMO, b, bar);
                } else if (h >= 0) {
                    const int c = 32 * step_k(h) + ((gr >> 1) & 30);
                    tma3d_ef(dst, c < 512 ? &tmw0 : &tmw1, step_m(h) * 256 + (gr & 3) * 64, c & 511, 0, bar);
                }
            };
            uint32_t gr;
            {
                const int v = lane >> 1, r = v < V0 ? x_round(v, lane & 1) : -1, h = v < V0 ? w_step(v, lane & 1) : -1;
                const uint32_t dst = pre_slot(sbase, v, lane & 1), bar = bars + B_PRE + 8 * lane;
                if (r >= 0 || h >= 0) mbar_expect_tx(bar, r >= 0 ? 8192 : 4096);
                if (v < PRE1) raw_load(r, -1, 0, dst, bar);
                mbar_wait(bars + B_TSEL, 0);
                gr = ts[64];
                raw_load(-1, h, gr, dst, bar);
                if (v >= PRE1) raw_load(r, -1, 0, dst, bar);
                __syncwarp();
            }
            mbar_wait(bars + B_PUB, 0);
#pragma unroll 1
            for (int v = V0; v < V0 + 64; v++) {
                mbar_wait(bars + B_EMPTY + 8 * (v % NST), ((v / NST) & 1) ^ 1);
                __syncwarp();
                const int r = lane < 2 ? x_round(v, lane) : -1, h = lane < 2 ? w_step(v, lane) : -1;
                const uint32_t fb = bars + B_FULL + 8 * (v % NST);
                const uint32_t bytes = __reduce_add_sync(0xffffffffu, r >= 0 ? 8192 : h >= 0 ? 4096 : 0);
                if (lane == 0) mbar_expect_tx(fb, bytes);
                __syncwarp();
                raw_load(r, h, gr, raw_slot(sbase, v, lane), fb);
                if (v >= 20 && v < 40) {
                    const int t = (v - 20) / 5, i = (v - 20) % 5 * 32 + lane, db = 4 * (t >> 1) + 2 * (cta & 1) + (t & 1);
                    ts[(OFF_YT - OFF_TS) / 4 + t * kNT + i] = y_unit(db, i, (cta >> 1) & 1, ts[66]);
                }
                if (v == 66 && lane == 0) {
#pragma unroll 1
                    for (uint32_t n = 0; n < (1u << 15); n++) {
                        unsigned c0, c1;
                        asm volatile("ld.relaxed.gpu.global.u32 %0, [%1];" : "=r"(c0) : "l"(&g_cready[(gr >> 6) * 64]) : "memory");
                        asm volatile("ld.relaxed.gpu.global.u32 %0, [%1];" : "=r"(c1) : "l"(&g_cready[(gr >> 6) * 64 + 32]) : "memory");
                        if (c0 == ts[76] && c1 == ts[76]) break;
                        __nanosleep(500);
                    }
                    asm volatile("fence.acquire.gpu;" ::: "memory");
                    asm volatile("fence.proxy.async.global;" ::: "memory");
                    mbar_expect_tx(bars + B_FTAB, 8192 + 2560);
                    bulk_g2s(sbase + OFF_F, g_tab.inv, 8192, bars + B_FTAB);
                    for (int t = 0; t < 2; t++) {
                        corr_load(sbase, gr, t, bars + B_FTAB);
                        asm volatile("cp.async.bulk.prefetch.L2.global [%0], 1280;" ::"l"(corr_src(gr, 2 + t)) : "memory");
                    }
                }
            }
            channel_scales(sbase, smem_raw, sp, lane);
        } else {
            uint32_t epoch;
            if (lane == 0) {
                bar_setup<B_SIG, B_END>(bars);
                mbar_arrive(bars + B_TSEL);
            }
            asm volatile("ld.relaxed.gpu.global.u32 %0, [%1];" : "=r"(epoch) : "l"(&g_epoch) : "memory");
            mbar_wait(bars + B_TSEL, 0);
            const uint32_t gr = ts[64];
#pragma unroll
            for (int i = lane; i < 256; i += 32) {
                const int d = 64 * tail_block(gr, i >> 6) + (i & 33) + 8 * ((i >> 1) & 3) + 2 * ((i >> 3) & 3);
                ts[(OFF_GB - OFF_TS) / 4 + 2 * i] = (uint32_t)__bfloat16_as_ushort(gamma[d]) << 16;
                ts[(OFF_GB - OFF_TS) / 4 + 2 * i + 1] = (uint32_t)__bfloat16_as_ushort(beta[d]) << 16;
            }
            if (lane == 0) ts[76] = epoch + 1;
            if (cta < 32) stg128(part_sums(sp, cta >> 4, (cta >> 1) & 7, epoch) + (cta & 1) * 64 + 2 * lane, 0, 0, 0, 0);
            __syncwarp();
            if (lane) return;
#pragma unroll 1
            for (int gc = 0; gc < 33;) {
                mbar_wait(bars + B_SIG + 8 * gc, 0);
                if (gc < MERGE) mbar_wait(bars + B_SIG + 8 * MERGE, 0);
                int ge = gc + 1;
                while (ge < 33 && mbar_test(bars + B_SIG + 8 * ge, 0)) ge++;
                asm volatile("fence.acq_rel.gpu;" ::: "memory");
                for (; gc < ge; gc++) {
                    red_relaxed(chunk_flag(sp, 0, 0, gc));
                    red_relaxed(chunk_flag(sp, 0, 1, gc));
                    if (gc == 0) mbar_arrive(bars + B_PUB);
                }
            }
            publish_tiles(sp, bars, cta, 0);
        }
    } else {
        asm volatile("setmaxnreg.inc.sync.aligned.u32 232;");
        uint4 fx[2];
#pragma unroll
        for (int i = 0; i < 2; i++) fx[i] = __ldg(reinterpret_cast<const uint4*>(g_tab.fx) + 2 * (tid & 127) + i);
        const uint4 ft = __ldg(reinterpret_cast<const uint4*>(g_tab.tap) + (tid & 127));
        if (wg == 1) {
            uint4 sm[8];
#pragma unroll
            for (int j = 0; j < 4; j++) {
                const int r = 2 * j + ((tid >> 6) & 1);
                sm[j] = __ldg(reinterpret_cast<const uint4*>(x) + ((r >> 2) * kRows + 1000 + 2000 * (r & 3)) * 128 + (((j + r) & 1) << 6) + (tid & 63));
                sm[4 + j] = __ldg(reinterpret_cast<const uint4*>(wt) + (4 * r * 512 + 67 * r + 7) * 64 + (tid & 63));
            }
#pragma unroll
            for (int k = 0; k < 2; k++) {
                uint32_t mx = 0;
#pragma unroll
                for (int j = 4 * k; j < 4 * k + 4; j++)
                    mx = __vmaxu2(__vmaxu2(mx, __vmaxu2(sm[j].x & 0x7FFF7FFFu, sm[j].y & 0x7FFF7FFFu)), __vmaxu2(sm[j].z & 0x7FFF7FFFu, sm[j].w & 0x7FFF7FFFu));
                mx = __reduce_max_sync(0xffffffffu, max(mx & 0xFFFFu, mx >> 16));
                if (lane == 0) atomicMax(const_cast<uint32_t*>(ts) + 72 + k, mx);
            }
        }
        if ((cta & 3) == 0) {
            if (probing) {
                const int w = tid >> 5;
                unsigned best = 0xffffu;
#pragma unroll 1
                for (int r = 0; r < 6; r++) {
                    unsigned t0, t1;
                    asm volatile("{\n.reg .pred p;\nsetp.eq.u32 p, %1, 0xffffffff;\nmov.u32 %0, 0;\n@!p mov.u32 %0, %%clock;\n}"
                                 : "=r"(t0) : "r"(pv) : "memory");
                    asm volatile("atom.relaxed.gpu.global.exch.b32 %0, [%1], %2;" : "=r"(pv) : "l"(pw), "r"(r) : "memory");
                    asm volatile("{\n.reg .pred p;\nsetp.eq.u32 p, %1, 0xffffffff;\nmov.u32 %0, 0;\n@!p mov.u32 %0, %%clock;\n}"
                                 : "=r"(t1) : "r"(pv) : "memory");
                    ts[68 + w] = best = min(best, t1 - t0);
                    const unsigned other = ts[68 + (w ^ 1)];
                    if (min(best, other) < PROBE_NEAR && max(best, other) > PROBE_NEAR) break;
                }
            }
            if (wg == 0) {
                named_bar(2, 128);
                if (tid == 0) {
                    const uint32_t part = ts[71] < ts[70];
                    const uint32_t v = 16 | (part << 3) | ((ts[69] < ts[68]) ^ part);
                    asm volatile("st.relaxed.gpu.global.u32 [%0], %1;" ::"l"(&g_tsel[cta >> 2]), "r"(v) : "memory");
                }
            }
        }
        if (tid < 2 * (V0 + 65)) ts[(OFF_PLAN - OFF_TS) / 4 + tid] = plan_word(tid >> 1, tid & 1, cta);
        if (wg == 1) sts128(sbase + OFF_TMP + 16 * (tid & 127), ft.x, ft.y, ft.z, ft.w);
        named_bar(1, 256);
        const uint32_t ex = min(max(251 - (int)(ts[72] >> 7), 8), 187), ew = min(max(251 - (int)(ts[73] >> 7), 8), 187);
        if (tid == 0) { ts[74] = ex << 23; ts[75] = ew << 23; }
        const int t = tid & 127;
        Xf f;
        f.sbase = sbase; f.lane = lane; f.dw = desc_lo(sbase + (wg ? OFF_W1 : OFF_W0));
        {
            const int w = t >> 5;
            const uint32_t nw = (8 * (w & 1) + (lane >> 2)) * 4 + (cta & 3), rw = R_W + nw / 3;
            f.pw = sp + (rw << 16) + 4096 + ((nw % 3) << 14) + (w >> 1) * 4096;
            f.cw = (lane & 7) << 4;
            for (int i = 0; i < RW; i++) f.cw |= run_sel(rw + i * 22, 0, 0) << (8 + i);
#pragma unroll
            for (int i = 0; i < 2; i++) {
                f.fx[i][0] = mul_bf16x2(fx[i].x, ex * 0x800080u);
                f.fx[i][1] = mul_bf16x2(fx[i].y, ex * 0x800080u);
                f.fx[i][2] = mul_bf16x2(fx[i].z, ex * 0x800080u);
                f.fx[i][3] = mul_bf16x2(fx[i].w, ex * 0x800080u);
            }
            mbar_wait(bars + B_FULL + 8 * (NST - 1), 0);
            mbar_wait(bars + B_TSEL, 0);
            const uint32_t gr = ts[64], pmask = ts[66];
            f.cx = 0;
#pragma unroll
            for (int i = 0; i < 2; i++) {
                const int ps = 4 * w + (lane >> 3), pp = (lane >> 2) & 1;
                const uint32_t rx = ts[ps == 0 ? 16 * pp : i ? 32 - ps : ps];
                f.px[i] = sp + ((rx & 15) << 18) + 4096;
                f.cx |= ((((lane & 3) + 4 * (ps == 0 ? i : pp)) << 4) | ((((pmask >> ((rx >> 3) & 1)) ^ -(((rx >> 1) ^ (rx >> 4)) & 1)) & 0x55) << 8)) << (16 * i);
            }
#pragma unroll
            for (int i = 0; i < RW; i++) f.cw ^= (((pmask >> ((rw + i * 22) >> 5)) ^ (gr >> 6)) & 1) << (8 + i);
            const uint32_t row = ((gr & 12) << 1) | ((gr & 48) >> 3);
            f.pw += row * 128;
            f.cw ^= (row & 7) << 4;
            const uint32_t s = ts[32 + (gr >> 6) * 16 + 8 * (w & 1) + (lane >> 2)], ga = sbase + OFF_TMP + (16 * (s >> 3) + 8 * (w >> 1) + (s & 7)) * 32 + (lane & 3) * 4;
#pragma unroll
            for (int i = 0; i < 4; i += 2) {
                asm volatile("ld.shared.u32 %0, [%1];" : "=r"(f.g[i]) : "r"(ga + i * 8) : "memory");
                f.g[i] = f.g[i + 1] = mul_bf16x2(f.g[i], ew * 0x800080u);
            }
        }
        {
            float at[32];
#pragma unroll 1
            for (uint32_t v = 0; v < V0; v++) {
                const uint32_t e = plan_load(f, v, wg), raw = pre_slot(sbase, v, wg);
                if (v >= NST) mbar_wait(bars + B_FULL + 8 * (v % NST), (v / NST) & 1);
                if (e & 6) mbar_wait(bars + B_PRE + 16 * v + 8 * wg, 0);
                if (v == PAUSE) mbar_wait(bars + B_PUB, 0);
                wg_fence();
                if ((e & 6) == 2) {
                    unit_mma<false>(at, f, raw);
                    wg_wait<0>();
                    unit_store<false>(at, f, e);
                } else if (e & 4) {
                    unit_mma<true>(at, f, raw);
                    wg_wait<0>();
                    unit_store<true>(at, f, e);
                }
                if (lane == 0) mbar_arrive(bars + B_EMPTY + 8 * (v % NST));
                unit_done(f, e, v);
            }
        }
        const int slot = cta >> 2;
        f.e = plan_load(f, V0, wg);
        uint32_t a0[40], a1[40], b0[40], b1[40];
#pragma unroll
        for (int i = 0; i < 40; i++) a0[i] = a1[i] = b0[i] = b1[i] = 0;
        if (slot == 0) gemm_main<true>(a0, a1, b0, b1, f, wg);
        else gemm_main<false>(a0, a1, b0, b1, f, wg);
        const uint32_t gr = __shfl_sync(0xffffffffu, ts[64], 0);
        const float sx = __uint_as_float(ts[74]), sw = __uint_as_float(ts[75]);
        uint32_t wr[2][4][4];
        w_fetch(wr[0], f, V0 + HEND);
#pragma unroll 1
        for (int m = 0; m < 2; m++) {
            if (slot == 0) gemm_last<true>(a0, a1, wr, f, wg, m);
            else gemm_last<false>(a0, a1, wr, f, wg, m);
            reg_fence(a0);
            reg_fence(a1);
            const int wsw = gr & 4;
            mbar_wait(bars + B_GATE + 8 * y_gate(2 * m + wg), 0);
            if (m) mbar_wait(bars + B_FTAB, 0);
            const uint32_t ytab = sbase + OFF_YT + (m * 2 + wg) * (kNT * 4);
            store_tile(a0, a1, b0, b1, wr[0], f, m == 0, sbase + OFF_STG + wg * 16384, t, wg, sp, slot, ytab, wsw);
            __syncwarp();
            if (lane == 0) mbar_arrive(bars + B_YS + 8 * (2 * m + wg));
        }
        tail_phase(sbase, smem_raw, sp, wg, gr, sx, sw, x, wt, gamma, beta, out);
    }
}

constexpr int C_STAGE = 32768 + 2 * XB, C_SMEM = 3 * C_STAGE + 64;
__global__ void __launch_bounds__(256, 1) corr_kernel(const __grid_constant__ CUtensorMap tmx, const __grid_constant__ CUtensorMap tmw) {
    extern __shared__ __align__(1024) uint8_t smem_raw[];
    const uint32_t sbase = smem_u32(smem_raw) & ~1023u, bars = sbase + 3 * C_STAGE;
    const int tid = threadIdx.x, wg = __shfl_sync(0xffffffffu, tid >> 7, 0), b = blockIdx.x >> 1, dh = blockIdx.x & 1;
    auto load = [&](int k) {
        const uint32_t st = sbase + (k % 3) * C_STAGE, bar = bars + 8 * (k % 3);
        mbar_expect_tx(bar, C_STAGE);
        for (int i = 0; i < 4; i++) tma2d(st + i * 8192, &tmw, 256 * dh + 64 * i, 64 * k, bar);
        tma4d(st + 32768, &tmx, 64 * k, 64 - kMO, 1, b, bar);
        tma4d(st + 32768 + XB, &tmx, 64 * k, 0, 0, b, bar);
    };
    uint32_t epoch = 0;
    if (tid == 0) {
        for (int i = 0; i < 3; i++) mbar_init(bars + 8 * i, 1);
        fence_mbar_init();
        fence_proxy_async_smem();
        for (int k = 0; k < 3; k++) load(k);
        asm volatile("ld.relaxed.gpu.global.u32 %0, [%1];" : "=r"(epoch) : "l"(&g_epoch) : "memory");
    }
    __syncthreads();
    float a[2][80];
#pragma unroll
    for (int i = 0; i < 80; i++) a[0][i] = a[1][i] = 0.f;
#pragma unroll 1
    for (int k = 0; k < 8; k++) {
        const uint32_t dA = desc_lo(sbase + (k % 3) * C_STAGE + wg * 16384), dB = desc_lo(sbase + (k % 3) * C_STAGE + 32768);
        mbar_wait(bars + 8 * (k % 3), (k / 3) & 1);
        wg_fence();
#pragma unroll
        for (int i = 0; i < 8; i++) {
            wgmma_n160_f<1>(a[i & 1], dA + (i & 1) * 512 + (i >> 1) * 128, dB + (i >> 1) * 2);
            wgmma_n160_f<-1>(a[i & 1], dA + (i & 1) * 512 + (i >> 1) * 128, dB + XB / 16 + (i >> 1) * 2);
        }
        wg_commit();
        wg_wait<0>();
        __syncthreads();
        if (tid == 0 && k + 3 < 8) load(k + 3);
    }
    reg_fence(a[0]);
    reg_fence(a[1]);
    const int w = (tid >> 5) & 3, g = (tid & 31) >> 2, q = tid & 3;
    float* stage = reinterpret_cast<float*>(smem_raw);
#pragma unroll
    for (int i = 0; i < 160; i++) {
        const int m = i / 80, j = i % 80, d = 16 * w + 8 * ((j >> 1) & 1) + g;
        stage[((2 * wg + m) * kNT + 8 * (j >> 2) + 2 * q + (j & 1)) * 64 + (d & 33) + 8 * ((d >> 1) & 3) + 2 * ((d >> 3) & 3)] = a[m][j];
    }
    __syncthreads();
    for (int i = tid; i < 4 * kNT * 16; i += 256)
        reinterpret_cast<float4*>(g_corr)[(b * 8 + 4 * dh) * kNT * 16 + i] = reinterpret_cast<const float4*>(stage)[i];
    __syncthreads();
    if (tid == 0) {
        asm volatile("fence.acq_rel.gpu;" ::: "memory");
        asm volatile("st.relaxed.gpu.global.u32 [%0], %1;" ::"l"(&g_cready[blockIdx.x * 32]), "r"(epoch + 1) : "memory");
    }
}

__global__ void __launch_bounds__(256) plain_conv(const __nv_bfloat16* __restrict__ x, const __nv_bfloat16* __restrict__ w) {
    __shared__ float xs[64][17], ws[16][65];
    float* h = g_direct;
    const int b = blockIdx.z, l0 = blockIdx.x * 64, d0 = blockIdx.y * 64, tx = threadIdx.x & 15, ty = threadIdx.x >> 4;
    float acc[4][4] = {};
    for (int k0 = 0; k0 < 31 * 512; k0 += 16) {
        for (int i = threadIdx.x; i < 1024; i += 256) {
            const int l = min(l0 + (i >> 4), kL - 1);
            xs[i >> 4][i & 15] = __bfloat162float(x[((size_t)b * kRows + l) * 1024 + k0 + (i & 15)]);
            ws[i >> 6][i & 63] = __bfloat162float(w[(size_t)(k0 + (i >> 6)) * 512 + d0 + (i & 63)]);
        }
        __syncthreads();
        for (int k = 0; k < 16; k++)
            for (int i = 0; i < 4; i++)
                for (int j = 0; j < 4; j++) acc[i][j] = fmaf(xs[ty * 4 + i][k], ws[k][tx * 4 + j], acc[i][j]);
        __syncthreads();
    }
    for (int i = 0; i < 4; i++)
        for (int j = 0; j < 4; j++)
            if (l0 + ty * 4 + i < kL) h[((size_t)b * kL + l0 + ty * 4 + i) * 512 + d0 + tx * 4 + j] = acc[i][j];
}
__global__ void __launch_bounds__(256) plain_norm(const __nv_bfloat16* __restrict__ gamma, const __nv_bfloat16* __restrict__ beta,
                                                  __nv_bfloat16* __restrict__ out) {
    __shared__ float s1[8][32], s2[8][32];
    const int c = threadIdx.x & 31, r = threadIdx.x >> 5, d = blockIdx.x * 32 + c;
    const float* h = g_direct + (size_t)blockIdx.y * kL * 512 + d;
    float a = 0.f, q = 0.f;
    for (int l = r; l < kL; l += 8) { const float v = h[(size_t)l * 512]; a += v; q = fmaf(v, v, q); }
    s1[r][c] = a; s2[r][c] = q;
    __syncthreads();
    a = q = 0.f;
    for (int i = 0; i < 8; i++) { a += s1[i][c]; q += s2[i][c]; }
    const float mean = a * (1.0f / kL), sc = __bfloat162float(gamma[d]) / sqrtf(fmaxf(q * (1.0f / kL) - mean * mean, 0.f) + 1e-5f);
    const float sh = __bfloat162float(beta[d]) - mean * sc;
    for (int l = r; l < kL; l += 8)
        out[((size_t)blockIdx.y * kL + l) * 512 + d] = __float2bfloat16(gelu_half(0.5f * fmaf(h[(size_t)l * 512], sc, sh)));
}

typedef CUresult (*EncodeTiledFn)(CUtensorMap*, CUtensorMapDataType, cuuint32_t, void*, const cuuint64_t*, const cuuint64_t*,
                                  const cuuint32_t*, const cuuint32_t*, CUtensorMapInterleave, CUtensorMapSwizzle,
                                  CUtensorMapL2promotion, CUtensorMapFloatOOBfill);

void encode(EncodeTiledFn fn, CUtensorMap* tm, const void* ptr, int rank, const cuuint64_t* dims, const cuuint64_t* strides,
            const cuuint32_t* box, CUtensorMapL2promotion promo, CUtensorMapSwizzle swz = CU_TENSOR_MAP_SWIZZLE_128B) {
    const cuuint32_t es[5] = {1, 1, 1, 1, 1};
    fn(tm, CU_TENSOR_MAP_DATA_TYPE_BFLOAT16, rank, const_cast<void*>(ptr), dims, strides, box, es, CU_TENSOR_MAP_INTERLEAVE_NONE,
       swz, promo, CU_TENSOR_MAP_FLOAT_OOB_FILL_NONE);
}

}

extern "C" void kernel_launch(void* const* d_in, const int* in_sizes, int n_in, void* d_out, int out_size) {
    const __nv_bfloat16* x = (const __nv_bfloat16*)d_in[0];
    const __nv_bfloat16* w = (const __nv_bfloat16*)d_in[1];
    const __nv_bfloat16* gamma = (const __nv_bfloat16*)d_in[2];
    const __nv_bfloat16* beta = (const __nv_bfloat16*)d_in[3];
    static EncodeTiledFn enc = nullptr;
    static int resident = 0;
    if (!enc) {
        void* fn = nullptr;
        cudaDriverEntryPointQueryResult qr;
        cudaGetDriverEntryPoint("cuTensorMapEncodeTiled", &fn, cudaEnableDefault, &qr);
        enc = (EncodeTiledFn)fn;
        cudaFuncSetAttribute(main_kernel, cudaFuncAttributeMaxDynamicSharedMemorySize, MAIN_SMEM);
        cudaFuncSetAttribute(corr_kernel, cudaFuncAttributeMaxDynamicSharedMemorySize, C_SMEM);
        int dev = 0, per_sm = 0;
        cudaGetDevice(&dev);
        cudaDeviceGetAttribute(&resident, cudaDevAttrMultiProcessorCount, dev);
        cudaOccupancyMaxActiveBlocksPerMultiprocessor(&per_sm, main_kernel, 384, MAIN_SMEM);
        resident *= per_sm;
    }
    if (resident < NCTA + 4) {
        plain_conv<<<dim3((kL + 63) / 64, 8, 2), 256>>>(x, w);
        plain_norm<<<dim3(16, 2), 256>>>(gamma, beta, (__nv_bfloat16*)d_out);
        return;
    }
    CUtensorMap tmx, tmw0, tmw1, tmcx, tmcw;
    {
        const cuuint64_t dims[3] = {1024, kRows, 2}, strides[2] = {2048, (cuuint64_t)kRows * 2048};
        const cuuint32_t box[3] = {64, 64, 1};
        encode(enc, &tmx, x, 3, dims, strides, box, CU_TENSOR_MAP_L2_PROMOTION_L2_128B);
    }
    {
        const cuuint64_t dims0[3] = {512, 512, 16}, dims1[3] = {512, 512, 15}, strides[2] = {1024, 2 * 512 * 512 * 2};
        const cuuint32_t box[3] = {64, 2, 16};
        encode(enc, &tmw0, w, 3, dims0, strides, box, CU_TENSOR_MAP_L2_PROMOTION_L2_128B);
        encode(enc, &tmw1, w + 512 * 512, 3, dims1, strides, box, CU_TENSOR_MAP_L2_PROMOTION_L2_128B);
    }
    {
        const cuuint64_t dims[4] = {512, kMO, kNT, 2}, strides[3] = {2048, kMO * 2048, (cuuint64_t)kRows * 2048};
        const cuuint32_t box[4] = {64, 1, kNT, 1};
        encode(enc, &tmcx, x, 4, dims, strides, box, CU_TENSOR_MAP_L2_PROMOTION_L2_128B);
        const cuuint64_t dimw[2] = {512, 512}, stridew[1] = {1024};
        const cuuint32_t boxw[2] = {64, 64};
        encode(enc, &tmcw, w + 30 * 512 * 512, 2, dimw, stridew, boxw, CU_TENSOR_MAP_L2_PROMOTION_L2_128B);
    }
    main_kernel<<<NCTA, 384, MAIN_SMEM>>>(tmx, tmw0, tmw1, x, w, gamma, beta, (__nv_bfloat16*)d_out);
    cudaLaunchConfig_t cfg = {};
    cudaLaunchAttribute at[1];
    cfg.gridDim = 4;
    cfg.blockDim = 256;
    cfg.dynamicSmemBytes = C_SMEM;
    at[0].id = cudaLaunchAttributeProgrammaticStreamSerialization;
    at[0].val.programmaticStreamSerializationAllowed = 1;
    cfg.attrs = at;
    cfg.numAttrs = 1;
    cudaLaunchKernelEx(&cfg, corr_kernel, tmcx, tmcw);
}
```
